```python
import torch

def _softmax(x, axis=-1):
    return torch.softmax(x, dim=axis)
def _gelu(x):
    return torch.nn.functional.gelu(x, approximate="tanh")
def _silu(x):
    return torch.nn.functional.silu(x)
def _sigmoid(x):
    return torch.sigmoid(x)
def _layernorm(x, axis=-1, eps=1e-5):
    m = x.mean(dim=axis, keepdim=True)
    v = x.var(dim=axis, keepdim=True, unbiased=False)
    return (x - m) / torch.sqrt(v + eps)
def _scatter_add(tgt, idx, src, axis=0):
    return tgt.clone().index_add_(axis, idx, src)
def _segment_sum(src, seg, n):
    out = torch.zeros((n,) + src.shape[1:], dtype=src.dtype)
    return out.index_add_(0, seg, src)
def _pad(x, pw):
    flat = tuple(v for pair in reversed(pw) for v in pair)
    return torch.nn.functional.pad(x, flat)

kernel_name = 'recurrent_scan__linear_kernel_hedgehog__moe_arch_mod__prompt'

def setup_inputs():

    _w = (lambda a: (lambda t: t.to(torch.bfloat16) if t.is_floating_point() else t)(torch.as_tensor(a)))
    def _A_setup():
        B, S, D, H = 1, 2048, 1024, 32
        Dh = D // H
        return {
            "x": _w((lambda *s: torch.randn(*s, dtype=torch.bfloat16) * 0.05)(B, S, D)),
            "wqkv": _w((lambda *s: torch.randn(*s, dtype=torch.bfloat16) * 0.2)(D, 3 * D)),
            "w_phi": _w((lambda *s: torch.randn(*s, dtype=torch.bfloat16) * 0.2)(H, Dh, Dh) * (Dh ** -0.5)),
            "wo": _w((lambda *s: torch.randn(*s, dtype=torch.bfloat16) * 0.05)(D, D)),
        }
    _A_in = _A_setup()

    def _B_setup():
        B, S, D, F, C = 1, 2048, 1024, 3584, 1
        return {
            "x": _w((lambda *s: torch.randn(*s, dtype=torch.bfloat16) * 0.05)(B, S, D)),
            "w_r": _w((lambda *s: torch.randn(*s, dtype=torch.bfloat16) * 0.05)(D)),
            "w_gate": _w((lambda *s: torch.randn(*s, dtype=torch.bfloat16) * 0.05)(D, F)),
            "w_up": _w((lambda *s: torch.randn(*s, dtype=torch.bfloat16) * 0.05)(D, F)),
            "w_down": _w((lambda *s: torch.randn(*s, dtype=torch.bfloat16) * 0.05)(F, D)),
        }
    _B_in = _B_setup()

    return {
        "A_x": _A_in["x"],
        "A_wqkv": _A_in["wqkv"],
        "A_w_phi": _A_in["w_phi"],
        "A_wo": _A_in["wo"],
        "B_x": _B_in["x"],
        "B_w_r": _B_in["w_r"],
        "B_w_gate": _B_in["w_gate"],
        "B_w_up": _B_in["w_up"],
        "B_w_down": _B_in["w_down"],
    }

def reference(A_x, A_wqkv, A_w_phi, A_wo, B_x, B_w_r, B_w_gate, B_w_up, B_w_down):
    def _A_ref(x, wqkv, w_phi, wo):
        B, S, D = x.shape
        H = 32; Dh = D // H
        qkv = (lambda x, *d: x.permute(*d))((x @ wqkv).reshape(B, S, 3, H, Dh), 2, 0, 3, 1, 4)
        q, k, v = qkv[0], qkv[1], qkv[2]
        pq = torch.einsum("bhsd,hdf->bhsf", q, w_phi)
        pk = torch.einsum("bhsd,hdf->bhsf", k, w_phi)
        phi_q = torch.concatenate([_softmax(pq, axis=-1), _softmax(-pq, axis=-1)], axis=-1)
        phi_k = torch.concatenate([_softmax(pk, axis=-1), _softmax(-pk, axis=-1)], axis=-1)
        kv = torch.einsum("bhsf,bhsd->bhfd", phi_k, v)
        z  = torch.einsum("bhsf->bhf", phi_k)
        num = torch.einsum("bhqf,bhfd->bhqd", phi_q, kv)
        den = torch.einsum("bhqf,bhf->bhq", phi_q, z)[..., None] + 1e-6
        o = num / den
        return (lambda x, *d: x.permute(*d))(o, 0, 2, 1, 3).reshape(B, S, D) @ wo

    def _B_ref(x, w_r, w_gate, w_up, w_down):
        B, S, D = x.shape
        C = 1
        r = x @ w_r
        idx = torch.argsort(-r, axis=-1)[:, :C]
        idx_e = (lambda x, n, axis: torch.repeat_interleave(x, n, dim=axis))(idx.reshape(B, C, 1), D, axis=2)
        x_sel = (lambda x, i, axis: torch.take_along_dim(x, i, dim=axis))(x, idx_e, axis=1)
        g = _silu(x_sel @ w_gate)
        u = x_sel @ w_up
        y = (g * u) @ w_down
        r_sel = _sigmoid((lambda x, i, axis: torch.take_along_dim(x, i, dim=axis))(r, idx, axis=1))
        y = y * r_sel.reshape(B, C, 1)
        b_off = (torch.arange(B) * S).reshape(B, 1)
        flat_idx = (idx + b_off).reshape(B * C)
        zero = (x * 0.0).reshape(B * S, D)
        upd = _scatter_add(zero, flat_idx, y.reshape(B * C, D), axis=0)
        return x + upd.reshape(B, S, D)

    x = A_x
    xn = _layernorm(x, axis=-1)
    s = _A_ref(xn, A_wqkv, A_w_phi, A_wo)
    g = _silu(_B_ref(xn, B_w_r, B_w_gate, B_w_up, B_w_down))
    return x + s * g
```

```cpp
#include <cuda_runtime.h>
#include <cuda_bf16.h>
#include <cuda.h>
#include <stdint.h>

namespace {

constexpr int S_ = 2048, D_ = 1024, F_ = 3584;
constexpr int NCTA = 128, NTHREADS = 384;
#define POLL_NS 100
#define OREL 1
#define OSTAG 12
#define OARR 2
#define NG2 4
#define NGU 24
#define GSPLIT 1
#define GSPLIT2 2
#define GST 3

constexpr int STAGE = 57344;
constexpr int SM_PHI = 0;
constexpr int SM_V = 131072;
constexpr int SM_AX = 172032;
constexpr int SM_BX = 176128;
constexpr int SM_SP = 172032;
constexpr int SM_FB = 180224;
constexpr int SM_XS = 221184;
constexpr int SM_KVOP = 172032;
constexpr int SM_MD = 223232;
constexpr int SM_RS = 224256;
constexpr int SM_Y = 225280;
constexpr int SM_GU = 225536;
constexpr int SM_MISC = 226688;
constexpr int SM_H = 179200;
constexpr int SM_BARS = 226816;
constexpr int SM_WPHI = 227840;
constexpr int SM_TOTAL = 232448;

constexpr int B_FULL = 0, B_EMPTY = 3, B_OF = 6, B_SD = 22, B_O = 33, B_PHI = 35, B_T = 37, B_WPHI = 38, B_Y = 39, B_KV = 40, B_LN = 42, B_S1 = 43, B_FF = 44, B_X = 54, B_C1 = 55, B_DN = 56, B_GT = 58, B_COUNT = 59, B_XR = 59, B_S0 = 60;
constexpr int NB_KV = 1, NB_FFN = 2, NB_AUX = 3, NB_DN = 4, NB_STAG = 5;
__device__ __forceinline__ int o_slot(int i) { const int r = i % 5; return r == 4 ? 10 : r; }
__device__ __forceinline__ int wo_slot(int i) { const int r = i % 7; return r == 6 ? 11 : 4 + r; }

struct __align__(128) Acc {
    float4 cs[48 * 8 * 3];
    float4 y[4 * 4 * 3 * 32];
    unsigned cnt_o[16 * 64];
};
constexpr int ACC_VEC_PER_CTA = (int)(sizeof(Acc) / 16 / NCTA);
static_assert(sizeof(Acc) == ACC_VEC_PER_CTA * 16 * NCTA && ACC_VEC_PER_CTA <= 256, "");
struct __align__(128) Scratch {
    Acc acc[2];
    uint4 kv[32 * 4 * 3 * 32];
    unsigned hint[8 * 32];
    uint2 rows[S_];
    uint4 best[NCTA];
    unsigned epoch;
};
__device__ Scratch g_scr;
__device__ __align__(1024) __nv_bfloat16 g_o[2 * S_ * D_];

#define TL(e) do {} while (0)
#define TLP(c, e) do {} while (0)
#define TLG(c, e) do {} while (0)
#define TL_DUMP() do {} while (0)

struct SideMaps { CUtensorMap wc, wg, wu, wd8, wgt, wut; };
struct Params {
    const __nv_bfloat16* x;
    const __nv_bfloat16* wr;
    const __nv_bfloat16* wqkv;
    const __nv_bfloat16* wg;
    const __nv_bfloat16* wu;
    const __nv_bfloat16* wd;
    const __nv_bfloat16* wo;
    __nv_bfloat16* out;
    __nv_bfloat16* o;
    Scratch* scr;
    unsigned long long* tl;
};

__device__ __forceinline__ bool elect_one() {
    uint32_t p; asm volatile("{\n.reg .pred q;\nelect.sync _|q, 0xffffffff;\nselp.u32 %0, 1, 0, q;\n}" : "=r"(p)); return p;
}
__device__ __forceinline__ uint32_t smem_u32(const void* p) { return (uint32_t)__cvta_generic_to_shared(p); }
__device__ __forceinline__ void mbar_init(uint32_t bar, uint32_t cnt) { asm volatile("mbarrier.init.shared::cta.b64 [%0], %1;" :: "r"(bar), "r"(cnt) : "memory"); }
__device__ __forceinline__ void mbar_expect_tx(uint32_t bar, uint32_t bytes) { asm volatile("mbarrier.arrive.expect_tx.shared::cta.b64 _, [%0], %1;" :: "r"(bar), "r"(bytes) : "memory"); }
__device__ __forceinline__ void mbar_arrive_if(bool p, uint32_t bar) {
    asm volatile("{\n.reg .pred q;\nsetp.ne.b32 q, %1, 0;\n@q mbarrier.arrive.shared::cta.b64 _, [%0];\n}" :: "r"(bar), "r"((int)p) : "memory");
}
__device__ __forceinline__ void mbar_wait(uint32_t bar, uint32_t parity) {
    asm volatile("{\n.reg .pred p;\n.reg .u32 n;\nmov.u32 n, 0;\n"
                 "WAIT_LOOP:\nmbarrier.try_wait.parity.shared::cta.b64 p, [%0], %1;\n@p bra WAIT_DONE;\n"
                 "add.u32 n, n, 1;\nsetp.lt.u32 p, n, 0x40000;\n@p bra WAIT_LOOP;\nWAIT_DONE:\n}" :: "r"(bar), "r"(parity) : "memory");
}
__device__ __forceinline__ bool mbar_test(uint32_t bar, uint32_t parity) {
    uint32_t ok;
    asm volatile("{\n.reg .pred p;\nmbarrier.test_wait.parity.shared::cta.b64 p, [%1], %2;\nselp.u32 %0, 1, 0, p;\n}" : "=r"(ok) : "r"(bar), "r"(parity) : "memory");
    return __all_sync(0xffffffffu, ok);
}
__device__ __forceinline__ void tma_2d(uint32_t dst, const CUtensorMap* tm, uint32_t bar, int c0, int c1) {
    asm volatile("cp.async.bulk.tensor.2d.shared::cluster.global.mbarrier::complete_tx::bytes [%0], [%1, {%3, %4}], [%2];"
        :: "r"(dst), "l"(tm), "r"(bar), "r"(c0), "r"(c1) : "memory");
}
__device__ __forceinline__ void tma_3d(uint32_t dst, const CUtensorMap* tm, uint32_t bar, int c0, int c1, int c2) {
    asm volatile("cp.async.bulk.tensor.3d.shared::cluster.global.mbarrier::complete_tx::bytes [%0], [%1, {%3, %4, %5}], [%2];"
        :: "r"(dst), "l"(tm), "r"(bar), "r"(c0), "r"(c1), "r"(c2) : "memory");
}
__device__ __forceinline__ void tma_4d(uint32_t dst, const CUtensorMap* tm, uint32_t bar, int c0, int c1, int c2, int c3) {
    asm volatile("cp.async.bulk.tensor.4d.shared::cluster.global.mbarrier::complete_tx::bytes [%0], [%1, {%3, %4, %5, %6}], [%2];"
        :: "r"(dst), "l"(tm), "r"(bar), "r"(c0), "r"(c1), "r"(c2), "r"(c3) : "memory");
}
__device__ __forceinline__ void prefetch_l2(const void* p, uint32_t bytes) { asm volatile("cp.async.bulk.prefetch.L2.global [%0], %1;" :: "l"(p), "r"(bytes) : "memory"); }
__device__ __forceinline__ void wgmma_fence() { asm volatile("wgmma.fence.sync.aligned;" ::: "memory"); }
__device__ __forceinline__ void wgmma_commit() { asm volatile("wgmma.commit_group.sync.aligned;" ::: "memory"); }
template <int N> __device__ __forceinline__ void wgmma_wait() { asm volatile("wgmma.wait_group.sync.aligned %0;" :: "n"(N) : "memory"); }
template <int N> __device__ __forceinline__ void fence_regs(float (&a)[N]) {
#pragma unroll
    for (int i = 0; i < N; i++) asm volatile("" : "+f"(a[i]) :: "memory");
}
template <int N> __device__ __forceinline__ void fence_regs(uint32_t (&a)[N]) {
#pragma unroll
    for (int i = 0; i < N; i++) asm volatile("" : "+r"(a[i]) :: "memory");
}
__device__ __forceinline__ uint64_t desc_from(uint32_t lo, uint32_t hi) { uint64_t d; asm("mov.b64 %0, {%1, %2};" : "=l"(d) : "r"(lo), "r"(hi)); return d; }
__device__ __forceinline__ uint32_t dlo(uint32_t addr, uint32_t lbo) { return ((addr & 0x3FFFF) >> 4) | ((lbo >> 4) << 16); }
__device__ __forceinline__ void nb_sync(int id, int cnt) { asm volatile("bar.sync %0, %1;" :: "r"(id), "r"(cnt) : "memory"); }
__device__ __forceinline__ void nb_arrive(int id, int cnt) { asm volatile("bar.arrive %0, %1;" :: "r"(id), "r"(cnt) : "memory"); }
__device__ __forceinline__ void fence_async_smem() { asm volatile("fence.proxy.async.shared::cta;" ::: "memory"); }
__device__ __forceinline__ void red_v4(float4* p, float a, float b, float c, float d) {
    asm volatile("red.relaxed.gpu.global.add.v4.f32 [%0], {%1, %2, %3, %4};" :: "l"(p), "f"(a), "f"(b), "f"(c), "f"(d) : "memory");
}
__device__ __forceinline__ void red_h8(uint4* p, uint32_t a, uint32_t b, uint32_t c, uint32_t d) {
    asm volatile("red.relaxed.gpu.global.add.noftz.v4.f16x2 [%0], {%1, %2, %3, %4};" :: "l"(p), "r"(a), "r"(b), "r"(c), "r"(d) : "memory");
}
__device__ __forceinline__ float4 ld_gpu(const float4* p) {
    float4 v; asm volatile("ld.relaxed.gpu.global.v4.f32 {%0, %1, %2, %3}, [%4];" : "=f"(v.x), "=f"(v.y), "=f"(v.z), "=f"(v.w) : "l"(p) : "memory"); return v;
}
__device__ __forceinline__ uint4 ld_gpu(const uint4* p) {
    uint4 v; asm volatile("ld.relaxed.gpu.global.v4.u32 {%0, %1, %2, %3}, [%4];" : "=r"(v.x), "=r"(v.y), "=r"(v.z), "=r"(v.w) : "l"(p) : "memory"); return v;
}
__device__ __forceinline__ void poll_counter(const unsigned* p, unsigned target) {
    unsigned it = 0, v;
#pragma unroll 1
    do {
        asm volatile("ld.acquire.gpu.global.u32 %0, [%1];" : "=r"(v) : "l"(p) : "memory");
    } while (v < target && ++it < (1u << 20));
}
__device__ __forceinline__ uint32_t pack_bf16(float lo, float hi) { uint32_t r; asm("cvt.rn.bf16x2.f32 %0, %1, %2;" : "=r"(r) : "f"(hi), "f"(lo)); return r; }
__device__ __forceinline__ uint32_t pack_f16(float lo, float hi) { uint32_t r; asm("cvt.rn.f16x2.f32 %0, %1, %2;" : "=r"(r) : "f"(hi), "f"(lo)); return r; }
__device__ __forceinline__ float2 unpack_f16(uint32_t v) { float2 r; asm("{\n.reg .f16 l, h;\nmov.b32 {l, h}, %2;\ncvt.f32.f16 %0, l;\ncvt.f32.f16 %1, h;\n}" : "=f"(r.x), "=f"(r.y) : "r"(v)); return r; }
__device__ __forceinline__ float bf_lo(uint32_t v) { return __uint_as_float(v << 16); }
__device__ __forceinline__ float bf_hi(uint32_t v) { return __uint_as_float(v & 0xFFFF0000u); }
__device__ __forceinline__ float round_bf16(float v) { return bf_lo(pack_bf16(v, 0.f)); }
__device__ __forceinline__ float ex2(float v) { float r; asm("ex2.approx.ftz.f32 %0, %1;" : "=f"(r) : "f"(v)); return r; }
__device__ __forceinline__ float rcp(float v) { float r; asm("rcp.approx.ftz.f32 %0, %1;" : "=f"(r) : "f"(v)); return r; }
__device__ __forceinline__ float sqrt_a(float v) { float r; asm("sqrt.approx.f32 %0, %1;" : "=f"(r) : "f"(v)); return r; }
__device__ __forceinline__ void stsm(uint32_t addr, uint32_t r0, uint32_t r1, uint32_t r2, uint32_t r3) {
    asm volatile("stmatrix.sync.aligned.m8n8.x4.shared.b16 [%0], {%1, %2, %3, %4};" :: "r"(addr), "r"(r0), "r"(r1), "r"(r2), "r"(r3) : "memory");
}
__device__ __forceinline__ void stsm_t(uint32_t addr, uint32_t r0, uint32_t r1, uint32_t r2, uint32_t r3) {
    asm volatile("stmatrix.sync.aligned.m8n8.x4.trans.shared.b16 [%0], {%1, %2, %3, %4};" :: "r"(addr), "r"(r0), "r"(r1), "r"(r2), "r"(r3) : "memory");
}
__device__ __forceinline__ uint4 lds128(uint32_t addr) {
    uint4 v; asm volatile("ld.shared.v4.u32 {%0, %1, %2, %3}, [%4];" : "=r"(v.x), "=r"(v.y), "=r"(v.z), "=r"(v.w) : "r"(addr) : "memory"); return v;
}
__device__ __forceinline__ void sts128(uint32_t addr, uint32_t a, uint32_t b, uint32_t c, uint32_t d) {
    asm volatile("st.shared.v4.u32 [%0], {%1, %2, %3, %4};" :: "r"(addr), "r"(a), "r"(b), "r"(c), "r"(d) : "memory");
}
__device__ __forceinline__ void sts64(uint32_t addr, uint32_t a, uint32_t b) { asm volatile("st.shared.v2.u32 [%0], {%1, %2};" :: "r"(addr), "r"(a), "r"(b) : "memory"); }
__device__ __forceinline__ uint32_t lds32(uint32_t addr) { uint32_t v; asm volatile("ld.shared.u32 %0, [%1];" : "=r"(v) : "r"(addr) : "memory"); return v; }
__device__ __forceinline__ float ldsf(uint32_t addr) { return __uint_as_float(lds32(addr)); }
__device__ __forceinline__ void sts32(uint32_t addr, uint32_t v) { asm volatile("st.shared.u32 [%0], %1;" :: "r"(addr), "r"(v) : "memory"); }
__device__ __forceinline__ uint32_t hmul2(uint32_t a, uint32_t b) { uint32_t r; asm("mul.rn.bf16x2 %0, %1, %2;" : "=r"(r) : "r"(a), "r"(b)); return r; }
__device__ __forceinline__ uint32_t hadd2(uint32_t a, uint32_t b) { uint32_t r; asm("add.rn.bf16x2 %0, %1, %2;" : "=r"(r) : "r"(a), "r"(b)); return r; }
__device__ __forceinline__ uint32_t hsub2(uint32_t a, uint32_t b) { uint32_t r; asm("sub.rn.bf16x2 %0, %1, %2;" : "=r"(r) : "r"(a), "r"(b)); return r; }

__device__ __forceinline__ void wgmma_ss_n192_tb(float (&d)[96], uint64_t da, uint64_t db, int scale_d) {
    asm volatile(
        "{\n.reg .pred p;\nsetp.ne.b32 p, %98, 0;\n"
        "wgmma.mma_async.sync.aligned.m64n192k16.f32.bf16.bf16 "
        "{%0, %1, %2, %3, %4, %5, %6, %7, %8, %9, %10, %11, %12, %13, %14, %15, %16, %17, %18, %19, %20, %21, %22, %23, %24, %25, %26, %27, %28, %29, %30, %31, %32, %33, %34, %35, %36, %37, %38, %39, %40, %41, %42, %43, %44, %45, %46, %47, %48, %49, %50, %51, %52, %53, %54, %55, %56, %57, %58, %59, %60, %61, %62, %63, %64, %65, %66, %67, %68, %69, %70, %71, %72, %73, %74, %75, %76, %77, %78, %79, %80, %81, %82, %83, %84, %85, %86, %87, %88, %89, %90, %91, %92, %93, %94, %95}, %96, %97, p, 1, 1, 0, 1;\n}\n"
        : "+f"(d[0]), "+f"(d[1]), "+f"(d[2]), "+f"(d[3]), "+f"(d[4]), "+f"(d[5]), "+f"(d[6]), "+f"(d[7]), "+f"(d[8]), "+f"(d[9]), "+f"(d[10]), "+f"(d[11]), "+f"(d[12]), "+f"(d[13]), "+f"(d[14]), "+f"(d[15]), "+f"(d[16]), "+f"(d[17]), "+f"(d[18]), "+f"(d[19]), "+f"(d[20]), "+f"(d[21]), "+f"(d[22]), "+f"(d[23]), "+f"(d[24]), "+f"(d[25]), "+f"(d[26]), "+f"(d[27]), "+f"(d[28]), "+f"(d[29]), "+f"(d[30]), "+f"(d[31]), "+f"(d[32]), "+f"(d[33]), "+f"(d[34]), "+f"(d[35]), "+f"(d[36]), "+f"(d[37]), "+f"(d[38]), "+f"(d[39]), "+f"(d[40]), "+f"(d[41]), "+f"(d[42]), "+f"(d[43]), "+f"(d[44]), "+f"(d[45]), "+f"(d[46]), "+f"(d[47]), "+f"(d[48]), "+f"(d[49]), "+f"(d[50]), "+f"(d[51]), "+f"(d[52]), "+f"(d[53]), "+f"(d[54]), "+f"(d[55]), "+f"(d[56]), "+f"(d[57]), "+f"(d[58]), "+f"(d[59]), "+f"(d[60]), "+f"(d[61]), "+f"(d[62]), "+f"(d[63]), "+f"(d[64]), "+f"(d[65]), "+f"(d[66]), "+f"(d[67]), "+f"(d[68]), "+f"(d[69]), "+f"(d[70]), "+f"(d[71]), "+f"(d[72]), "+f"(d[73]), "+f"(d[74]), "+f"(d[75]), "+f"(d[76]), "+f"(d[77]), "+f"(d[78]), "+f"(d[79]), "+f"(d[80]), "+f"(d[81]), "+f"(d[82]), "+f"(d[83]), "+f"(d[84]), "+f"(d[85]), "+f"(d[86]), "+f"(d[87]), "+f"(d[88]), "+f"(d[89]), "+f"(d[90]), "+f"(d[91]), "+f"(d[92]), "+f"(d[93]), "+f"(d[94]), "+f"(d[95])
        : "l"(da), "l"(db), "r"(scale_d));
}
__device__ __forceinline__ void wgmma_ss_n128_tb(float (&d)[64], uint64_t da, uint64_t db, int scale_d) {
    asm volatile(
        "{\n.reg .pred p;\nsetp.ne.b32 p, %66, 0;\n"
        "wgmma.mma_async.sync.aligned.m64n128k16.f32.bf16.bf16 "
        "{%0, %1, %2, %3, %4, %5, %6, %7, %8, %9, %10, %11, %12, %13, %14, %15, %16, %17, %18, %19, %20, %21, %22, %23, %24, %25, %26, %27, %28, %29, %30, %31, %32, %33, %34, %35, %36, %37, %38, %39, %40, %41, %42, %43, %44, %45, %46, %47, %48, %49, %50, %51, %52, %53, %54, %55, %56, %57, %58, %59, %60, %61, %62, %63}, %64, %65, p, 1, 1, 0, 1;\n}\n"
        : "+f"(d[0]), "+f"(d[1]), "+f"(d[2]), "+f"(d[3]), "+f"(d[4]), "+f"(d[5]), "+f"(d[6]), "+f"(d[7]), "+f"(d[8]), "+f"(d[9]), "+f"(d[10]), "+f"(d[11]), "+f"(d[12]), "+f"(d[13]), "+f"(d[14]), "+f"(d[15]), "+f"(d[16]), "+f"(d[17]), "+f"(d[18]), "+f"(d[19]), "+f"(d[20]), "+f"(d[21]), "+f"(d[22]), "+f"(d[23]), "+f"(d[24]), "+f"(d[25]), "+f"(d[26]), "+f"(d[27]), "+f"(d[28]), "+f"(d[29]), "+f"(d[30]), "+f"(d[31]), "+f"(d[32]), "+f"(d[33]), "+f"(d[34]), "+f"(d[35]), "+f"(d[36]), "+f"(d[37]), "+f"(d[38]), "+f"(d[39]), "+f"(d[40]), "+f"(d[41]), "+f"(d[42]), "+f"(d[43]), "+f"(d[44]), "+f"(d[45]), "+f"(d[46]), "+f"(d[47]), "+f"(d[48]), "+f"(d[49]), "+f"(d[50]), "+f"(d[51]), "+f"(d[52]), "+f"(d[53]), "+f"(d[54]), "+f"(d[55]), "+f"(d[56]), "+f"(d[57]), "+f"(d[58]), "+f"(d[59]), "+f"(d[60]), "+f"(d[61]), "+f"(d[62]), "+f"(d[63])
        : "l"(da), "l"(db), "r"(scale_d));
}
__device__ __forceinline__ void wgmma_ss_n40(float (&d)[20], uint64_t da, uint64_t db, int scale_d) {
    asm volatile(
        "{\n.reg .pred p;\nsetp.ne.b32 p, %22, 0;\n"
        "wgmma.mma_async.sync.aligned.m64n40k16.f32.bf16.bf16 "
        "{%0, %1, %2, %3, %4, %5, %6, %7, %8, %9, %10, %11, %12, %13, %14, %15, %16, %17, %18, %19}, %20, %21, p, 1, 1, 0, 0;\n}\n"
        : "+f"(d[0]), "+f"(d[1]), "+f"(d[2]), "+f"(d[3]), "+f"(d[4]), "+f"(d[5]), "+f"(d[6]), "+f"(d[7]), "+f"(d[8]), "+f"(d[9]), "+f"(d[10]), "+f"(d[11]), "+f"(d[12]), "+f"(d[13]), "+f"(d[14]), "+f"(d[15]), "+f"(d[16]), "+f"(d[17]), "+f"(d[18]), "+f"(d[19])
        : "l"(da), "l"(db), "r"(scale_d));
}
__device__ __forceinline__ void wgmma_ss_n8_ta(float (&d)[4], uint64_t da, uint64_t db, int scale_d) {
    asm volatile(
        "{\n.reg .pred p;\nsetp.ne.b32 p, %6, 0;\n"
        "wgmma.mma_async.sync.aligned.m64n8k16.f32.bf16.bf16 "
        "{%0, %1, %2, %3}, %4, %5, p, 1, 1, 1, 0;\n}\n"
        : "+f"(d[0]), "+f"(d[1]), "+f"(d[2]), "+f"(d[3])
        : "l"(da), "l"(db), "r"(scale_d));
}
__device__ __forceinline__ void wgmma_rs_n32_tb(float (&d)[16], uint32_t a0, uint32_t a1, uint32_t a2, uint32_t a3, uint64_t db, int scale_d) {
    asm volatile(
        "{\n.reg .pred p;\nsetp.ne.b32 p, %21, 0;\n"
        "wgmma.mma_async.sync.aligned.m64n32k16.f32.bf16.bf16 "
        "{%0, %1, %2, %3, %4, %5, %6, %7, %8, %9, %10, %11, %12, %13, %14, %15}, {%16, %17, %18, %19}, %20, p, 1, 1, 1;\n}\n"
        : "+f"(d[0]), "+f"(d[1]), "+f"(d[2]), "+f"(d[3]), "+f"(d[4]), "+f"(d[5]), "+f"(d[6]), "+f"(d[7]), "+f"(d[8]), "+f"(d[9]), "+f"(d[10]), "+f"(d[11]), "+f"(d[12]), "+f"(d[13]), "+f"(d[14]), "+f"(d[15])
        : "r"(a0), "r"(a1), "r"(a2), "r"(a3), "l"(db), "r"(scale_d));
}
__device__ __forceinline__ void wgmma_rs_n40_tb(float (&d)[20], uint32_t a0, uint32_t a1, uint32_t a2, uint32_t a3, uint64_t db, int scale_d) {
    asm volatile(
        "{\n.reg .pred p;\nsetp.ne.b32 p, %25, 0;\n"
        "wgmma.mma_async.sync.aligned.m64n40k16.f32.bf16.bf16 "
        "{%0, %1, %2, %3, %4, %5, %6, %7, %8, %9, %10, %11, %12, %13, %14, %15, %16, %17, %18, %19}, {%20, %21, %22, %23}, %24, p, 1, 1, 1;\n}\n"
        : "+f"(d[0]), "+f"(d[1]), "+f"(d[2]), "+f"(d[3]), "+f"(d[4]), "+f"(d[5]), "+f"(d[6]), "+f"(d[7]), "+f"(d[8]), "+f"(d[9]), "+f"(d[10]), "+f"(d[11]), "+f"(d[12]), "+f"(d[13]), "+f"(d[14]), "+f"(d[15]), "+f"(d[16]), "+f"(d[17]), "+f"(d[18]), "+f"(d[19])
        : "r"(a0), "r"(a1), "r"(a2), "r"(a3), "l"(db), "r"(scale_d));
}

constexpr float LOG2E = 1.4426950408889634f;
constexpr uint32_t DH128 = (1024u >> 4) | (1u << 30);

__device__ __forceinline__ float silu_f(float v) { return v * rcp(1.0f + ex2(-v * LOG2E)); }
__device__ __forceinline__ float silu_t(float v) { const float h = 0.5f * v; float th; asm("tanh.approx.f32 %0, %1;" : "=f"(th) : "f"(h)); return fmaf(h, th, h); }
__device__ __forceinline__ uint32_t ln_pair(uint32_t xv, uint32_t m2, float rs) { const uint32_t a = hsub2(xv, m2); return pack_bf16(bf_lo(a) * rs, bf_hi(a) * rs); }
__device__ __forceinline__ uint32_t silu_pair(uint32_t v) { return pack_bf16(silu_t(bf_lo(v)), silu_t(bf_hi(v))); }
__device__ __forceinline__ uint32_t gate_pair(uint32_t v, float hr, float hm) {
    const float a = fmaf(bf_lo(v), hr, hm), b = fmaf(bf_hi(v), hr, hm);
    float ta, tb;
    asm("tanh.approx.f32 %0, %1;" : "=f"(ta) : "f"(a)); asm("tanh.approx.f32 %0, %1;" : "=f"(tb) : "f"(b));
    return pack_bf16(fmaf(a, ta, a), fmaf(b, tb, b));
}
__device__ __forceinline__ void gate_item(uint4& v, uint32_t sb, int row) {
    const float hr = 0.5f * ldsf(sb + SM_RS + row * 4), hm = -bf_lo(lds32(sb + SM_MD + row * 4)) * hr;
    v.x = gate_pair(v.x, hr, hm); v.y = gate_pair(v.y, hr, hm); v.z = gate_pair(v.z, hr, hm); v.w = gate_pair(v.w, hr, hm);
    asm volatile("" : "+r"(v.x), "+r"(v.y), "+r"(v.z), "+r"(v.w) :: "memory");
}
__device__ __forceinline__ uint32_t hfma2(uint32_t a, uint32_t b, uint32_t c) { uint32_t r; asm("fma.rn.bf16x2 %0, %1, %2, %3;" : "=r"(r) : "r"(a), "r"(b), "r"(c)); return r; }
__device__ __forceinline__ uint32_t dup_lo(uint32_t v) { uint32_t r; asm("{\n.reg .b16 l, h;\nmov.b32 {l, h}, %1;\nmov.b32 %0, {l, l};\n}" : "=r"(r) : "r"(v)); return r; }
__device__ __forceinline__ uint32_t dup_hi(uint32_t v) { uint32_t r; asm("{\n.reg .b16 l, h;\nmov.b32 {l, h}, %1;\nmov.b32 %0, {h, h};\n}" : "=r"(r) : "r"(v)); return r; }
__device__ __forceinline__ uint32_t hmax2(uint32_t a, uint32_t b) { uint32_t r; asm("max.NaN.bf16x2 %0, %1, %2;" : "=r"(r) : "r"(a), "r"(b)); return r; }
template <bool SQ> __device__ __forceinline__ void colsum8(float (&a)[8], float& sq, const uint4 (&v)[8]) {
    uint32_t q = 0;
#pragma unroll
    for (int i = 0; i < 8; i++) {
        a[0] += bf_lo(v[i].x); a[1] += bf_hi(v[i].x); a[2] += bf_lo(v[i].y); a[3] += bf_hi(v[i].y);
        a[4] += bf_lo(v[i].z); a[5] += bf_hi(v[i].z); a[6] += bf_lo(v[i].w); a[7] += bf_hi(v[i].w);
        if (SQ) q = hfma2(v[i].x, v[i].x, hfma2(v[i].y, v[i].y, hfma2(v[i].z, v[i].z, hfma2(v[i].w, v[i].w, q))));
    }
    if (SQ) sq += bf_lo(q) + bf_hi(q);
}
__device__ __forceinline__ void hfma8(uint4& h, uint32_t w, const uint4& v) { h.x = hfma2(v.x, w, h.x); h.y = hfma2(v.y, w, h.y); h.z = hfma2(v.z, w, h.z); h.w = hfma2(v.w, w, h.w); }
template <int ST, class F>
__device__ __forceinline__ void gemv_run(float (&a)[8], int cnt, int b, uint32_t ph, uint32_t lo, uint32_t wa, uint32_t ws, uint32_t bar0, uint32_t pin, F done) {
    uint4 A[4], B[4];
    mbar_wait(bar0 + b * 8, ph);
    uint4 w = lds128(wa);
#pragma unroll
    for (int i = 0; i < 4; i++) A[i] = lds128(lo + b * 4096 + i * ST);
#pragma unroll 1
    for (int m = 0; m < cnt; m++) {
#pragma unroll
        for (int i = 0; i < 4; i++) B[i] = lds128(lo + b * 4096 + (4 + i) * ST);
        sts32(pin, 0u);
        uint4 h = make_uint4(0, 0, 0, 0);
        hfma8(h, dup_lo(w.x), A[0]); hfma8(h, dup_hi(w.x), A[1]); hfma8(h, dup_lo(w.y), A[2]); hfma8(h, dup_hi(w.y), A[3]);
        const uint32_t wz = w.z, ww = w.w;
        const int bc = b;
        if (++b == 3) { b = 0; ph ^= 1; }
        if (m + 1 < cnt) mbar_wait(bar0 + b * 8, ph);
        wa += ws;
        w = lds128(wa);
#pragma unroll
        for (int i = 0; i < 4; i++) A[i] = lds128(lo + b * 4096 + i * ST);
        sts32(pin, 0u);
        hfma8(h, dup_lo(wz), B[0]); hfma8(h, dup_hi(wz), B[1]); hfma8(h, dup_lo(ww), B[2]); hfma8(h, dup_hi(ww), B[3]);
        a[0] += bf_lo(h.x); a[1] += bf_hi(h.x); a[2] += bf_lo(h.y); a[3] += bf_hi(h.y);
        a[4] += bf_lo(h.z); a[5] += bf_hi(h.z); a[6] += bf_lo(h.w); a[7] += bf_hi(h.w);
        done(m, bc);
    }
}
template <int OFF> __device__ __forceinline__ void pack_head(const float (&acc)[96], uint32_t (&f)[8]) {
#pragma unroll
    for (int i = 0; i < 8; i++) f[i] = pack_bf16(acc[OFF + 2 * i], acc[OFF + 2 * i + 1]);
}
__device__ __forceinline__ void feat_mma(float (&p)[16], const uint32_t (&f)[8], uint32_t wlo) {
    constexpr uint32_t DH = (512u >> 4) | (2u << 30);
    wgmma_rs_n32_tb(p, f[0], f[1], f[2], f[3], desc_from(wlo, DH), 0);
    wgmma_rs_n32_tb(p, f[4], f[5], f[6], f[7], desc_from(wlo + 64, DH), 1);
}
template <int S> __device__ __forceinline__ void row_ext(const float (&p)[16], float& a, float& b) {
    auto op = [](float x, float y) { return S > 0 ? fmaxf(x, y) : fminf(x, y); };
    a = op(op(op(p[0], p[1]), op(p[4], p[5])), op(op(p[8], p[9]), op(p[12], p[13])));
    b = op(op(op(p[2], p[3]), op(p[6], p[7])), op(op(p[10], p[11]), op(p[14], p[15])));
#pragma unroll
    for (int o = 1; o <= 2; o <<= 1) { a = op(a, __shfl_xor_sync(0xffffffffu, a, o)); b = op(b, __shfl_xor_sync(0xffffffffu, b, o)); }
}
__device__ __forceinline__ void dual_exp(const float (&p)[16], float scA, float scB, uint32_t (&pos)[8], uint32_t (&neg)[8], uint32_t& chk) {
#pragma unroll
    for (int j = 0; j < 8; j += 2) {
        const float a0 = ex2(p[2 * j] * scA), a1 = ex2(p[2 * j + 1] * scA);
        const float b0 = ex2(p[2 * j + 2] * scB), b1 = ex2(p[2 * j + 3] * scB);
        const float pa = a0 * a1, pb = b0 * b1, R = rcp(pa * pb);
        const uint32_t r = pack_bf16(R * pb, R * pa);
        pos[j] = pack_bf16(a0, a1); pos[j + 1] = pack_bf16(b0, b1);
        neg[j] = hmul2(pos[j], dup_lo(r)); neg[j + 1] = hmul2(pos[j + 1], dup_hi(r));
        chk = hadd2(chk, hadd2(hadd2(pos[j], neg[j]), hadd2(pos[j + 1], neg[j + 1])));
    }
}
template <int S> __device__ __forceinline__ void exact_exp(const float (&p)[16], float scA, float scB, uint32_t (&o)[8]) {
    float mA, mB;
    row_ext<S>(p, mA, mB);
#pragma unroll
    for (int j = 0; j < 8; j++) {
        const float sc = S * ((j & 1) ? scB : scA), m = (j & 1) ? mB : mA;
        const float u = ex2((p[2 * j] - m) * sc), v = ex2((p[2 * j + 1] - m) * sc);
        o[j] = S > 0 ? pack_bf16(u, v) : pack_bf16(v, u);
    }
}
__device__ __forceinline__ void features(const float (&p0)[16], const float (&p1)[16], const float (&rs)[4],
                                         uint32_t (&pa)[8], uint32_t (&na)[8], uint32_t (&pb)[8], uint32_t (&nb)[8]) {
    uint32_t chk = 0;
    dual_exp(p0, rs[0] * LOG2E, rs[1] * LOG2E, pa, na, chk);
    dual_exp(p1, rs[2] * LOG2E, rs[3] * LOG2E, pb, nb, chk);
    if (__builtin_expect(!__all_sync(0xffffffffu, bf_lo(chk) + bf_hi(chk) < 1.0e9f), 0)) {
        exact_exp<1>(p0, rs[0] * LOG2E, rs[1] * LOG2E, pa); exact_exp<-1>(p0, rs[0] * LOG2E, rs[1] * LOG2E, na);
        exact_exp<1>(p1, rs[2] * LOG2E, rs[3] * LOG2E, pb); exact_exp<-1>(p1, rs[2] * LOG2E, rs[3] * LOG2E, nb);
    }
}
__device__ __forceinline__ float quad_sum(float v) { v += __shfl_xor_sync(0xffffffffu, v, 1); return v + __shfl_xor_sync(0xffffffffu, v, 2); }
__device__ __forceinline__ float key_block(const float (&p)[16], float rsA, float rsB, uint32_t d0, uint32_t d1, uint32_t off) {
    float r[8], sp[2], sn[2];
    uint32_t pos[8], neg[8];
    const float scA = rsA * LOG2E, scB = rsB * LOG2E;
#pragma unroll
    for (int j = 0; j < 8; j += 2) {
        const float a0 = ex2(p[2 * j] * scA), a1 = ex2(p[2 * j + 1] * scA);
        const float b0 = ex2(p[2 * j + 2] * scB), b1 = ex2(p[2 * j + 3] * scB);
        const float pa = a0 * a1, pb = b0 * b1, R = rcp(pa * pb), ta = a0 + a1, tb = b0 + b1;
        r[j] = R * pb; r[j + 1] = R * pa;
        if (j == 0) { sp[0] = ta; sp[1] = tb; sn[0] = r[0] * ta; sn[1] = r[1] * tb; }
        else { sp[0] += ta; sp[1] += tb; sn[0] = fmaf(r[j], ta, sn[0]); sn[1] = fmaf(r[j + 1], tb, sn[1]); }
        pos[j] = pack_bf16(a0, a1); pos[j + 1] = pack_bf16(b0, b1);
    }
    const float qa = quad_sum(sp[0]), qb = quad_sum(sp[1]), na = quad_sum(sn[0]), nb = quad_sum(sn[1]);
    const float iq = rcp(qa * qb), nA = rsA * rcp(na), nB = rsB * rcp(nb);
    const uint32_t fp = pack_bf16(rsA * qb * iq, rsB * qa * iq);
#pragma unroll
    for (int j = 0; j < 8; j += 2) {
        const uint32_t rn = pack_bf16(r[j] * nA, r[j + 1] * nB);
        neg[j] = hmul2(pos[j], dup_lo(rn)); neg[j + 1] = hmul2(pos[j + 1], dup_hi(rn));
        pos[j] = hmul2(pos[j], dup_lo(fp)); pos[j + 1] = hmul2(pos[j + 1], dup_hi(fp));
    }
    stsm_t(d0 + 4096, neg[0], neg[2], neg[4], neg[6]); stsm_t(d1 + 4096, neg[1], neg[3], neg[5], neg[7]);
    stsm_t(d0 + off, pos[0], pos[2], pos[4], pos[6]); stsm_t(d1 + off, pos[1], pos[3], pos[5], pos[7]);
    return (qa + qb) + (na + nb);
}
__device__ __forceinline__ void shift_max(float (&p)[16]) {
    float mA, mB;
    row_ext<1>(p, mA, mB);
#pragma unroll
    for (int j = 0; j < 16; j++) p[j] -= (j & 2) ? mB : mA;
}
__device__ __forceinline__ void key_head(float (&p0)[16], float (&p1)[16], const float (&rs)[4], uint32_t d0, uint32_t d1) {
    uint32_t st;
    asm volatile("mov.u32 %0, 0;" : "=r"(st));
    bool again;
#pragma unroll 1
    do {
        const uint32_t off = (st & 2u) << 11;
        const float chk = key_block(p0, rs[0], rs[1], d0, d1, off) + key_block(p1, rs[2], rs[3], d0 + 8192, d1 + 8192, off);
        again = st == 1u || (st == 0u && !__all_sync(0xffffffffu, chk < 1.0e9f));
        if (__builtin_expect(again, 0)) {
            if (st) {
#pragma unroll
                for (int j = 0; j < 16; j += 2) {
                    float t = p0[j]; p0[j] = -p0[j + 1]; p0[j + 1] = -t;
                    t = p1[j]; p1[j] = -p1[j + 1]; p1[j + 1] = -t;
                }
            }
            shift_max(p0); shift_max(p1);
            st++;
        }
        asm volatile("" ::: "memory");
    } while (again);
}
__device__ __forceinline__ void o_mma(float (&d)[20], float (&e)[20], const uint32_t (&pos)[8], const uint32_t (&neg)[8], uint32_t klo) {
    wgmma_rs_n40_tb(d, pos[0], pos[1], pos[2], pos[3], desc_from(klo, 1024u >> 4), 0);
    wgmma_rs_n40_tb(e, neg[0], neg[1], neg[2], neg[3], desc_from(klo + 32, 1024u >> 4), 0);
    wgmma_rs_n40_tb(d, pos[4], pos[5], pos[6], pos[7], desc_from(klo + 16, 1024u >> 4), 1);
    wgmma_rs_n40_tb(e, neg[4], neg[5], neg[6], neg[7], desc_from(klo + 48, 1024u >> 4), 1);
}
__device__ __forceinline__ void o_store(const float (&d)[20], const float (&e)[20], __nv_bfloat16* dst) {
    const float iA = rcp(fmaf(d[16], e[17], fmaf(e[16], d[17], 1e-6f * d[17] * e[17])));
    const float iB = rcp(fmaf(d[18], e[19], fmaf(e[18], d[19], 1e-6f * d[19] * e[19])));
    const float pA = e[17] * iA, nA = d[17] * iA, pB = e[19] * iB, nB = d[19] * iB;
    uint32_t oa[4], ob[4];
#pragma unroll
    for (int j = 0; j < 4; j++) {
        oa[j] = pack_bf16(fmaf(d[j * 4], pA, e[j * 4] * nA), fmaf(d[j * 4 + 1], pA, e[j * 4 + 1] * nA));
        ob[j] = pack_bf16(fmaf(d[j * 4 + 2], pB, e[j * 4 + 2] * nB), fmaf(d[j * 4 + 3], pB, e[j * 4 + 3] * nB));
    }
    *reinterpret_cast<uint4*>(dst) = make_uint4(oa[0], oa[1], oa[2], oa[3]);
    *reinterpret_cast<uint4*>(dst + 8 * D_) = make_uint4(ob[0], ob[1], ob[2], ob[3]);
}

template <int N> __device__ __forceinline__ void kv_gather(uint4 (&v)[3 * N], const uint4* src, uint32_t dst, int lane, float us) {
    unsigned it = 0;
#pragma unroll 1
    while (++it < (1u << 20)) {
        bool ok = true;
#pragma unroll
        for (int j = 0; j < 3 * N; j++) ok = ok && (v[j].w >> 16) == 0x4800u;
        if (__all_sync(0xffffffffu, ok)) break;
#pragma unroll
        for (int j = 0; j < 3 * N; j++) v[j] = ld_gpu(src + j * 32);
    }
    dst += (lane >> 2) * 16;
    auto cv = [&](uint32_t w) { const float2 f = unpack_f16(w); return pack_bf16(f.x * us, f.y * us); };
#pragma unroll
    for (int n = 0; n < N; n++) {
        sts128(dst + (lane & 3) * 1024 + n * 256, cv(v[3 * n].x), cv(v[3 * n].y), cv(v[3 * n].z), cv(v[3 * n + 2].x));
        sts128(dst + (lane & 3) * 1024 + n * 256 + 128, cv(v[3 * n + 1].x), cv(v[3 * n + 1].y), cv(v[3 * n + 1].z), cv(v[3 * n + 2].y));
        sts32(dst + 4096 + n * 256 + (lane & 3) * 4, pack_bf16(unpack_f16(v[3 * n].w).x, 1.0f));
        sts32(dst + 4096 + n * 256 + 128 + (lane & 3) * 4, pack_bf16(unpack_f16(v[3 * n + 1].w).x, 1.0f));
    }
    fence_async_smem();
    __syncwarp();
}

__global__ void __launch_bounds__(NTHREADS, 1)
fused_kernel(const __grid_constant__ CUtensorMap tmW0, const __grid_constant__ CUtensorMap tmX2, const __grid_constant__ CUtensorMap tmX, const __grid_constant__ CUtensorMap tmW, const Params P,
             const __grid_constant__ SideMaps tmS, const __grid_constant__ CUtensorMap tmPhi,
             const __grid_constant__ CUtensorMap tmWo, const __grid_constant__ CUtensorMap tmO) {
    extern __shared__ __align__(1024) uint8_t smem_raw[];
    constexpr uint32_t sb = 1024;
    if (smem_u32(smem_raw) != sb) return;
    constexpr uint32_t bars = sb + SM_BARS;
    const int rb = blockIdx.x >> 4, hp = blockIdx.x & 15;
    TLP(threadIdx.x == 32, 0); TLG(threadIdx.x == 32, 48);
    auto load_stage = [&](int s, int ks) {
        mbar_expect_tx(bars + 8 * (B_FULL + s), STAGE);
        tma_2d(sb + s * STAGE, &tmX, bars + 8 * (B_FULL + s), ks * 64, rb * 256);
        tma_3d(sb + s * STAGE + 32768, &tmW, bars + 8 * (B_FULL + s), hp * 64, ks * 64, 0);
    };
    if (threadIdx.x >= 64 && threadIdx.x < 104) {
        const int u = threadIdx.x - 64;
        const __nv_bfloat16* p = u < 16 ? P.x + (size_t)(blockIdx.x * 16 + u) * D_
                                        : P.wqkv + (size_t)(rb * 8 + ((u - 16) & 7)) * 3 * D_ + ((u - 16) >> 3) * D_ + hp * 64;
        asm volatile("prefetch.global.L2 [%0];" :: "l"(p));
    }
    if (threadIdx.x < 32 && elect_one()) {
#pragma unroll
        for (int i = 0; i < 3; i++) { mbar_init(bars + 8 * (B_FULL + i), 1); mbar_init(bars + 8 * (B_EMPTY + i), 8); }
        mbar_init(bars + 8 * B_XR, 1); mbar_init(bars + 8 * B_S0, 1); mbar_init(bars + 8 * B_S0 + 8, 1);
        asm volatile("fence.mbarrier_init.release.cluster;" ::: "memory");
        mbar_expect_tx(bars + 8 * B_S0, 28672);
        tma_3d(sb + 32768, &tmW0, bars + 8 * B_S0, hp * 64, 0, 0);
        tma_2d(sb, &tmX2, bars + 8 * B_S0, 0, rb * 256);
        mbar_expect_tx(bars + 8 * B_S0 + 8, 16384);
        tma_2d(sb + 16384, &tmX2, bars + 8 * B_S0 + 8, 0, rb * 256 + 128);
        mbar_expect_tx(bars + 8 * B_FULL, 12288);
        tma_3d(sb + 45056, &tmW0, bars + 8 * B_FULL, hp * 64, 32, 0);
        load_stage(1, 1); load_stage(2, 2);
        mbar_expect_tx(bars + 8 * B_XR, 32768);
        asm volatile("cp.async.bulk.shared::cluster.global.mbarrier::complete_tx::bytes [%0], [%1], 32768, [%2];"
                     :: "r"(sb + SM_FB + 4096), "l"(P.x + (size_t)blockIdx.x * 16 * D_), "r"(bars + 8 * B_XR) : "memory");
    }
    const int tid = threadIdx.x, warp = __shfl_sync(0xffffffffu, tid >> 5, 0), lane = tid & 31;
    const bool elect = lane == 0;

    if (warp >= 8) {
        const int aw = warp - 9;
        auto load_o = [&](int i, unsigned par) {
            mbar_expect_tx(bars + 8 * (B_OF + i), 16384);
            tma_2d(sb + o_slot(i) * 16384, &tmO, bars + 8 * (B_OF + i), i * 64, par * S_ + rb * 256 + (hp & 1) * 128);
        };
        auto load_wo = [&](int i) {
            mbar_expect_tx(bars + 8 * (B_OF + i), 16384);
            tma_4d(sb + wo_slot(i) * 16384, &tmWo, bars + 8 * (B_OF + i), 0, (i >> 3) * 32, (i & 7) * 2, hp & 14);
        };
        if (warp == 9) {
            if (elect_one()) {
#pragma unroll
                for (int i = B_OF; i < B_COUNT; i++)
                    mbar_init(bars + 8 * i, i < B_SD ? 2 : (i < B_WPHI ? 8 : ((i < B_KV || i >= B_FF || i == B_LN) ? 1 : 4)));
                asm volatile("fence.mbarrier_init.release.cluster;" ::: "memory");
            }
        }
        __syncwarp();
        nb_sync(0, NTHREADS);
        asm volatile("setmaxnreg.dec.sync.aligned.u32 56;");
        unsigned epoch;
        asm volatile("ld.relaxed.gpu.global.u32 %0, [%1];" : "=r"(epoch) : "l"(&P.scr->epoch) : "memory");
        auto get_acc = [&]() { return &P.scr->acc[epoch & 1u]; };
        if (warp == 8) {
            epoch = __shfl_sync(0xffffffffu, epoch, 0);
            int s = 0, ph = 0;
#pragma unroll 1
            for (int j = 0; j < 15; j++) {
                mbar_wait(bars + 8 * (B_EMPTY + s), ph);
                if (elect_one()) {
                    if (j < 13) load_stage(s, j + 3);
                    if (j < 2) {
                        prefetch_l2(P.wqkv + (size_t)(256 + j * 384 + blockIdx.x * 3) * 3 * D_, 18432);
                    } else if (j < 10) {
                        if (j == 2) asm volatile("mbarrier.arrive.shared::cta.b64 _, [%0];" :: "r"(bars + 8 * B_FF) : "memory");
                        const size_t o = (size_t)((j - 2) * 128 + blockIdx.x) * F_;
                        prefetch_l2(P.wg + o, F_ * 2); prefetch_l2(P.wu + o, F_ * 2);
                    } else if (blockIdx.x < 112 && j < 14) {
                        prefetch_l2(P.wd + (size_t)(blockIdx.x * 32 + (j - 10) * 8) * D_, 16384);
                    }
                    if (j == 14) prefetch_l2(P.wo + (size_t)blockIdx.x * 8 * D_, 16384);
                    if (j == 12) {
                        asm volatile("prefetch.tensormap [%0];" :: "l"(&tmO) : "memory");
                        asm volatile("prefetch.tensormap [%0];" :: "l"(&tmS.wgt) : "memory");
                        asm volatile("prefetch.tensormap [%0];" :: "l"(&tmS.wut) : "memory");
                        asm volatile("prefetch.tensormap [%0];" :: "l"(&tmS.wd8) : "memory");
                        asm volatile("prefetch.tensormap [%0];" :: "l"(&tmWo) : "memory");
                        mbar_expect_tx(bars + 8 * B_WPHI, 4096);
                        tma_2d(sb + SM_WPHI, &tmPhi, bars + 8 * B_WPHI, 0, hp * 64);
                    }
                    if (j >= 13) {
                        if (blockIdx.x >= 112) { load_wo(2 * j - 26); load_wo(2 * j - 25); }
                        else if (j == 13) {
                            mbar_expect_tx(bars + 8 * B_GT, 32768);
                            tma_2d(sb + 4 * 16384, &tmS.wgt, bars + 8 * B_GT, blockIdx.x * 32, 768);
                            tma_2d(sb + 5 * 16384, &tmS.wut, bars + 8 * B_GT, blockIdx.x * 32, 768);
                        } else {
                            mbar_expect_tx(bars + 8 * (B_DN + 1), 32768);
                            tma_3d(sb + 6 * 16384, &tmS.wd8, bars + 8 * (B_DN + 1), 0, blockIdx.x * 32, 8);
                        }
                    }
                }
                __syncwarp();
                if (++s == 3) { s = 0; ph ^= 1; }
                if (j == 12 && hp == 0 && lane < 4) P.scr->hint[rb * 32 + lane] = 0u;
                if (j >= 3 && j < 11) {
                    uint4* zp = reinterpret_cast<uint4*>(P.o + (size_t)((~epoch & 1u) * S_ + blockIdx.x * 16 + (j - 3) * 2) * D_) + lane;
#pragma unroll
                    for (int i = 0; i < 2; i++) zp[i * 128] = make_uint4(0, 0, 0, 0);
                    const int i = (j - 3) * 32 + lane;
                    if (i < ACC_VEC_PER_CTA) reinterpret_cast<uint4*>(&P.scr->acc[~epoch & 1u])[blockIdx.x * ACC_VEC_PER_CTA + i] = make_uint4(0, 0, 0, 0);
                }
            }
            TLP(elect, 20);
        } else {
            const bool ffn = blockIdx.x < 112;
            const uint32_t fbuf = sb + SM_FB + 4096 + aw * 12288, fbar = bars + 8 * (B_FF + 1 + aw * 3);
            const int ng = ffn ? (aw < 2 ? (NGU - NG2) / 2 : NG2) : 0, g0 = aw < 2 ? NG2 + aw : 0, gs = aw < 2 ? 2 : 1;
            const int nc = aw == 0 ? 3 : 6 - aw, c0 = aw == 0 ? 0 : 5 * aw - 2;
            auto issue_gu = [&](int m, int b) {
                __syncwarp();
                if (m < ng && elect_one()) {
                    mbar_expect_tx(fbar + b * 8, 4096);
                    tma_2d(fbuf + b * 4096, &tmS.wg, fbar + b * 8, blockIdx.x * 32, (g0 + gs * m) * 32);
                    tma_2d(fbuf + b * 4096 + 2048, &tmS.wu, fbar + b * 8, blockIdx.x * 32, (g0 + gs * m) * 32);
                }
                __syncwarp();
            };
            {
                uint4 wv[4];
#pragma unroll
                for (int i = 0; i < 4; i++) wv[i] = __ldg(reinterpret_cast<const uint4*>(P.wr) + i * 32 + lane);
                const uint32_t* ww = reinterpret_cast<const uint32_t*>(wv);
                float sw = 0.f;
#pragma unroll
                for (int i = 0; i < 16; i++) sw += bf_lo(ww[i]) + bf_hi(ww[i]);
#pragma unroll 1
                for (int o = 16; o > 0; o >>= 1) sw += __shfl_xor_sync(0xffffffffu, sw, o);
                sts32(sb + SM_MISC + 20, __float_as_uint(sw));
                if (aw == 2) {
#pragma unroll
                    for (int i = 0; i < 3; i++) P.scr->kv[(hp * 8 + rb) * 96 + i * 32 + lane] = make_uint4(0, 0, 0, 0);
                    asm volatile("fence.acq_rel.gpu;" ::: "memory");
                    __syncwarp();
                }
                mbar_wait(bars + 8 * B_XR, 0);
#pragma unroll 1
                for (int r = aw * 6; r < min(aw * 6 + 6, 16); r++) {
                    const uint32_t buf = sb + SM_FB + 4096 + r * 2048;
                    uint4 xv[4];
                    uint32_t c2 = lds32(buf);
#pragma unroll
                    for (int i = 0; i < 4; i++) xv[i] = lds128(buf + i * 512 + lane * 16);
                    sts32(sb + SM_MISC + 12, 0u);
                    c2 = fabsf(bf_lo(c2) - bf_hi(c2)) < 0.25f * fabsf(bf_lo(c2)) ? dup_lo(c2) : 0u;
                    const uint32_t* xw = reinterpret_cast<const uint32_t*>(xv);
                    uint32_t d2[2] = {0u, 0u};
                    float s0 = 0.f, s1 = 0.f, q0 = 0.f, q1 = 0.f;
#pragma unroll
                    for (int i = 0; i < 16; i++) {
                        const uint32_t a = hsub2(xw[i], c2);
                        s0 += bf_lo(a); s1 += bf_hi(a);
                        d2[i & 1] = hfma2(a, ww[i], d2[i & 1]);
                        q0 = fmaf(bf_lo(a), bf_lo(a), q0); q1 = fmaf(bf_hi(a), bf_hi(a), q1);
                    }
                    sts128(sb + SM_SP + r * 512 + lane * 16, __float_as_uint(s0 + s1), __float_as_uint(q0 + q1),
                           __float_as_uint((bf_lo(d2[0]) + bf_hi(d2[0])) + (bf_lo(d2[1]) + bf_hi(d2[1]))), c2 << 16);
                }
                epoch = __shfl_sync(0xffffffffu, epoch, 0);
                if (aw < 2) nb_arrive(NB_FFN, 96);
                auto issue_cs = [&](int m) {
                    mbar_expect_tx(fbar + (m % 3) * 8, 4096);
                    tma_2d(fbuf + (m % 3) * 4096, &tmS.wc, fbar + (m % 3) * 8, ((c0 + m) >> 2) * 1024 + hp * 64, rb * 128 + ((c0 + m) & 3) * 32);
                };
                mbar_wait(bars + 8 * B_FF, 0);
                if (elect_one()) { issue_cs(0); issue_cs(1); issue_cs(2); }
                __syncwarp();
                const unsigned tag = epoch + 1u;
                if (aw == 2) {
                    nb_sync(NB_FFN, 96);
                    TLP(elect, 23);
                    float s = 0.f, q = 0.f, dt = 0.f, x0;
#pragma unroll 8
                    for (int j = 0; j < 16; j++) {
                        const uint4 e = lds128(sb + SM_SP + lane * 256 + ((j + lane) & 15) * 16);
                        s += __uint_as_float(e.x); q += __uint_as_float(e.y); dt += __uint_as_float(e.z); x0 = __uint_as_float(e.w);
                    }
                    s += __shfl_xor_sync(0xffffffffu, s, 1); q += __shfl_xor_sync(0xffffffffu, q, 1); dt += __shfl_xor_sync(0xffffffffu, dt, 1);
                    const float ms = s * (1.0f / D_);
                    const float vb = round_bf16(fmaxf(q - s * ms, 0.f) * (1.0f / D_));
                    const uint32_t md = pack_bf16(x0 + ms, sqrt_a(round_bf16(vb + 1e-5f)));
                    const uint32_t rbits = pack_bf16((dt - (bf_lo(md) - x0) * ldsf(sb + SM_MISC + 20)) * rcp(bf_hi(md)), 0.f);
                    const int row = blockIdx.x * 16 + (lane >> 1);
                    const uint32_t key = ((((rbits & 0x8000u) ? (~rbits & 0xFFFFu) : (rbits | 0x8000u)) + 1u) << 11) | (uint32_t)(2047 - row);
                    asm volatile("st.relaxed.gpu.global.v2.u32 [%0], {%1, %2};" :: "l"(&P.scr->rows[row]), "r"(md), "r"(tag) : "memory");
                    if (key == __reduce_max_sync(0xffffffffu, key))
                        asm volatile("st.relaxed.gpu.global.v4.u32 [%0], {%1, %2, %3, %3};" :: "l"(&P.scr->best[blockIdx.x]), "r"(key), "r"(md), "r"(tag) : "memory");
                    TLP(elect, 24);
                }
                {
                    float a[8], sq = 0.f, wt = 0.f;
#pragma unroll
                    for (int i = 0; i < 8; i++) a[i] = 0.f;
#pragma unroll 1
                    for (int m = 0; m < nc; m++) {
                        const int b = m % 3, c = c0 + m;
                        mbar_wait(fbar + b * 8, m >= 3);
                        uint4 v[8];
#pragma unroll
                        for (int i = 0; i < 8; i++) v[i] = lds128(fbuf + b * 4096 + i * 512 + lane * 16);
                        sts32(sb + SM_MISC + 12, 0u);
                        colsum8<true>(a, sq, v);
                        fence_regs(a);
                        wt += 1.0f;
                        if (m + 3 < nc) {
                            __syncwarp();
                            if (elect_one()) issue_cs(m + 3);
                            __syncwarp();
                        } else {
                            issue_gu(m + 3 - nc, b);
                        }
                        if ((c & 3) == 3 || m == nc - 1) {
#pragma unroll 1
                            for (int o = 8; o <= 16; o <<= 1) {
#pragma unroll
                                for (int i = 0; i < 8; i++) a[i] += __shfl_xor_sync(0xffffffffu, a[i], o);
                                sq += __shfl_xor_sync(0xffffffffu, sq, o);
                            }
                            float4* dst = &get_acc()->cs[((c >> 2) * 16 + hp) * 24 + lane];
                            if (lane < 8) { red_v4(dst, a[0], a[1], a[2], wt); red_v4(dst + 8, a[3], a[4], a[5], wt); red_v4(dst + 16, a[6], a[7], sq, wt); }
#pragma unroll
                            for (int i = 0; i < 8; i++) a[i] = 0.f;
                            wt = 0.f;
                        }
                    }
                    TLP(tid == 288, 26); TLP(tid == 320, 15); TLP(tid == 352, 22);
                }
                if (aw == 0) {
                    uint4 v[4];
                    unsigned it = 0;
                    bool ok = true;
#pragma unroll 1
                    do {
                        if (!ok) __nanosleep(200);
#pragma unroll
                        for (int i = 0; i < 4; i++) v[i] = ld_gpu(&P.scr->best[i * 32 + lane]);
                        ok = v[0].z == tag && v[1].z == tag && v[2].z == tag && v[3].z == tag;
                    } while (!__all_sync(0xffffffffu, ok) && ++it < (1u << 20));
#pragma unroll
                    for (int i = 1; i < 4; i++) if (v[i].x > v[0].x) v[0] = v[i];
                    const uint32_t key = __reduce_max_sync(0xffffffffu, v[0].x);
                    const uint32_t md = __reduce_or_sync(0xffffffffu, v[0].x == key ? v[0].y : 0u);
                    const int sel = 2047 - (int)(key & 2047u);
                    const uint4* xp = reinterpret_cast<const uint4*>(P.x + (size_t)sel * D_) + lane;
#pragma unroll
                    for (int i = 0; i < 4; i++) v[i] = __ldg(xp + i * 32);
                    const uint32_t m2 = __byte_perm(md, 0, 0x1010);
                    const float rs = rcp(bf_hi(md));
                    const uint32_t ord = (key >> 11) - 1u;
                    const float r = __uint_as_float(((ord & 0x8000u) ? (ord & 0x7FFFu) : (~ord & 0xFFFFu)) << 16);
                    sts128(sb + SM_MISC, (uint32_t)sel, __float_as_uint(round_bf16(rcp(1.0f + ex2(-r * LOG2E)))), epoch, 0u);
#pragma unroll
                    for (int i = 0; i < 4; i++) {
                        const uint32_t e0 = ln_pair(v[i].x, m2, rs), e1 = ln_pair(v[i].y, m2, rs), e2 = ln_pair(v[i].z, m2, rs), e3 = ln_pair(v[i].w, m2, rs);
                        if (i == 3) { sts128(sb + SM_XS + 1536 + lane * 16, e0, e1, e2, e3); continue; }
                        const uint32_t xa = sb + SM_XS + i * 512 + (lane >> 2) * 64 + (lane & 3) * 4;
                        sts32(xa, __byte_perm(e0, e2, 0x5410)); sts32(xa + 16, __byte_perm(e0, e2, 0x7632));
                        sts32(xa + 32, __byte_perm(e1, e3, 0x5410)); sts32(xa + 48, __byte_perm(e1, e3, 0x7632));
                    }
                    TLP(elect, 25);
                    __syncwarp();
                    nb_arrive(NB_AUX, 96);
                } else {
                    nb_sync(NB_AUX, 96);
                }
            }
            if (ffn) {
                float a[8];
#pragma unroll
                for (int i = 0; i < 8; i++) a[i] = 0.f;
                TLP(elect, 40 + aw);
                gemv_run<256>(a, ng, nc - 3, 1, fbuf + (lane >> 4) * 2048 + (lane & 15) * 16, sb + SM_XS + g0 * 64 + (lane & 12) * 4, gs * 64, fbar, sb + SM_MISC + 12,
                              [&](int m, int b) { issue_gu(m + 3, b); });
                TLP(elect, 44 + aw);
#pragma unroll 1
                for (int o = 4; o <= 8; o <<= 1) {
#pragma unroll
                    for (int i = 0; i < 8; i++) a[i] += __shfl_xor_sync(0xffffffffu, a[i], o);
                }
                if ((lane & 12) == 0) {
                    const uint32_t ga = sb + SM_GU + aw * 256 + (lane >> 4) * 128 + (lane & 3) * 32;
                    sts128(ga, __float_as_uint(a[0]), __float_as_uint(a[1]), __float_as_uint(a[2]), __float_as_uint(a[3]));
                    sts128(ga + 16, __float_as_uint(a[4]), __float_as_uint(a[5]), __float_as_uint(a[6]), __float_as_uint(a[7]));
                }
                fence_async_smem();
                TLP(tid == 288, 27);
            }
            if (aw == 2) {
                    const int l = lane < 24 ? lane : 0;
                    const float4* src = &get_acc()->cs[((l >> 3) * 16 + hp) * 24 + (l & 7)];
                    float4 v0, v1, v2;
                    uint4 v[4];
                    unsigned it = 0;
                    bool ok;
#pragma unroll 1
                    do {
                        v0 = ld_gpu(src); v1 = ld_gpu(src + 8); v2 = ld_gpu(src + 16);
                        ok = v0.w == 32.0f && v1.w == 32.0f && v2.w == 32.0f;
#pragma unroll
                        for (int i = 0; i < 4; i++) v[i] = ld_gpu(reinterpret_cast<const uint4*>(&P.scr->rows[rb * 256]) + i * 32 + lane);
#pragma unroll
                        for (int i = 0; i < 4; i++) ok = ok && v[i].y == epoch + 1u && v[i].w == epoch + 1u;
                    } while (!__all_sync(0xffffffffu, ok) && ++it < (1u << 20));
#pragma unroll
                    for (int i = 0; i < 4; i++) {
                        const uint32_t o = i * 256 + lane * 8;
                        sts64(sb + SM_MD + o, v[i].x, v[i].z);
                        sts64(sb + SM_RS + o, __float_as_uint(rcp(bf_hi(v[i].x))), __float_as_uint(rcp(bf_hi(v[i].z))));
                        const uint32_t h0 = hmul2(dup_lo(v[i].x), 0xBF00BF00u), h1 = hmul2(dup_lo(v[i].z), 0xBF00BF00u);
                        sts128(sb + SM_AX + o * 4, h0, h0 & 0xFFFFu, 0u, 0u);
                        sts128(sb + SM_AX + o * 4 + 16, h1, h1 & 0xFFFFu, 0u, 0u);
                    }
                    sts128(sb + SM_H + lane * 16, 0u, 0u, 0u, 0u); sts128(sb + SM_H + 512 + lane * 16, 0u, 0u, 0u, 0u);
                    const uint32_t e2 = __reduce_max_sync(0xffffffffu, l >= 16 ? __float_as_uint(v2.z) : 0u) >> 23;
                    sts32(sb + SM_MISC + 16, (uint32_t)min(max(187 - (int)((e2 + 1) >> 1), 1), 180) << 23);
                    float cc[8] = {v0.x, v0.y, v0.z, v1.x, v1.y, v1.z, v2.x, v2.y};
                    const uint32_t bx = sb + SM_BX + (l >> 3) * 1024;
#pragma unroll 1
                    for (int k = 0; k < 8; k++) {
                        uint32_t w[4];
#pragma unroll
                        for (int i = 0; i < 4; i++) {
                            w[i] = pack_bf16(cc[2 * i], cc[2 * i + 1]);
                            cc[2 * i] -= bf_lo(w[i]); cc[2 * i + 1] -= bf_hi(w[i]);
                        }
                        sts128(bx + k * 128 + (((l & 7) ^ k) * 16), w[0], w[1], w[2], w[3]);
                    }
                    fence_async_smem();
                    __syncwarp();
                    mbar_arrive_if(elect, bars + 8 * B_LN);
                    TLP(elect, 28);
                }
        }
        {
            TLP(tid == 288, 38);
            const int w4 = warp & 3;
            const uint32_t sp = sb + SM_FB + w4 * 1536;
            auto send = [&](int h) {
                if (elect_one()) {
                    asm volatile("cp.reduce.async.bulk.global.shared::cta.bulk_group.add.noftz.f16 [%0], [%1], 1536;"
                                 :: "l"(&P.scr->kv[(hp * 8 + h * 4 + w4) * 96]), "r"(sp) : "memory");
                    asm volatile("cp.async.bulk.commit_group;" ::: "memory");
                }
            };
            if (blockIdx.x < 112) {
                float y[4];
                if (warp == 8) {
                    nb_sync(NB_DN, 128);
                    if (elect_one()) {
                        mbar_expect_tx(bars + 8 * B_DN, 32768);
                        tma_3d(sb + SM_FB + 8192, &tmS.wd8, bars + 8 * B_DN, 0, blockIdx.x * 32, 0);
                    }
                    __syncwarp();
                } else {
                    nb_arrive(NB_DN, 128);
                }
                mbar_wait(bars + 8 * B_GT, 0);
                mbar_wait(bars + 8 * B_T, 0);
                wgmma_fence();
#pragma unroll 4
                for (int k = 0; k < 16; k++)
                    wgmma_ss_n8_ta(y, desc_from(dlo(sb + 4 * 16384, 16384) + k * 64, (512u >> 4) | (2u << 30)), desc_from(dlo(sb + SM_XS + 1536, 16) + k * 2, 8), k);
                wgmma_commit();
                wgmma_wait<0>();
                fence_regs(y);
                if ((lane & 3) == 0) { sts32(sb + SM_GU + 768 + w4 * 64 + lane, __float_as_uint(y[0])); sts32(sb + SM_GU + 800 + w4 * 64 + lane, __float_as_uint(y[2])); }
                nb_sync(NB_KV, 128);
                if (warp == 8) {
                    if (elect_one()) { load_wo(0); load_wo(1); }
                } else if (warp == 9) {
                    const uint32_t ga = sb + SM_GU + lane * 4;
                    const float gg = round_bf16((ldsf(ga) + ldsf(ga + 256)) + (ldsf(ga + 512) + ldsf(ga + 768)));
                    const float uu = round_bf16((ldsf(ga + 128) + ldsf(ga + 384)) + (ldsf(ga + 640) + ldsf(ga + 896)));
                    asm volatile("st.shared.u16 [%0], %1;" :: "r"(sb + SM_H + (lane >> 3) * 256 + 112 + (lane & 7) * 2), "h"((uint16_t)pack_bf16(round_bf16(silu_f(gg)) * uu, 0.f)) : "memory");
                    fence_async_smem();
                }
                __syncwarp();
                TLP(tid == 288, 19);
            }
            float ya[4] = {0.f, 0.f, 0.f, 0.f}, yb[4] = {0.f, 0.f, 0.f, 0.f};
            uint4 g0[3];
#pragma unroll 1
            for (int h = 0; h < 2; h++) {
                {
                    float d[20];
                    const uint32_t alo = dlo(sb + SM_PHI + h * 32768, 16), vlo = dlo(sb + SM_V + h * 20480, 16);
                    mbar_wait(bars + 8 * (B_PHI + h), 0);
                    wgmma_fence();
#pragma unroll
                    for (int k = 0; k < 16; k++)
                        wgmma_ss_n40(d, desc_from(alo + (k >> 2) * 512 + (k & 3) * 2, DH128), desc_from(vlo + (k >> 2) * 320 + (k & 3) * 2, DH128), k);
                    wgmma_commit();
#pragma unroll
                    for (int j = 0; j < 3; j++) g0[j] = ld_gpu(&P.scr->kv[(hp * 8 + w4) * 96 + j * 32 + lane]);
                    asm volatile("cp.async.bulk.wait_group.read 0;" ::: "memory");
                    __syncwarp();
                    const float ksc = ldsf(sb + SM_MISC + 16);
                    wgmma_wait<0>();
                    fence_regs(d);
#define U(x) pack_f16(d[x] * ksc, d[x + 1] * ksc)
                    sts128(sp + lane * 16, U(0), U(4), U(8), pack_f16(d[16], 1.0f));
                    sts128(sp + 512 + lane * 16, U(2), U(6), U(10), pack_f16(d[18], 1.0f));
                    sts128(sp + 1024 + lane * 16, U(12), U(14), 0u, 0x3C000000u);
#undef U
                    fence_async_smem();
                    __syncwarp();
                    send(h);
                    TLP(tid == 256, 30 + h);
                    nb_sync(NB_KV, 128);
                    if (h) break;
                    if (warp == 8 && elect_one()) {
                        mbar_expect_tx(bars + 8 * B_X, 32768);
                        tma_2d(sb, &tmX2, bars + 8 * B_X, (hp >> 1) * 128, rb * 256 + (hp & 1) * 128);
                        tma_2d(sb + 16384, &tmX2, bars + 8 * B_X, (hp >> 1) * 128 + 64, rb * 256 + (hp & 1) * 128);
                        load_wo(4);
                    }
                    __syncwarp();
                }
                if (blockIdx.x < 112) {
                    const uint32_t hlo = dlo(sb + SM_H, 256);
                    mbar_wait(bars + 8 * B_DN, 0);
                    mbar_wait(bars + 8 * (B_DN + 1), 0);
                    wgmma_fence();
#pragma unroll 2
                    for (int k = 0; k < 16; k++) {
                        wgmma_ss_n8_ta(yb, desc_from(dlo(sb + 6 * 16384, 16) + k * 128, DH128), desc_from(hlo + (k & 1) * 32 + 7 - (k >> 1), 8), k);
                        wgmma_ss_n8_ta(ya, desc_from(dlo(sb + SM_FB + 8192, 16) + k * 128, DH128), desc_from(hlo + (k & 1) * 32 + 7 - (k >> 1), 8), k);
                    }
                    wgmma_commit();
                    wgmma_wait<0>();
                    fence_regs(ya); fence_regs(yb);
                    if (warp == 8) {
                        nb_sync(NB_KV, 128);
                        if (elect_one()) { load_wo(2); load_wo(3); }
                        __syncwarp();
                    } else {
                        nb_arrive(NB_KV, 128);
                    }
                    TLP(tid == 288, 29);
                }
            }
            const float kus = __uint_as_float((254u << 23) - lds32(sb + SM_MISC + 16));
            kv_gather<1>(g0, &P.scr->kv[(hp * 8 + w4) * 96 + lane], sb + SM_KVOP + w4 * 256, lane, kus);
            mbar_arrive_if(elect, bars + 8 * B_KV);
            asm volatile("cp.async.bulk.wait_group.read 0;" ::: "memory");
            __syncwarp();
            if (blockIdx.x < 112) {
#define U(x) __float_as_uint(x)
                sts128(sp + lane * 16, U(ya[0]), U(ya[1]), U(ya[2]), U(1.0f));
                sts128(sp + 512 + lane * 16, U(ya[3]), U(yb[0]), U(yb[1]), U(1.0f));
                sts128(sp + 1024 + lane * 16, U(yb[2]), U(yb[3]), 0u, U(1.0f));
#undef U
                fence_async_smem();
                __syncwarp();
                if (elect_one()) {
                    asm volatile("cp.reduce.async.bulk.global.shared::cta.bulk_group.add.f32 [%0], [%1], 1536;"
                                 :: "l"(&get_acc()->y[((blockIdx.x & 3) * 4 + w4) * 96]), "r"(sp) : "memory");
                    asm volatile("cp.async.bulk.commit_group;" ::: "memory");
                }
                __syncwarp();
            }
            if (w4 >= 2) {
                uint4 g1[6];
#pragma unroll
                for (int j = 0; j < 6; j++) g1[j] = make_uint4(0, 0, 0, 0);
                kv_gather<2>(g1, &P.scr->kv[(hp * 8 + 2 * w4) * 96 + lane], sb + SM_KVOP - 5120 + (w4 - 2) * 512, lane, kus);
                mbar_arrive_if(lane < 2, bars + 8 * (B_KV + 1));
            }
            asm volatile("cp.async.bulk.wait_group.read 0;" ::: "memory");
            __syncwarp();
            mbar_arrive_if(elect, bars + 8 * B_S1);
        }
        if (warp == 8) {
            if (elect_one()) {
                const unsigned* flag = &get_acc()->cnt_o[rb * 128];
                uint4 hint = make_uint4(0, 0, 0, 0);
                mbar_wait(bars + 8 * B_O, 0);
#pragma unroll
                for (int i = 0; i < 16; i++) {
                    if (i < 4) {
                        unsigned it = 0;
#pragma unroll 1
                        while ((i == 0 ? hint.x : (i == 1 ? hint.y : (i == 2 ? hint.z : hint.w))) < 16u && ++it < (1u << 14)) hint = ld_gpu(reinterpret_cast<const uint4*>(&P.scr->hint[rb * 32]));
                    }
                    if (i == 4) poll_counter(flag + 32, 16);
                    if (i == 8) mbar_wait(bars + 8 * B_C1, 0);
                    if (i == 4 || i == 8) asm volatile("fence.proxy.async.global;" ::: "memory");
                    if ((i & 3) == 0 && i < 12) TL(i == 0 ? 21 : (i == 4 ? 34 : 36));
                    if (i == 4 || i > 5) mbar_wait(bars + 8 * (B_SD + max(i - 5, 0)), 0);
                    load_o(i, epoch & 1u);
                    if (i == 3) { load_wo(5); mbar_wait(bars + 8 * B_S1, 0); load_wo(6); }
                    if (i >= 5 && i < 14) load_wo(i + 2);
                }
            }
        } else if (warp == 9) {
            if (elect_one()) {
                unsigned* flag = &get_acc()->cnt_o[rb * 128];
                mbar_wait(bars + 8 * B_O, 0);
                asm volatile("red.release.gpu.global.add.u32 [%0], 1;" :: "l"(flag + 32) : "memory");
                TL(35);
            }
        } else if (warp == 10) {
            if (elect_one()) {
                unsigned* f = &get_acc()->cnt_o[rb * 128 + 96];
                mbar_wait(bars + 8 * (B_O + 1), 0);
                asm volatile("red.release.gpu.global.add.u32 [%0], 1;" :: "l"(f) : "memory");
                TL(37);
                poll_counter(f, 16);
                asm volatile("mbarrier.arrive.shared::cta.b64 _, [%0];" :: "r"(bars + 8 * B_C1) : "memory");
            }
        } else if (warp == 11) {
            const uint4 misc = lds128(sb + SM_MISC);
            if ((int)(misc.x >> 7) == rb * 2 + (hp & 1)) {
                float y[4] = {0.f, 0.f, 0.f, 0.f};
#pragma unroll 1
                for (int rep = 0; rep < 4; rep++) {
                    const float4* yp = &get_acc()->y[(rep * 4 + (lane >> 3)) * 96 + (hp >> 3) * 32 + (lane & 7) * 4 + ((hp >> 1) & 3)];
                    float4 u, v;
                    unsigned it = 0;
#pragma unroll 1
                    do { u = ld_gpu(yp); v = ld_gpu(yp + 32); } while (!__all_sync(0xffffffffu, u.w == 28.0f && v.w == 28.0f) && ++it < (1u << 20));
                    if (hp & 8) { y[0] += u.y; y[1] += v.x; y[2] += u.z; y[3] += v.y; } else { y[0] += u.x; y[1] += u.z; y[2] += u.y; y[3] += v.x; }
                }
                const uint32_t sg = __byte_perm(misc.y, 0, 0x3232), ya = sb + SM_Y + ((lane >> 3) * 16 + (lane & 7)) * 2;
                const uint32_t w0 = hmul2(pack_bf16(y[0], y[1]), sg), w1 = hmul2(pack_bf16(y[2], y[3]), sg);
                asm volatile("st.shared.u16 [%0], %1;" :: "r"(ya), "h"((uint16_t)w0) : "memory");
                asm volatile("st.shared.u16 [%0], %1;" :: "r"(ya + 16), "h"((uint16_t)(w0 >> 16)) : "memory");
                asm volatile("st.shared.u16 [%0], %1;" :: "r"(ya + 128), "h"((uint16_t)w1) : "memory");
                asm volatile("st.shared.u16 [%0], %1;" :: "r"(ya + 144), "h"((uint16_t)(w1 >> 16)) : "memory");
                __syncwarp();
                if (lane < 16) {
                    const uint4 xc = __ldg(reinterpret_cast<const uint4*>(P.x + (size_t)misc.x * D_ + (hp >> 1) * 128) + lane);
                    const uint32_t m2 = __byte_perm(lds32(sb + SM_MD + (misc.x & 255u) * 4), 0, 0x1010);
                    const float r = ldsf(sb + SM_RS + (misc.x & 255u) * 4);
                    const uint4 yv = lds128(sb + SM_Y + lane * 16);
                    sts128(sb + SM_Y + lane * 16, silu_pair(hadd2(ln_pair(xc.x, m2, r), yv.x)), silu_pair(hadd2(ln_pair(xc.y, m2, r), yv.y)),
                           silu_pair(hadd2(ln_pair(xc.z, m2, r), yv.z)), silu_pair(hadd2(ln_pair(xc.w, m2, r), yv.w)));
                    sts128(sb + SM_Y + 256 + lane * 16, xc.x, xc.y, xc.z, xc.w);
                }
                __syncwarp();
                mbar_arrive_if(elect, bars + 8 * B_Y);
                TLP(elect, 39);
            }
        }
    } else {
        const int wg = warp >> 2, w4 = warp & 3, g = lane >> 2;
        nb_sync(0, NTHREADS);
        asm volatile("setmaxnreg.inc.sync.aligned.u32 224;");
        TLP(tid == 0, 1);
        const int row0 = wg * 128 + w4 * 16 + g;
        float pq0[16], pq1[16];
        float rs[4];
        uint32_t f2[8], f3[8], q0[8], q1[8], q2[8], q3[8];
        const uint32_t wlo = dlo(sb + SM_WPHI, 16);
        const uint32_t sw0 = (uint32_t)(((w4 * 2) ^ (lane & 7)) * 16), sw1 = sw0 ^ 16u;
        {
            float acc0[96], acc1[96];
            {
                const uint32_t alo0 = dlo(sb + wg * 16384, 16), blo0 = dlo(sb + 32768, 8192);
                {
                    const uint32_t b0 = dlo(sb + 32768, 4096);
                    mbar_wait(bars + 8 * B_S0, 0);
                    mbar_wait(bars + 8 * (B_S0 + wg), 0);
                    TLP(tid == 0, 2); TLG(tid == 0, 49);
                    wgmma_fence();
#pragma unroll
                    for (int k = 0; k < 4; k++) {
                        if (k == 2) { wgmma_commit(); mbar_wait(bars + 8 * B_FULL, 0); wgmma_fence(); }
                        wgmma_ss_n192_tb(acc0, desc_from(alo0 + k * 2, DH128), desc_from(b0 + (k >> 1) * 768 + (k & 1) * 128, DH128), k);
                        wgmma_ss_n192_tb(acc1, desc_from(alo0 + 512 + k * 2, DH128), desc_from(b0 + (k >> 1) * 768 + (k & 1) * 128, DH128), k);
                    }
                    wgmma_commit();
                }
                int s = 1, ph = 0, ps = 0;
#pragma unroll 1
                for (int ks = 1; ks < 16; ks++) {
                    mbar_wait(bars + 8 * (B_FULL + s), ph);
                    const uint32_t alo = alo0 + s * (STAGE >> 4), blo = blo0 + s * (STAGE >> 4);
                    wgmma_fence();
#pragma unroll
                    for (int k = 0; k < 4; k++) {
                        wgmma_ss_n192_tb(acc0, desc_from(alo + k * 2, DH128), desc_from(blo + k * 128, DH128), 1);
                        wgmma_ss_n192_tb(acc1, desc_from(alo + 512 + k * 2, DH128), desc_from(blo + k * 128, DH128), 1);
                        if (k == 0) {
                            wgmma_commit();
                            wgmma_wait<1>();
                            mbar_arrive_if(elect, bars + 8 * (B_EMPTY + ps));
                        }
                    }
                    wgmma_commit();
                    ps = s;
                    if (++s == 3) { s = 0; ph ^= 1; }
                }
            }
            mbar_wait(bars + 8 * B_LN, 0);
            wgmma_fence();
            wgmma_ss_n192_tb(acc0, desc_from(dlo(sb + SM_AX + wg * 2048, 0), 128u >> 4), desc_from(dlo(sb + SM_BX, 1024), 1u << 30), 1);
            wgmma_ss_n192_tb(acc1, desc_from(dlo(sb + SM_AX + wg * 2048 + 1024, 0), 128u >> 4), desc_from(dlo(sb + SM_BX, 1024), 1u << 30), 1);
            wgmma_commit();
            mbar_wait(bars + 8 * (B_EMPTY + 2), 0);
            mbar_wait(bars + 8 * B_WPHI, 0);
            {
                uint32_t md[4];
#pragma unroll
                for (int i = 0; i < 4; i++) {
                    const int r = row0 + (i >> 1) * 64 + (i & 1) * 8;
                    md[i] = __byte_perm(lds32(sb + SM_MD + r * 4), 0, 0x3232);
                    rs[i] = ldsf(sb + SM_RS + r * 4);
                }
                const uint32_t zb = sb + SM_V + wg * 10240 + (lane >> 4) * 5120 + 4096 + (lane & 7) * 128 + (sw0 ^ ((lane & 8) * 2));
                stsm_t(zb, md[0], md[1], md[2], md[3]);
                stsm_t(zb + 20480, md[0], md[1], md[2], md[3]);
            }
            wgmma_wait<0>();
            fence_regs(acc0); fence_regs(acc1);
            TLP(tid == 0, 3); TLG(tid == 0, 50);
            const uint32_t vb = sb + SM_V + wg * 10240 + lane * 128;
            uint32_t f0[8], f1[8], v[8];
            pack_head<64>(acc0, v); stsm_t(vb + sw0, v[0], v[2], v[4], v[6]); stsm_t(vb + sw1, v[1], v[3], v[5], v[7]);
            pack_head<64>(acc1, v); stsm_t(vb + 5120 + sw0, v[0], v[2], v[4], v[6]); stsm_t(vb + 5120 + sw1, v[1], v[3], v[5], v[7]);
#pragma unroll
            for (int i = 32; i < 48; i++) { asm volatile("" : "+f"(acc0[i]) :: "memory"); asm volatile("" : "+f"(acc1[i]) :: "memory"); }
            pack_head<32>(acc0, f0); pack_head<32>(acc1, f1);
            wgmma_fence();
            feat_mma(pq0, f0, wlo); feat_mma(pq1, f1, wlo);
            wgmma_commit();
            pack_head<80>(acc0, v); stsm_t(vb + 20480 + sw0, v[0], v[2], v[4], v[6]); stsm_t(vb + 20480 + sw1, v[1], v[3], v[5], v[7]);
            pack_head<80>(acc1, v); stsm_t(vb + 25600 + sw0, v[0], v[2], v[4], v[6]); stsm_t(vb + 25600 + sw1, v[1], v[3], v[5], v[7]);
            pack_head<48>(acc0, f2); pack_head<48>(acc1, f3);
            pack_head<0>(acc0, q0); pack_head<0>(acc1, q1); pack_head<16>(acc0, q2); pack_head<16>(acc1, q3);
            fence_regs(f2); fence_regs(f3); fence_regs(q0); fence_regs(q1); fence_regs(q2); fence_regs(q3);
            wgmma_wait<0>();
            fence_regs(pq0); fence_regs(pq1); fence_regs(f0); fence_regs(f1);
            mbar_arrive_if(elect, bars + 8 * B_T);
            TLP(tid == 0, 4);
        }
#pragma unroll 1
        for (int h = 0; h < 2; h++) {
            const uint32_t pb = sb + SM_PHI + wg * 16384 + lane * 128 + h * 32768;
            key_head(pq0, pq1, rs, pb + sw0, pb + sw1);
            wgmma_fence();
            feat_mma(pq0, f2, wlo + 128 - h * 128); feat_mma(pq1, f3, wlo + 128 - h * 128);
            wgmma_commit();
            fence_async_smem();
            __syncwarp();
            mbar_arrive_if(elect, bars + 8 * (B_PHI + h));
            TLP(tid == 0, 6 + 2 * h);
            mbar_wait(bars + 8 * B_T, 0);
            wgmma_wait<0>();
            fence_regs(pq0); fence_regs(pq1); fence_regs(f2); fence_regs(f3);
#pragma unroll
            for (int j = 0; j < 8; j++) { f2[j] = q0[j]; f3[j] = q1[j]; }
            fence_regs(f2); fence_regs(f3);
        }
        const uint32_t par = lds32(sb + SM_MISC + 8) & 1u;
        unsigned* flag = &P.scr->acc[par].cnt_o[rb * 128];
        const int orow = (hp & 1) * 128 + wg * 64 + w4 * 16 + (lane >> 4);
        const size_t goff = (size_t)(rb * 256 + orow) * D_ + (hp >> 1) * 128 + (lane & 15) * 8;
        uint4 gv[8], xv[8];
#pragma unroll
        for (int i = 0; i < 8; i++) xv[i] = make_uint4(0, 0, 0, 0);
#pragma unroll
        for (int i = 0; i < GSPLIT2; i++) gv[i] = make_uint4(0, 0, 0, 0);
        const uint32_t rowc = sb + ((lane >> 3) & 1) * 16384 + (wg * 64 + w4 * 16 + (lane >> 4)) * 128;
        {
            __nv_bfloat16* od = P.o + (size_t)(par * S_ + rb * 256 + row0) * D_ + hp * 32 + (lane & 3) * 8;
#pragma unroll 1
            for (int h = 0; h < 2; h++) {
                uint32_t pa[8], na[8], pb[8], nb[8];
                features(pq0, pq1, rs, pa, na, pb, nb);
                TLP(tid == 0, 16 + h);
                if (h == 0) {
                    wgmma_fence();
                    feat_mma(pq0, q2, wlo + 128); feat_mma(pq1, q3, wlo + 128);
                    wgmma_commit();
                    mbar_wait(bars + 8 * B_X, 0);
#pragma unroll
                    for (int i = 0; i < 8; i++) xv[i] = lds128(rowc + i * 256 + (((lane & 7) ^ ((2 * i + (lane >> 4)) & 7)) * 16));
#pragma unroll
                    for (int i = 0; i < GSPLIT; i++) { gv[i] = xv[i]; gate_item(gv[i], sb, orow + 2 * i); }
                    wgmma_wait<0>();
                    fence_regs(pq0); fence_regs(pq1); fence_regs(q2); fence_regs(q3);
                    TLP(tid == 0, 18);
                } else {
#pragma unroll
                    for (int i = GSPLIT; i < GSPLIT2; i++) { gv[i] = xv[i]; gate_item(gv[i], sb, orow + 2 * i); }
                    TLP(tid == 0, 10);
                }
                {
                    float d0[20], e0[20], d1[20], e1[20];
                    const uint32_t klo = dlo(sb + SM_KVOP - h * 5120, 128);
                    fence_regs(pa); fence_regs(na); fence_regs(pb); fence_regs(nb);
                    mbar_wait(bars + 8 * (B_KV + h), 0);
                    TLP(tid == 0, 32 + h);
                    wgmma_fence();
                    o_mma(d0, e0, pa, na, klo);
                    o_mma(d1, e1, pb, nb, klo);
                    wgmma_commit();
                    wgmma_wait<0>();
                    fence_regs(d0); fence_regs(e0); fence_regs(pa); fence_regs(na);
                    fence_regs(d1); fence_regs(e1); fence_regs(pb); fence_regs(nb);
                    o_store(d0, e0, od + h * 512);
                    o_store(d1, e1, od + h * 512 + 64 * D_);
                    __syncwarp();
                    if (!h && hp < 8 && elect) asm volatile("red.relaxed.gpu.global.add.u32 [%0], 1;" :: "l"(&P.scr->hint[rb * 32 + (hp >> 1)]) : "memory");
                    mbar_arrive_if(elect, bars + 8 * (B_O + h));
                }
                TLP(tid == 0, 9 + 2 * h);
            }
        }
        float ghr[8], ghm[8];
#pragma unroll
        for (int i = GSPLIT2; i < 8; i++) { ghr[i] = 0.5f * ldsf(sb + SM_RS + (orow + 2 * i) * 4); ghm[i] = -bf_lo(lds32(sb + SM_MD + (orow + 2 * i) * 4)) * ghr[i]; }
        float acc[64];
        {
            const uint32_t alo0 = dlo(sb + wg * 8192, 16), blo0 = dlo(sb, 8192);
            const uint32_t ta0 = sb + (wg * 64 + w4 * 16) * 128 + lane * 16;
            uint4 cv[2][4];
#pragma unroll
            for (int i = 0; i < 1; i++) {
                mbar_wait(bars + 8 * (B_OF + i), 0);
#pragma unroll
                for (int j = 0; j < 4; j++) cv[i][j] = lds128(ta0 + i * 16384 + j * 512);
            }
#pragma unroll
            for (int i = 0; i < 16; i++) {
                const uint32_t alo = alo0 + o_slot(i) * 1024, blo = blo0 + wo_slot(i) * 1024;
                if (i < 4) {
                    bool bad = false;
#pragma unroll
                    for (int j = 0; j < 4; j++) bad |= (cv[i & 1][j].x | cv[i & 1][j].y | cv[i & 1][j].z | cv[i & 1][j].w) == 0u;
                    if (__builtin_expect(__any_sync(0xffffffffu, bad), 0)) {
                        poll_counter(flag + 32, 16);
#pragma unroll 1
                        for (int j = 0; j < 4; j++) {
                            const int r = j * 4 + (lane >> 3);
                            const uint4 v = ld_gpu(reinterpret_cast<const uint4*>(P.o + (size_t)(par * S_ + rb * 256 + (orow & ~1) + r) * D_ + i * 64) + ((lane ^ r) & 7));
                            sts128(ta0 + (i & 3) * 16384 + j * 512, v.x, v.y, v.z, v.w);
                        }
                        fence_async_smem();
                        __syncwarp();
                    }
                } else {
                    mbar_wait(bars + 8 * (B_OF + i), 0);
                }
                if (i == OSTAG && wg == 0) nb_sync(NB_STAG, 256);
                wgmma_fence();
#pragma unroll
                for (int k = 0; k < 4; k++) {
                    if (i == 15 && k == OARR && wg) nb_arrive(NB_STAG, 256);
                    wgmma_ss_n128_tb(acc, desc_from(alo + k * 2, DH128), desc_from(blo + k * 128, DH128), k | i);
                    if (k == OREL) {
                        if (i > 0 && i < 12) {
                            wgmma_commit();
                            wgmma_wait<1>();
                            mbar_arrive_if(elect, bars + 8 * (B_SD + i - 1));
                        }
                    }
                }
                wgmma_commit();
                if (i == 0) { TLP(tid == 0, 12); TLG(tid == 0, 51); }
                if (i < 3) {
                    mbar_wait(bars + 8 * (B_OF + i + 1), 0);
#pragma unroll
                    for (int j = 0; j < 4; j++) cv[~i & 1][j] = lds128(ta0 + (i + 1) * 16384 + j * 512);
                }
                static_assert(2 * (8 - GSPLIT2) <= 16 - GST, "");
                if (i >= GST && GSPLIT2 + (i - GST) / 2 < 8) {
                    const int q = GSPLIT2 + (i - GST) / 2;
                    if ((i - GST) & 1) { gv[q].z = gate_pair(xv[q].z, ghr[q], ghm[q]); gv[q].w = gate_pair(xv[q].w, ghr[q], ghm[q]); asm volatile("" : "+r"(gv[q].z), "+r"(gv[q].w) :: "memory"); }
                    else { gv[q].x = gate_pair(xv[q].x, ghr[q], ghm[q]); gv[q].y = gate_pair(xv[q].y, ghr[q], ghm[q]); asm volatile("" : "+r"(gv[q].x), "+r"(gv[q].y) :: "memory"); }
                }
            }
        }
        wgmma_wait<0>();
        fence_regs(acc);
        TLP(tid == 0, 13); TLG(tid == 0, 52);
        {
            const uint32_t stg = sb + (wg * 64 + w4 * 16) * 128;
            const int rr = lane & 7;
#pragma unroll
            for (int c = 0; c < 4; c++) {
                const uint32_t a0 = stg + (c >> 1) * 16384 + rr * 128 + ((((c & 1) * 4 + (lane >> 3)) ^ rr) * 16);
                stsm(a0, pack_bf16(acc[c * 16 + 0], acc[c * 16 + 1]), pack_bf16(acc[c * 16 + 4], acc[c * 16 + 5]),
                     pack_bf16(acc[c * 16 + 8], acc[c * 16 + 9]), pack_bf16(acc[c * 16 + 12], acc[c * 16 + 13]));
                stsm(a0 + 1024, pack_bf16(acc[c * 16 + 2], acc[c * 16 + 3]), pack_bf16(acc[c * 16 + 6], acc[c * 16 + 7]),
                     pack_bf16(acc[c * 16 + 10], acc[c * 16 + 11]), pack_bf16(acc[c * 16 + 14], acc[c * 16 + 15]));
            }
            __syncwarp();
#pragma unroll
            for (int i = 0; i < 8; i++) {
                const uint4 sv = lds128(rowc + i * 256 + (((lane & 7) ^ ((2 * i + (lane >> 4)) & 7)) * 16));
                uint4 o;
                o.x = hadd2(xv[i].x, hmul2(sv.x, gv[i].x)); o.y = hadd2(xv[i].y, hmul2(sv.y, gv[i].y));
                o.z = hadd2(xv[i].z, hmul2(sv.z, gv[i].z)); o.w = hadd2(xv[i].w, hmul2(sv.w, gv[i].w));
                *reinterpret_cast<uint4*>(P.out + goff + (size_t)i * 2 * D_) = o;
            }
            const uint32_t sel = lds32(sb + SM_MISC);
            if ((int)(sel >> 4) == rb * 16 + (orow >> 4)) {
                mbar_wait(bars + 8 * B_Y, 0);
                if ((sel & 1u) == (uint32_t)(lane >> 4)) {
                    const int i = (sel & 15u) >> 1;
                    const uint4 sv = lds128(rowc + i * 256 + (((lane & 7) ^ (sel & 7u)) * 16));
                    const uint4 gq = lds128(sb + SM_Y + (lane & 15) * 16), xq = lds128(sb + SM_Y + 256 + (lane & 15) * 16);
                    *reinterpret_cast<uint4*>(P.out + goff + (size_t)i * 2 * D_) = make_uint4(hadd2(xq.x, hmul2(sv.x, gq.x)), hadd2(xq.y, hmul2(sv.y, gq.y)), hadd2(xq.z, hmul2(sv.z, gq.z)), hadd2(xq.w, hmul2(sv.w, gq.w)));
                }
            }
        }
        TLG(tid == 0, 53);
        if (tid == 0) { TL(14); TL_DUMP(); }
        if (blockIdx.x == 0 && tid == 0) asm volatile("st.relaxed.gpu.global.u32 [%0], %1;" :: "l"(&P.scr->epoch), "r"(lds32(sb + SM_MISC + 8) + 1u) : "memory");
    }
}

typedef CUresult (*PFN_encodeTiled)(CUtensorMap*, CUtensorMapDataType, cuuint32_t, void*, const cuuint64_t*, const cuuint64_t*,
                                    const cuuint32_t*, const cuuint32_t*, CUtensorMapInterleave, CUtensorMapSwizzle,
                                    CUtensorMapL2promotion, CUtensorMapFloatOOBfill);

void make_map(PFN_encodeTiled fn, CUtensorMap* m, const void* ptr, int rank, const cuuint64_t* dims, const cuuint64_t* strides, const cuuint32_t* box, CUtensorMapSwizzle sw) {
    const cuuint32_t es[5] = {1, 1, 1, 1, 1};
    fn(m, CU_TENSOR_MAP_DATA_TYPE_BFLOAT16, rank, const_cast<void*>(ptr), dims, strides, box, es, CU_TENSOR_MAP_INTERLEAVE_NONE,
       sw, CU_TENSOR_MAP_L2_PROMOTION_L2_256B, CU_TENSOR_MAP_FLOAT_OOB_FILL_NONE);
}
void make_2d(PFN_encodeTiled fn, CUtensorMap* m, const void* ptr, uint64_t rows, uint64_t cols, uint32_t box_rows, uint32_t box_cols, CUtensorMapSwizzle sw) {
    const cuuint64_t gd[2] = {cols, rows}, gs[1] = {cols * 2};
    const cuuint32_t bd[2] = {box_cols, box_rows};
    make_map(fn, m, ptr, 2, gd, gs, bd, sw);
}

}

extern "C" void kernel_launch(void* const* d_in, const int* in_sizes, int n_in, void* d_out, int out_size) {
    (void)in_sizes; (void)n_in; (void)out_size;
    static PFN_encodeTiled fn = nullptr;
    static void* o_ptr = nullptr;
    static void* scr_ptr = nullptr;
    static void* tl_ptr = nullptr;
    if (!fn) {
        void* p = nullptr;
        cudaDriverEntryPointQueryResult st;
        cudaGetDriverEntryPoint("cuTensorMapEncodeTiled", &p, cudaEnableDefault, &st);
        fn = (PFN_encodeTiled)p;
        cudaGetSymbolAddress(&o_ptr, g_o);
        cudaGetSymbolAddress(&scr_ptr, g_scr);
        cudaFuncSetAttribute(fused_kernel, cudaFuncAttributeMaxDynamicSharedMemorySize, SM_TOTAL);
    }
    CUtensorMap tmX, tmW, tmPhi, tmWo, tmO, tmX2, tmW0;
    SideMaps tmS;
    make_2d(fn, &tmX, d_in[0], S_, D_, 256, 64, CU_TENSOR_MAP_SWIZZLE_128B);
    {
        const cuuint64_t gd[3] = {1024, 1024, 3}, gs[2] = {6144, 2048};
        const cuuint32_t bd[3] = {64, 64, 3};
        make_map(fn, &tmW, d_in[1], 3, gd, gs, bd, CU_TENSOR_MAP_SWIZZLE_128B);
        const cuuint32_t bd0[3] = {64, 32, 3};
        make_map(fn, &tmW0, d_in[1], 3, gd, gs, bd0, CU_TENSOR_MAP_SWIZZLE_128B);
    }
    make_2d(fn, &tmS.wc, d_in[1], D_, 3 * D_, 32, 64, CU_TENSOR_MAP_SWIZZLE_NONE);
    make_2d(fn, &tmPhi, d_in[2], 1024, 32, 64, 32, CU_TENSOR_MAP_SWIZZLE_64B);
    make_2d(fn, &tmS.wg, d_in[6], D_, F_, 32, 32, CU_TENSOR_MAP_SWIZZLE_NONE);
    make_2d(fn, &tmS.wu, d_in[7], D_, F_, 32, 32, CU_TENSOR_MAP_SWIZZLE_NONE);
    make_2d(fn, &tmS.wgt, d_in[6], D_, F_, 256, 32, CU_TENSOR_MAP_SWIZZLE_64B);
    make_2d(fn, &tmS.wut, d_in[7], D_, F_, 256, 32, CU_TENSOR_MAP_SWIZZLE_64B);
    {
        const cuuint64_t gd[3] = {64, F_, 16}, gs[2] = {2048, 128};
        const cuuint32_t bd[3] = {64, 32, 8};
        make_map(fn, &tmS.wd8, d_in[8], 3, gd, gs, bd, CU_TENSOR_MAP_SWIZZLE_128B);
    }
    {
        const cuuint64_t gd[4] = {64, 64, 16, 16}, gs[3] = {2048, 64 * 2048, 128};
        const cuuint32_t bd[4] = {64, 32, 2, 2};
        make_map(fn, &tmWo, d_in[3], 4, gd, gs, bd, CU_TENSOR_MAP_SWIZZLE_128B);
    }
    make_2d(fn, &tmO, o_ptr, 2 * S_, D_, 128, 64, CU_TENSOR_MAP_SWIZZLE_128B);
    make_2d(fn, &tmX2, d_in[0], S_, D_, 128, 64, CU_TENSOR_MAP_SWIZZLE_128B);
    Params P;
    P.x = (const __nv_bfloat16*)d_in[0];
    P.wr = (const __nv_bfloat16*)d_in[5];
    P.wqkv = (const __nv_bfloat16*)d_in[1];
    P.wg = (const __nv_bfloat16*)d_in[6];
    P.wu = (const __nv_bfloat16*)d_in[7];
    P.wd = (const __nv_bfloat16*)d_in[8];
    P.wo = (const __nv_bfloat16*)d_in[3];
    P.out = (__nv_bfloat16*)d_out;
    P.o = (__nv_bfloat16*)o_ptr;
    P.scr = (Scratch*)scr_ptr;
    P.tl = (unsigned long long*)tl_ptr;
    cudaLaunchConfig_t cfg = {};
    cfg.gridDim = dim3(NCTA); cfg.blockDim = dim3(NTHREADS); cfg.dynamicSmemBytes = SM_TOTAL; cfg.stream = cudaStreamPerThread;
    cudaLaunchAttribute at[1];
    at[0].id = cudaLaunchAttributeCooperative; at[0].val.cooperative = 1;
    cfg.attrs = at; cfg.numAttrs = 1;
    cudaLaunchKernelEx(&cfg, fused_kernel, tmW0, tmX2, tmX, tmW, P, tmS, tmPhi, tmWo, tmO);
}
```

```cpp
#include <cuda_runtime.h>
#include <cuda_bf16.h>
#include <cuda.h>
#include <stdint.h>

namespace {

constexpr int S_ = 2048, D_ = 1024, F_ = 3584;
constexpr int NCTA = 128, NTHREADS = 384;
#define POLL_NS 100
#define OREL 1
#define OSTAG 12
#define OARR 2
#define NC0 3
#define NC2 4
#define NG0 12
#define NG1 12
#define GSPLIT 1
#define GSPLIT2 2
#define GST 3
#define JWO 12

constexpr int STAGE = 57344;
constexpr int SM_PHI = 0;
constexpr int SM_V = 131072;
constexpr int SM_AX = 172032;
constexpr int SM_BX = 176128;
constexpr int SM_SP = 172032;
constexpr int SM_FB = 180224;
constexpr int SM_XS = 221184;
constexpr int SM_KVOP = 172032;
constexpr int SM_MD = 223232;
constexpr int SM_RS = 224256;
constexpr int SM_Y = 225280;
constexpr int SM_GU = 225536;
constexpr int SM_MISC = 226688;
constexpr int SM_H = 179200;
constexpr int SM_BARS = 226816;
constexpr int SM_WPHI = 227840;
constexpr int SM_TOTAL = 232448;

constexpr int B_FULL = 0, B_EMPTY = 3, B_OF = 6, B_SD = 22, B_O = 33, B_PHI = 35, B_T = 37, B_WPHI = 38, B_Y = 39, B_KV = 40, B_LN = 42, B_S1 = 43, B_FF = 44, B_X = 54, B_C1 = 55, B_DN = 56, B_XS = 58, B_COUNT = 59, B_XR = 59, B_S0 = 60;
constexpr int NB_KV = 1, NB_FFN = 2, NB_AUX = 3, NB_DN = 4, NB_STAG = 5;
__device__ __forceinline__ int o_slot(int i) { const int r = i % 5; return r == 4 ? 10 : r; }
__device__ __forceinline__ int wo_slot(int i) { const int r = i % 7; return r == 6 ? 11 : 4 + r; }

struct __align__(128) Acc {
    float4 cs[48 * 8 * 3];
    float4 y[4 * 4 * 3 * 32];
    unsigned cnt_o[16 * 64];
};
constexpr int ACC_VEC_PER_CTA = (int)(sizeof(Acc) / 16 / NCTA);
static_assert(sizeof(Acc) == ACC_VEC_PER_CTA * 16 * NCTA && ACC_VEC_PER_CTA <= 256, "");
struct __align__(128) Scratch {
    Acc acc[2];
    uint4 kv[32 * 4 * 3 * 32];
    unsigned hint[8 * 32];
    uint2 rows[S_];
    uint4 best[NCTA];
    unsigned epoch;
};
__device__ Scratch g_scr;
__device__ __align__(1024) __nv_bfloat16 g_o[2 * S_ * D_];

#define TL(e) do {} while (0)
#define TLP(c, e) do {} while (0)
#define TLG(c, e) do {} while (0)
#define TL_DUMP() do {} while (0)

struct SideMaps { CUtensorMap wc, wg, wu, wd8; };
struct Params {
    const __nv_bfloat16* x;
    const __nv_bfloat16* wr;
    const __nv_bfloat16* wqkv;
    const __nv_bfloat16* wg;
    const __nv_bfloat16* wu;
    const __nv_bfloat16* wd;
    const __nv_bfloat16* wo;
    __nv_bfloat16* out;
    __nv_bfloat16* o;
    Scratch* scr;
    unsigned long long* tl;
};

__device__ __forceinline__ bool elect_one() {
    uint32_t p; asm volatile("{\n.reg .pred q;\nelect.sync _|q, 0xffffffff;\nselp.u32 %0, 1, 0, q;\n}" : "=r"(p)); return p;
}
__device__ __forceinline__ uint32_t smem_u32(const void* p) { return (uint32_t)__cvta_generic_to_shared(p); }
__device__ __forceinline__ void mbar_init(uint32_t bar, uint32_t cnt) { asm volatile("mbarrier.init.shared::cta.b64 [%0], %1;" :: "r"(bar), "r"(cnt) : "memory"); }
__device__ __forceinline__ void mbar_expect_tx(uint32_t bar, uint32_t bytes) { asm volatile("mbarrier.arrive.expect_tx.shared::cta.b64 _, [%0], %1;" :: "r"(bar), "r"(bytes) : "memory"); }
__device__ __forceinline__ void mbar_arrive_if(bool p, uint32_t bar) {
    asm volatile("{\n.reg .pred q;\nsetp.ne.b32 q, %1, 0;\n@q mbarrier.arrive.shared::cta.b64 _, [%0];\n}" :: "r"(bar), "r"((int)p) : "memory");
}
__device__ __forceinline__ void mbar_wait(uint32_t bar, uint32_t parity) {
    asm volatile("{\n.reg .pred p;\n.reg .u32 n;\nmov.u32 n, 0;\n"
                 "WAIT_LOOP:\nmbarrier.try_wait.parity.shared::cta.b64 p, [%0], %1;\n@p bra WAIT_DONE;\n"
                 "add.u32 n, n, 1;\nsetp.lt.u32 p, n, 0x40000;\n@p bra WAIT_LOOP;\nWAIT_DONE:\n}" :: "r"(bar), "r"(parity) : "memory");
}
__device__ __forceinline__ bool mbar_test(uint32_t bar, uint32_t parity) {
    uint32_t ok;
    asm volatile("{\n.reg .pred p;\nmbarrier.test_wait.parity.shared::cta.b64 p, [%1], %2;\nselp.u32 %0, 1, 0, p;\n}" : "=r"(ok) : "r"(bar), "r"(parity) : "memory");
    return __all_sync(0xffffffffu, ok);
}
__device__ __forceinline__ void tma_2d(uint32_t dst, const CUtensorMap* tm, uint32_t bar, int c0, int c1) {
    asm volatile("cp.async.bulk.tensor.2d.shared::cluster.global.mbarrier::complete_tx::bytes [%0], [%1, {%3, %4}], [%2];"
        :: "r"(dst), "l"(tm), "r"(bar), "r"(c0), "r"(c1) : "memory");
}
__device__ __forceinline__ void tma_3d(uint32_t dst, const CUtensorMap* tm, uint32_t bar, int c0, int c1, int c2) {
    asm volatile("cp.async.bulk.tensor.3d.shared::cluster.global.mbarrier::complete_tx::bytes [%0], [%1, {%3, %4, %5}], [%2];"
        :: "r"(dst), "l"(tm), "r"(bar), "r"(c0), "r"(c1), "r"(c2) : "memory");
}
__device__ __forceinline__ void tma_4d(uint32_t dst, const CUtensorMap* tm, uint32_t bar, int c0, int c1, int c2, int c3) {
    asm volatile("cp.async.bulk.tensor.4d.shared::cluster.global.mbarrier::complete_tx::bytes [%0], [%1, {%3, %4, %5, %6}], [%2];"
        :: "r"(dst), "l"(tm), "r"(bar), "r"(c0), "r"(c1), "r"(c2), "r"(c3) : "memory");
}
__device__ __forceinline__ void prefetch_l2(const void* p, uint32_t bytes) { asm volatile("cp.async.bulk.prefetch.L2.global [%0], %1;" :: "l"(p), "r"(bytes) : "memory"); }
__device__ __forceinline__ void wgmma_fence() { asm volatile("wgmma.fence.sync.aligned;" ::: "memory"); }
__device__ __forceinline__ void wgmma_commit() { asm volatile("wgmma.commit_group.sync.aligned;" ::: "memory"); }
template <int N> __device__ __forceinline__ void wgmma_wait() { asm volatile("wgmma.wait_group.sync.aligned %0;" :: "n"(N) : "memory"); }
template <int N> __device__ __forceinline__ void fence_regs(float (&a)[N]) {
#pragma unroll
    for (int i = 0; i < N; i++) asm volatile("" : "+f"(a[i]) :: "memory");
}
template <int N> __device__ __forceinline__ void fence_regs(uint32_t (&a)[N]) {
#pragma unroll
    for (int i = 0; i < N; i++) asm volatile("" : "+r"(a[i]) :: "memory");
}
__device__ __forceinline__ uint64_t desc_from(uint32_t lo, uint32_t hi) { uint64_t d; asm("mov.b64 %0, {%1, %2};" : "=l"(d) : "r"(lo), "r"(hi)); return d; }
__device__ __forceinline__ uint32_t dlo(uint32_t addr, uint32_t lbo) { return ((addr & 0x3FFFF) >> 4) | ((lbo >> 4) << 16); }
__device__ __forceinline__ void nb_sync(int id, int cnt) { asm volatile("bar.sync %0, %1;" :: "r"(id), "r"(cnt) : "memory"); }
__device__ __forceinline__ void nb_arrive(int id, int cnt) { asm volatile("bar.arrive %0, %1;" :: "r"(id), "r"(cnt) : "memory"); }
__device__ __forceinline__ void fence_async_smem() { asm volatile("fence.proxy.async.shared::cta;" ::: "memory"); }
__device__ __forceinline__ void red_v4(float4* p, float a, float b, float c, float d) {
    asm volatile("red.relaxed.gpu.global.add.v4.f32 [%0], {%1, %2, %3, %4};" :: "l"(p), "f"(a), "f"(b), "f"(c), "f"(d) : "memory");
}
__device__ __forceinline__ void red_h8(uint4* p, uint32_t a, uint32_t b, uint32_t c, uint32_t d) {
    asm volatile("red.relaxed.gpu.global.add.noftz.v4.f16x2 [%0], {%1, %2, %3, %4};" :: "l"(p), "r"(a), "r"(b), "r"(c), "r"(d) : "memory");
}
__device__ __forceinline__ float4 ld_gpu(const float4* p) {
    float4 v; asm volatile("ld.relaxed.gpu.global.v4.f32 {%0, %1, %2, %3}, [%4];" : "=f"(v.x), "=f"(v.y), "=f"(v.z), "=f"(v.w) : "l"(p) : "memory"); return v;
}
__device__ __forceinline__ uint4 ld_gpu(const uint4* p) {
    uint4 v; asm volatile("ld.relaxed.gpu.global.v4.u32 {%0, %1, %2, %3}, [%4];" : "=r"(v.x), "=r"(v.y), "=r"(v.z), "=r"(v.w) : "l"(p) : "memory"); return v;
}
__device__ __forceinline__ void poll_counter(const unsigned* p, unsigned target) {
    unsigned it = 0, v;
#pragma unroll 1
    do {
        asm volatile("ld.acquire.gpu.global.u32 %0, [%1];" : "=r"(v) : "l"(p) : "memory");
    } while (v < target && ++it < (1u << 20));
}
__device__ __forceinline__ uint32_t pack_bf16(float lo, float hi) { uint32_t r; asm("cvt.rn.bf16x2.f32 %0, %1, %2;" : "=r"(r) : "f"(hi), "f"(lo)); return r; }
__device__ __forceinline__ uint32_t pack_f16(float lo, float hi) { uint32_t r; asm("cvt.rn.f16x2.f32 %0, %1, %2;" : "=r"(r) : "f"(hi), "f"(lo)); return r; }
__device__ __forceinline__ float2 unpack_f16(uint32_t v) { float2 r; asm("{\n.reg .f16 l, h;\nmov.b32 {l, h}, %2;\ncvt.f32.f16 %0, l;\ncvt.f32.f16 %1, h;\n}" : "=f"(r.x), "=f"(r.y) : "r"(v)); return r; }
__device__ __forceinline__ float bf_lo(uint32_t v) { return __uint_as_float(v << 16); }
__device__ __forceinline__ float bf_hi(uint32_t v) { return __uint_as_float(v & 0xFFFF0000u); }
__device__ __forceinline__ float round_bf16(float v) { return bf_lo(pack_bf16(v, 0.f)); }
__device__ __forceinline__ float ex2(float v) { float r; asm("ex2.approx.ftz.f32 %0, %1;" : "=f"(r) : "f"(v)); return r; }
__device__ __forceinline__ float rcp(float v) { float r; asm("rcp.approx.ftz.f32 %0, %1;" : "=f"(r) : "f"(v)); return r; }
__device__ __forceinline__ float sqrt_a(float v) { float r; asm("sqrt.approx.f32 %0, %1;" : "=f"(r) : "f"(v)); return r; }
__device__ __forceinline__ void stsm(uint32_t addr, uint32_t r0, uint32_t r1, uint32_t r2, uint32_t r3) {
    asm volatile("stmatrix.sync.aligned.m8n8.x4.shared.b16 [%0], {%1, %2, %3, %4};" :: "r"(addr), "r"(r0), "r"(r1), "r"(r2), "r"(r3) : "memory");
}
__device__ __forceinline__ void stsm_t(uint32_t addr, uint32_t r0, uint32_t r1, uint32_t r2, uint32_t r3) {
    asm volatile("stmatrix.sync.aligned.m8n8.x4.trans.shared.b16 [%0], {%1, %2, %3, %4};" :: "r"(addr), "r"(r0), "r"(r1), "r"(r2), "r"(r3) : "memory");
}
__device__ __forceinline__ uint4 lds128(uint32_t addr) {
    uint4 v; asm volatile("ld.shared.v4.u32 {%0, %1, %2, %3}, [%4];" : "=r"(v.x), "=r"(v.y), "=r"(v.z), "=r"(v.w) : "r"(addr) : "memory"); return v;
}
__device__ __forceinline__ void sts128(uint32_t addr, uint32_t a, uint32_t b, uint32_t c, uint32_t d) {
    asm volatile("st.shared.v4.u32 [%0], {%1, %2, %3, %4};" :: "r"(addr), "r"(a), "r"(b), "r"(c), "r"(d) : "memory");
}
__device__ __forceinline__ void sts64(uint32_t addr, uint32_t a, uint32_t b) { asm volatile("st.shared.v2.u32 [%0], {%1, %2};" :: "r"(addr), "r"(a), "r"(b) : "memory"); }
__device__ __forceinline__ uint32_t lds32(uint32_t addr) { uint32_t v; asm volatile("ld.shared.u32 %0, [%1];" : "=r"(v) : "r"(addr) : "memory"); return v; }
__device__ __forceinline__ float ldsf(uint32_t addr) { return __uint_as_float(lds32(addr)); }
__device__ __forceinline__ void sts32(uint32_t addr, uint32_t v) { asm volatile("st.shared.u32 [%0], %1;" :: "r"(addr), "r"(v) : "memory"); }
__device__ __forceinline__ uint32_t hmul2(uint32_t a, uint32_t b) { uint32_t r; asm("mul.rn.bf16x2 %0, %1, %2;" : "=r"(r) : "r"(a), "r"(b)); return r; }
__device__ __forceinline__ uint32_t hadd2(uint32_t a, uint32_t b) { uint32_t r; asm("add.rn.bf16x2 %0, %1, %2;" : "=r"(r) : "r"(a), "r"(b)); return r; }
__device__ __forceinline__ uint32_t hsub2(uint32_t a, uint32_t b) { uint32_t r; asm("sub.rn.bf16x2 %0, %1, %2;" : "=r"(r) : "r"(a), "r"(b)); return r; }

__device__ __forceinline__ void wgmma_ss_n192_tb(float (&d)[96], uint64_t da, uint64_t db, int scale_d) {
    asm volatile(
        "{\n.reg .pred p;\nsetp.ne.b32 p, %98, 0;\n"
        "wgmma.mma_async.sync.aligned.m64n192k16.f32.bf16.bf16 "
        "{%0, %1, %2, %3, %4, %5, %6, %7, %8, %9, %10, %11, %12, %13, %14, %15, %16, %17, %18, %19, %20, %21, %22, %23, %24, %25, %26, %27, %28, %29, %30, %31, %32, %33, %34, %35, %36, %37, %38, %39, %40, %41, %42, %43, %44, %45, %46, %47, %48, %49, %50, %51, %52, %53, %54, %55, %56, %57, %58, %59, %60, %61, %62, %63, %64, %65, %66, %67, %68, %69, %70, %71, %72, %73, %74, %75, %76, %77, %78, %79, %80, %81, %82, %83, %84, %85, %86, %87, %88, %89, %90, %91, %92, %93, %94, %95}, %96, %97, p, 1, 1, 0, 1;\n}\n"
        : "+f"(d[0]), "+f"(d[1]), "+f"(d[2]), "+f"(d[3]), "+f"(d[4]), "+f"(d[5]), "+f"(d[6]), "+f"(d[7]), "+f"(d[8]), "+f"(d[9]), "+f"(d[10]), "+f"(d[11]), "+f"(d[12]), "+f"(d[13]), "+f"(d[14]), "+f"(d[15]), "+f"(d[16]), "+f"(d[17]), "+f"(d[18]), "+f"(d[19]), "+f"(d[20]), "+f"(d[21]), "+f"(d[22]), "+f"(d[23]), "+f"(d[24]), "+f"(d[25]), "+f"(d[26]), "+f"(d[27]), "+f"(d[28]), "+f"(d[29]), "+f"(d[30]), "+f"(d[31]), "+f"(d[32]), "+f"(d[33]), "+f"(d[34]), "+f"(d[35]), "+f"(d[36]), "+f"(d[37]), "+f"(d[38]), "+f"(d[39]), "+f"(d[40]), "+f"(d[41]), "+f"(d[42]), "+f"(d[43]), "+f"(d[44]), "+f"(d[45]), "+f"(d[46]), "+f"(d[47]), "+f"(d[48]), "+f"(d[49]), "+f"(d[50]), "+f"(d[51]), "+f"(d[52]), "+f"(d[53]), "+f"(d[54]), "+f"(d[55]), "+f"(d[56]), "+f"(d[57]), "+f"(d[58]), "+f"(d[59]), "+f"(d[60]), "+f"(d[61]), "+f"(d[62]), "+f"(d[63]), "+f"(d[64]), "+f"(d[65]), "+f"(d[66]), "+f"(d[67]), "+f"(d[68]), "+f"(d[69]), "+f"(d[70]), "+f"(d[71]), "+f"(d[72]), "+f"(d[73]), "+f"(d[74]), "+f"(d[75]), "+f"(d[76]), "+f"(d[77]), "+f"(d[78]), "+f"(d[79]), "+f"(d[80]), "+f"(d[81]), "+f"(d[82]), "+f"(d[83]), "+f"(d[84]), "+f"(d[85]), "+f"(d[86]), "+f"(d[87]), "+f"(d[88]), "+f"(d[89]), "+f"(d[90]), "+f"(d[91]), "+f"(d[92]), "+f"(d[93]), "+f"(d[94]), "+f"(d[95])
        : "l"(da), "l"(db), "r"(scale_d));
}
__device__ __forceinline__ void wgmma_ss_n128_tb(float (&d)[64], uint64_t da, uint64_t db, int scale_d) {
    asm volatile(
        "{\n.reg .pred p;\nsetp.ne.b32 p, %66, 0;\n"
        "wgmma.mma_async.sync.aligned.m64n128k16.f32.bf16.bf16 "
        "{%0, %1, %2, %3, %4, %5, %6, %7, %8, %9, %10, %11, %12, %13, %14, %15, %16, %17, %18, %19, %20, %21, %22, %23, %24, %25, %26, %27, %28, %29, %30, %31, %32, %33, %34, %35, %36, %37, %38, %39, %40, %41, %42, %43, %44, %45, %46, %47, %48, %49, %50, %51, %52, %53, %54, %55, %56, %57, %58, %59, %60, %61, %62, %63}, %64, %65, p, 1, 1, 0, 1;\n}\n"
        : "+f"(d[0]), "+f"(d[1]), "+f"(d[2]), "+f"(d[3]), "+f"(d[4]), "+f"(d[5]), "+f"(d[6]), "+f"(d[7]), "+f"(d[8]), "+f"(d[9]), "+f"(d[10]), "+f"(d[11]), "+f"(d[12]), "+f"(d[13]), "+f"(d[14]), "+f"(d[15]), "+f"(d[16]), "+f"(d[17]), "+f"(d[18]), "+f"(d[19]), "+f"(d[20]), "+f"(d[21]), "+f"(d[22]), "+f"(d[23]), "+f"(d[24]), "+f"(d[25]), "+f"(d[26]), "+f"(d[27]), "+f"(d[28]), "+f"(d[29]), "+f"(d[30]), "+f"(d[31]), "+f"(d[32]), "+f"(d[33]), "+f"(d[34]), "+f"(d[35]), "+f"(d[36]), "+f"(d[37]), "+f"(d[38]), "+f"(d[39]), "+f"(d[40]), "+f"(d[41]), "+f"(d[42]), "+f"(d[43]), "+f"(d[44]), "+f"(d[45]), "+f"(d[46]), "+f"(d[47]), "+f"(d[48]), "+f"(d[49]), "+f"(d[50]), "+f"(d[51]), "+f"(d[52]), "+f"(d[53]), "+f"(d[54]), "+f"(d[55]), "+f"(d[56]), "+f"(d[57]), "+f"(d[58]), "+f"(d[59]), "+f"(d[60]), "+f"(d[61]), "+f"(d[62]), "+f"(d[63])
        : "l"(da), "l"(db), "r"(scale_d));
}
__device__ __forceinline__ void wgmma_ss_n40(float (&d)[20], uint64_t da, uint64_t db, int scale_d) {
    asm volatile(
        "{\n.reg .pred p;\nsetp.ne.b32 p, %22, 0;\n"
        "wgmma.mma_async.sync.aligned.m64n40k16.f32.bf16.bf16 "
        "{%0, %1, %2, %3, %4, %5, %6, %7, %8, %9, %10, %11, %12, %13, %14, %15, %16, %17, %18, %19}, %20, %21, p, 1, 1, 0, 0;\n}\n"
        : "+f"(d[0]), "+f"(d[1]), "+f"(d[2]), "+f"(d[3]), "+f"(d[4]), "+f"(d[5]), "+f"(d[6]), "+f"(d[7]), "+f"(d[8]), "+f"(d[9]), "+f"(d[10]), "+f"(d[11]), "+f"(d[12]), "+f"(d[13]), "+f"(d[14]), "+f"(d[15]), "+f"(d[16]), "+f"(d[17]), "+f"(d[18]), "+f"(d[19])
        : "l"(da), "l"(db), "r"(scale_d));
}
__device__ __forceinline__ void wgmma_ss_n8_ta(float (&d)[4], uint64_t da, uint64_t db, int scale_d) {
    asm volatile(
        "{\n.reg .pred p;\nsetp.ne.b32 p, %6, 0;\n"
        "wgmma.mma_async.sync.aligned.m64n8k16.f32.bf16.bf16 "
        "{%0, %1, %2, %3}, %4, %5, p, 1, 1, 1, 0;\n}\n"
        : "+f"(d[0]), "+f"(d[1]), "+f"(d[2]), "+f"(d[3])
        : "l"(da), "l"(db), "r"(scale_d));
}
__device__ __forceinline__ void wgmma_rs_n32_tb(float (&d)[16], uint32_t a0, uint32_t a1, uint32_t a2, uint32_t a3, uint64_t db, int scale_d) {
    asm volatile(
        "{\n.reg .pred p;\nsetp.ne.b32 p, %21, 0;\n"
        "wgmma.mma_async.sync.aligned.m64n32k16.f32.bf16.bf16 "
        "{%0, %1, %2, %3, %4, %5, %6, %7, %8, %9, %10, %11, %12, %13, %14, %15}, {%16, %17, %18, %19}, %20, p, 1, 1, 1;\n}\n"
        : "+f"(d[0]), "+f"(d[1]), "+f"(d[2]), "+f"(d[3]), "+f"(d[4]), "+f"(d[5]), "+f"(d[6]), "+f"(d[7]), "+f"(d[8]), "+f"(d[9]), "+f"(d[10]), "+f"(d[11]), "+f"(d[12]), "+f"(d[13]), "+f"(d[14]), "+f"(d[15])
        : "r"(a0), "r"(a1), "r"(a2), "r"(a3), "l"(db), "r"(scale_d));
}
__device__ __forceinline__ void wgmma_rs_n40_tb(float (&d)[20], uint32_t a0, uint32_t a1, uint32_t a2, uint32_t a3, uint64_t db, int scale_d) {
    asm volatile(
        "{\n.reg .pred p;\nsetp.ne.b32 p, %25, 0;\n"
        "wgmma.mma_async.sync.aligned.m64n40k16.f32.bf16.bf16 "
        "{%0, %1, %2, %3, %4, %5, %6, %7, %8, %9, %10, %11, %12, %13, %14, %15, %16, %17, %18, %19}, {%20, %21, %22, %23}, %24, p, 1, 1, 1;\n}\n"
        : "+f"(d[0]), "+f"(d[1]), "+f"(d[2]), "+f"(d[3]), "+f"(d[4]), "+f"(d[5]), "+f"(d[6]), "+f"(d[7]), "+f"(d[8]), "+f"(d[9]), "+f"(d[10]), "+f"(d[11]), "+f"(d[12]), "+f"(d[13]), "+f"(d[14]), "+f"(d[15]), "+f"(d[16]), "+f"(d[17]), "+f"(d[18]), "+f"(d[19])
        : "r"(a0), "r"(a1), "r"(a2), "r"(a3), "l"(db), "r"(scale_d));
}

constexpr float LOG2E = 1.4426950408889634f;
constexpr uint32_t DH128 = (1024u >> 4) | (1u << 30);

__device__ __forceinline__ float silu_f(float v) { return v * rcp(1.0f + ex2(-v * LOG2E)); }
__device__ __forceinline__ float silu_t(float v) { const float h = 0.5f * v; float th; asm("tanh.approx.f32 %0, %1;" : "=f"(th) : "f"(h)); return fmaf(h, th, h); }
__device__ __forceinline__ uint32_t ln_pair(uint32_t xv, uint32_t m2, float rs) { const uint32_t a = hsub2(xv, m2); return pack_bf16(bf_lo(a) * rs, bf_hi(a) * rs); }
__device__ __forceinline__ uint32_t silu_pair(uint32_t v) { return pack_bf16(silu_t(bf_lo(v)), silu_t(bf_hi(v))); }
__device__ __forceinline__ uint32_t gate_pair(uint32_t v, float hr, float hm) {
    const float a = fmaf(bf_lo(v), hr, hm), b = fmaf(bf_hi(v), hr, hm);
    float ta, tb;
    asm("tanh.approx.f32 %0, %1;" : "=f"(ta) : "f"(a)); asm("tanh.approx.f32 %0, %1;" : "=f"(tb) : "f"(b));
    return pack_bf16(fmaf(a, ta, a), fmaf(b, tb, b));
}
__device__ __forceinline__ void gate_item(uint4& v, uint32_t sb, int row) {
    const float hr = 0.5f * ldsf(sb + SM_RS + row * 4), hm = -bf_lo(lds32(sb + SM_MD + row * 4)) * hr;
    v.x = gate_pair(v.x, hr, hm); v.y = gate_pair(v.y, hr, hm); v.z = gate_pair(v.z, hr, hm); v.w = gate_pair(v.w, hr, hm);
    asm volatile("" : "+r"(v.x), "+r"(v.y), "+r"(v.z), "+r"(v.w) :: "memory");
}
__device__ __forceinline__ uint32_t hfma2(uint32_t a, uint32_t b, uint32_t c) { uint32_t r; asm("fma.rn.bf16x2 %0, %1, %2, %3;" : "=r"(r) : "r"(a), "r"(b), "r"(c)); return r; }
__device__ __forceinline__ uint32_t dup_lo(uint32_t v) { uint32_t r; asm("{\n.reg .b16 l, h;\nmov.b32 {l, h}, %1;\nmov.b32 %0, {l, l};\n}" : "=r"(r) : "r"(v)); return r; }
__device__ __forceinline__ uint32_t dup_hi(uint32_t v) { uint32_t r; asm("{\n.reg .b16 l, h;\nmov.b32 {l, h}, %1;\nmov.b32 %0, {h, h};\n}" : "=r"(r) : "r"(v)); return r; }
__device__ __forceinline__ uint32_t hmax2(uint32_t a, uint32_t b) { uint32_t r; asm("max.NaN.bf16x2 %0, %1, %2;" : "=r"(r) : "r"(a), "r"(b)); return r; }
template <bool SQ> __device__ __forceinline__ void colsum8(float (&a)[8], float& sq, const uint4 (&v)[8]) {
    uint32_t q = 0;
#pragma unroll
    for (int i = 0; i < 8; i++) {
        a[0] += bf_lo(v[i].x); a[1] += bf_hi(v[i].x); a[2] += bf_lo(v[i].y); a[3] += bf_hi(v[i].y);
        a[4] += bf_lo(v[i].z); a[5] += bf_hi(v[i].z); a[6] += bf_lo(v[i].w); a[7] += bf_hi(v[i].w);
        if (SQ) q = hfma2(v[i].x, v[i].x, hfma2(v[i].y, v[i].y, hfma2(v[i].z, v[i].z, hfma2(v[i].w, v[i].w, q))));
    }
    if (SQ) sq += bf_lo(q) + bf_hi(q);
}
__device__ __forceinline__ void hfma8(uint4& h, uint32_t w, const uint4& v) { h.x = hfma2(v.x, w, h.x); h.y = hfma2(v.y, w, h.y); h.z = hfma2(v.z, w, h.z); h.w = hfma2(v.w, w, h.w); }
template <int ST, class F>
__device__ __forceinline__ void gemv_run(float (&a)[8], int cnt, int b, uint32_t ph, uint32_t lo, uint32_t wa, uint32_t ws, uint32_t bar0, uint32_t pin, F done) {
    uint32_t rdy = 0;
#pragma unroll 1
    for (int m = 0; m < cnt; m++) {
        if (!rdy) mbar_wait(bar0 + b * 8, ph);
        uint4 A[8];
        const uint4 w = lds128(wa);
#pragma unroll
        for (int i = 0; i < 8; i++) A[i] = lds128(lo + b * 4096 + i * ST);
        const int bc = b;
        if (++b == 3) { b = 0; ph ^= 1; }
        asm volatile("{\n.reg .pred p;\nmbarrier.test_wait.parity.shared::cta.b64 p, [%1], %2;\nselp.u32 %0, 1, 0, p;\n}" : "=r"(rdy) : "r"(bar0 + b * 8), "r"(ph) : "memory");
        sts32(pin, 0u);
        wa += ws;
        uint4 h = make_uint4(0, 0, 0, 0);
        hfma8(h, dup_lo(w.x), A[0]); hfma8(h, dup_hi(w.x), A[1]); hfma8(h, dup_lo(w.y), A[2]); hfma8(h, dup_hi(w.y), A[3]);
        hfma8(h, dup_lo(w.z), A[4]); hfma8(h, dup_hi(w.z), A[5]); hfma8(h, dup_lo(w.w), A[6]); hfma8(h, dup_hi(w.w), A[7]);
        a[0] += bf_lo(h.x); a[1] += bf_hi(h.x); a[2] += bf_lo(h.y); a[3] += bf_hi(h.y);
        a[4] += bf_lo(h.z); a[5] += bf_hi(h.z); a[6] += bf_lo(h.w); a[7] += bf_hi(h.w);
        fence_regs(a);
        done(m, bc);
    }
}
template <int OFF> __device__ __forceinline__ void pack_head(const float (&acc)[96], uint32_t (&f)[8]) {
#pragma unroll
    for (int i = 0; i < 8; i++) f[i] = pack_bf16(acc[OFF + 2 * i], acc[OFF + 2 * i + 1]);
}
__device__ __forceinline__ void feat_mma(float (&p)[16], const uint32_t (&f)[8], uint32_t wlo) {
    constexpr uint32_t DH = (512u >> 4) | (2u << 30);
    wgmma_rs_n32_tb(p, f[0], f[1], f[2], f[3], desc_from(wlo, DH), 0);
    wgmma_rs_n32_tb(p, f[4], f[5], f[6], f[7], desc_from(wlo + 64, DH), 1);
}
template <int S> __device__ __forceinline__ void row_ext(const float (&p)[16], float& a, float& b) {
    auto op = [](float x, float y) { return S > 0 ? fmaxf(x, y) : fminf(x, y); };
    a = op(op(op(p[0], p[1]), op(p[4], p[5])), op(op(p[8], p[9]), op(p[12], p[13])));
    b = op(op(op(p[2], p[3]), op(p[6], p[7])), op(op(p[10], p[11]), op(p[14], p[15])));
#pragma unroll
    for (int o = 1; o <= 2; o <<= 1) { a = op(a, __shfl_xor_sync(0xffffffffu, a, o)); b = op(b, __shfl_xor_sync(0xffffffffu, b, o)); }
}
__device__ __forceinline__ void dual_exp(const float (&p)[16], float scA, float scB, uint32_t (&pos)[8], uint32_t (&neg)[8], uint32_t& chk) {
#pragma unroll
    for (int j = 0; j < 8; j += 2) {
        const float a0 = ex2(p[2 * j] * scA), a1 = ex2(p[2 * j + 1] * scA);
        const float b0 = ex2(p[2 * j + 2] * scB), b1 = ex2(p[2 * j + 3] * scB);
        const float pa = a0 * a1, pb = b0 * b1, R = rcp(pa * pb);
        const uint32_t r = pack_bf16(R * pb, R * pa);
        pos[j] = pack_bf16(a0, a1); pos[j + 1] = pack_bf16(b0, b1);
        neg[j] = hmul2(pos[j], dup_lo(r)); neg[j + 1] = hmul2(pos[j + 1], dup_hi(r));
        chk = hadd2(chk, hadd2(hadd2(pos[j], neg[j]), hadd2(pos[j + 1], neg[j + 1])));
    }
}
template <int S> __device__ __forceinline__ void exact_exp(const float (&p)[16], float scA, float scB, uint32_t (&o)[8]) {
    float mA, mB;
    row_ext<S>(p, mA, mB);
#pragma unroll
    for (int j = 0; j < 8; j++) {
        const float sc = S * ((j & 1) ? scB : scA), m = (j & 1) ? mB : mA;
        const float u = ex2((p[2 * j] - m) * sc), v = ex2((p[2 * j + 1] - m) * sc);
        o[j] = S > 0 ? pack_bf16(u, v) : pack_bf16(v, u);
    }
}
__device__ __forceinline__ void features(const float (&p0)[16], const float (&p1)[16], const float (&rs)[4],
                                         uint32_t (&pa)[8], uint32_t (&na)[8], uint32_t (&pb)[8], uint32_t (&nb)[8]) {
    uint32_t chk = 0;
    dual_exp(p0, rs[0] * LOG2E, rs[1] * LOG2E, pa, na, chk);
    dual_exp(p1, rs[2] * LOG2E, rs[3] * LOG2E, pb, nb, chk);
    if (__builtin_expect(!__all_sync(0xffffffffu, bf_lo(chk) + bf_hi(chk) < 1.0e9f), 0)) {
        exact_exp<1>(p0, rs[0] * LOG2E, rs[1] * LOG2E, pa); exact_exp<-1>(p0, rs[0] * LOG2E, rs[1] * LOG2E, na);
        exact_exp<1>(p1, rs[2] * LOG2E, rs[3] * LOG2E, pb); exact_exp<-1>(p1, rs[2] * LOG2E, rs[3] * LOG2E, nb);
    }
}
__device__ __forceinline__ float quad_sum(float v) { v += __shfl_xor_sync(0xffffffffu, v, 1); return v + __shfl_xor_sync(0xffffffffu, v, 2); }
__device__ __forceinline__ float key_block(const float (&p)[16], float rsA, float rsB, uint32_t d0, uint32_t d1, uint32_t off) {
    float r[8], sp[2], sn[2];
    uint32_t pos[8], neg[8];
    const float scA = rsA * LOG2E, scB = rsB * LOG2E;
#pragma unroll
    for (int j = 0; j < 8; j += 2) {
        const float a0 = ex2(p[2 * j] * scA), a1 = ex2(p[2 * j + 1] * scA);
        const float b0 = ex2(p[2 * j + 2] * scB), b1 = ex2(p[2 * j + 3] * scB);
        const float pa = a0 * a1, pb = b0 * b1, R = rcp(pa * pb), ta = a0 + a1, tb = b0 + b1;
        r[j] = R * pb; r[j + 1] = R * pa;
        if (j == 0) { sp[0] = ta; sp[1] = tb; sn[0] = r[0] * ta; sn[1] = r[1] * tb; }
        else { sp[0] += ta; sp[1] += tb; sn[0] = fmaf(r[j], ta, sn[0]); sn[1] = fmaf(r[j + 1], tb, sn[1]); }
        pos[j] = pack_bf16(a0, a1); pos[j + 1] = pack_bf16(b0, b1);
    }
    const float qa = quad_sum(sp[0]), qb = quad_sum(sp[1]), na = quad_sum(sn[0]), nb = quad_sum(sn[1]);
    const float iq = rcp(qa * qb), nA = rsA * rcp(na), nB = rsB * rcp(nb);
    const uint32_t fp = pack_bf16(rsA * qb * iq, rsB * qa * iq);
#pragma unroll
    for (int j = 0; j < 8; j += 2) {
        const uint32_t rn = pack_bf16(r[j] * nA, r[j + 1] * nB);
        neg[j] = hmul2(pos[j], dup_lo(rn)); neg[j + 1] = hmul2(pos[j + 1], dup_hi(rn));
        pos[j] = hmul2(pos[j], dup_lo(fp)); pos[j + 1] = hmul2(pos[j + 1], dup_hi(fp));
    }
    stsm_t(d0 + 4096, neg[0], neg[2], neg[4], neg[6]); stsm_t(d1 + 4096, neg[1], neg[3], neg[5], neg[7]);
    stsm_t(d0 + off, pos[0], pos[2], pos[4], pos[6]); stsm_t(d1 + off, pos[1], pos[3], pos[5], pos[7]);
    return (qa + qb) + (na + nb);
}
__device__ __forceinline__ void shift_max(float (&p)[16]) {
    float mA, mB;
    row_ext<1>(p, mA, mB);
#pragma unroll
    for (int j = 0; j < 16; j++) p[j] -= (j & 2) ? mB : mA;
}
__device__ __forceinline__ void key_head(float (&p0)[16], float (&p1)[16], const float (&rs)[4], uint32_t d0, uint32_t d1) {
    uint32_t st;
    asm volatile("mov.u32 %0, 0;" : "=r"(st));
    bool again;
#pragma unroll 1
    do {
        const uint32_t off = (st & 2u) << 11;
        const float chk = key_block(p0, rs[0], rs[1], d0, d1, off) + key_block(p1, rs[2], rs[3], d0 + 8192, d1 + 8192, off);
        again = st == 1u || (st == 0u && !__all_sync(0xffffffffu, chk < 1.0e9f));
        if (__builtin_expect(again, 0)) {
            if (st) {
#pragma unroll
                for (int j = 0; j < 16; j += 2) {
                    float t = p0[j]; p0[j] = -p0[j + 1]; p0[j + 1] = -t;
                    t = p1[j]; p1[j] = -p1[j + 1]; p1[j + 1] = -t;
                }
            }
            shift_max(p0); shift_max(p1);
            st++;
        }
        asm volatile("" ::: "memory");
    } while (again);
}
__device__ __forceinline__ void o_mma(float (&d)[20], float (&e)[20], const uint32_t (&pos)[8], const uint32_t (&neg)[8], uint32_t klo) {
    wgmma_rs_n40_tb(d, pos[0], pos[1], pos[2], pos[3], desc_from(klo, 1024u >> 4), 0);
    wgmma_rs_n40_tb(e, neg[0], neg[1], neg[2], neg[3], desc_from(klo + 32, 1024u >> 4), 0);
    wgmma_rs_n40_tb(d, pos[4], pos[5], pos[6], pos[7], desc_from(klo + 16, 1024u >> 4), 1);
    wgmma_rs_n40_tb(e, neg[4], neg[5], neg[6], neg[7], desc_from(klo + 48, 1024u >> 4), 1);
}
__device__ __forceinline__ void o_store(const float (&d)[20], const float (&e)[20], __nv_bfloat16* dst) {
    const float iA = rcp(fmaf(d[16], e[17], fmaf(e[16], d[17], 1e-6f * d[17] * e[17])));
    const float iB = rcp(fmaf(d[18], e[19], fmaf(e[18], d[19], 1e-6f * d[19] * e[19])));
    const float pA = e[17] * iA, nA = d[17] * iA, pB = e[19] * iB, nB = d[19] * iB;
    uint32_t oa[4], ob[4];
#pragma unroll
    for (int j = 0; j < 4; j++) {
        oa[j] = pack_bf16(fmaf(d[j * 4], pA, e[j * 4] * nA), fmaf(d[j * 4 + 1], pA, e[j * 4 + 1] * nA));
        ob[j] = pack_bf16(fmaf(d[j * 4 + 2], pB, e[j * 4 + 2] * nB), fmaf(d[j * 4 + 3], pB, e[j * 4 + 3] * nB));
    }
    *reinterpret_cast<uint4*>(dst) = make_uint4(oa[0], oa[1], oa[2], oa[3]);
    *reinterpret_cast<uint4*>(dst + 8 * D_) = make_uint4(ob[0], ob[1], ob[2], ob[3]);
}

template <int N> __device__ __forceinline__ void kv_gather(uint4 (&v)[3 * N], const uint4* src, uint32_t dst, int lane, float us) {
    unsigned it = 0;
#pragma unroll 1
    while (++it < (1u << 20)) {
        bool ok = true;
#pragma unroll
        for (int j = 0; j < 3 * N; j++) ok = ok && (v[j].w >> 16) == 0x4800u;
        if (__all_sync(0xffffffffu, ok)) break;
#pragma unroll
        for (int j = 0; j < 3 * N; j++) v[j] = ld_gpu(src + j * 32);
    }
    dst += (lane >> 2) * 16;
    auto cv = [&](uint32_t w) { const float2 f = unpack_f16(w); return pack_bf16(f.x * us, f.y * us); };
#pragma unroll
    for (int n = 0; n < N; n++) {
        sts128(dst + (lane & 3) * 1024 + n * 256, cv(v[3 * n].x), cv(v[3 * n].y), cv(v[3 * n].z), cv(v[3 * n + 2].x));
        sts128(dst + (lane & 3) * 1024 + n * 256 + 128, cv(v[3 * n + 1].x), cv(v[3 * n + 1].y), cv(v[3 * n + 1].z), cv(v[3 * n + 2].y));
        sts32(dst + 4096 + n * 256 + (lane & 3) * 4, pack_bf16(unpack_f16(v[3 * n].w).x, 1.0f));
        sts32(dst + 4096 + n * 256 + 128 + (lane & 3) * 4, pack_bf16(unpack_f16(v[3 * n + 1].w).x, 1.0f));
    }
    fence_async_smem();
    __syncwarp();
}

__global__ void __launch_bounds__(NTHREADS, 1)
fused_kernel(const __grid_constant__ CUtensorMap tmW0, const __grid_constant__ CUtensorMap tmX2, const __grid_constant__ CUtensorMap tmX, const __grid_constant__ CUtensorMap tmW, const Params P,
             const __grid_constant__ SideMaps tmS, const __grid_constant__ CUtensorMap tmPhi,
             const __grid_constant__ CUtensorMap tmWo, const __grid_constant__ CUtensorMap tmO) {
    extern __shared__ __align__(1024) uint8_t smem_raw[];
    constexpr uint32_t sb = 1024;
    if (smem_u32(smem_raw) != sb) return;
    constexpr uint32_t bars = sb + SM_BARS;
    const int rb = blockIdx.x >> 4, hp = blockIdx.x & 15;
    TLP(threadIdx.x == 32, 0); TLG(threadIdx.x == 32, 48);
    auto load_stage = [&](int s, int ks) {
        mbar_expect_tx(bars + 8 * (B_FULL + s), STAGE);
        tma_2d(sb + s * STAGE, &tmX, bars + 8 * (B_FULL + s), ks * 64, rb * 256);
        tma_3d(sb + s * STAGE + 32768, &tmW, bars + 8 * (B_FULL + s), hp * 64, ks * 64, 0);
    };
    if (threadIdx.x >= 64 && threadIdx.x < 104) {
        const int u = threadIdx.x - 64;
        const __nv_bfloat16* p = u < 16 ? P.x + (size_t)(blockIdx.x * 16 + u) * D_
                                        : P.wqkv + (size_t)(rb * 8 + ((u - 16) & 7)) * 3 * D_ + ((u - 16) >> 3) * D_ + hp * 64;
        asm volatile("prefetch.global.L2 [%0];" :: "l"(p));
    }
    if (threadIdx.x < 32 && elect_one()) {
#pragma unroll
        for (int i = 0; i < 3; i++) { mbar_init(bars + 8 * (B_FULL + i), 1); mbar_init(bars + 8 * (B_EMPTY + i), 8); }
        mbar_init(bars + 8 * B_XR, 1); mbar_init(bars + 8 * B_S0, 1); mbar_init(bars + 8 * B_S0 + 8, 1);
        asm volatile("fence.mbarrier_init.release.cluster;" ::: "memory");
        mbar_expect_tx(bars + 8 * B_S0, 28672);
        tma_3d(sb + 32768, &tmW0, bars + 8 * B_S0, hp * 64, 0, 0);
        tma_2d(sb, &tmX2, bars + 8 * B_S0, 0, rb * 256);
        mbar_expect_tx(bars + 8 * B_S0 + 8, 16384);
        tma_2d(sb + 16384, &tmX2, bars + 8 * B_S0 + 8, 0, rb * 256 + 128);
        mbar_expect_tx(bars + 8 * B_FULL, 12288);
        tma_3d(sb + 45056, &tmW0, bars + 8 * B_FULL, hp * 64, 32, 0);
        load_stage(1, 1); load_stage(2, 2);
        mbar_expect_tx(bars + 8 * B_XR, 32768);
        asm volatile("cp.async.bulk.shared::cluster.global.mbarrier::complete_tx::bytes [%0], [%1], 32768, [%2];"
                     :: "r"(sb + SM_FB + 4096), "l"(P.x + (size_t)blockIdx.x * 16 * D_), "r"(bars + 8 * B_XR) : "memory");
    }
    const int tid = threadIdx.x, warp = __shfl_sync(0xffffffffu, tid >> 5, 0), lane = tid & 31;
    const bool elect = lane == 0;

    if (warp >= 8) {
        const int aw = warp - 9;
        auto load_o = [&](int i, unsigned par) {
            mbar_expect_tx(bars + 8 * (B_OF + i), 16384);
            tma_2d(sb + o_slot(i) * 16384, &tmO, bars + 8 * (B_OF + i), i * 64, par * S_ + rb * 256 + (hp & 1) * 128);
        };
        auto load_wo = [&](int i) {
            mbar_expect_tx(bars + 8 * (B_OF + i), 16384);
            tma_4d(sb + wo_slot(i) * 16384, &tmWo, bars + 8 * (B_OF + i), 0, (i >> 3) * 32, (i & 7) * 2, hp & 14);
        };
        if (warp == 9) {
            if (elect_one()) {
#pragma unroll
                for (int i = B_OF; i < B_COUNT; i++)
                    mbar_init(bars + 8 * i, i < B_SD ? 2 : (i < B_WPHI ? 8 : ((i < B_KV || i >= B_FF || i == B_LN) ? 1 : 4)));
                asm volatile("fence.mbarrier_init.release.cluster;" ::: "memory");
            }
        }
        __syncwarp();
        nb_sync(0, NTHREADS);
        asm volatile("setmaxnreg.dec.sync.aligned.u32 56;");
        unsigned epoch;
        asm volatile("ld.relaxed.gpu.global.u32 %0, [%1];" : "=r"(epoch) : "l"(&P.scr->epoch) : "memory");
        auto get_acc = [&]() { return &P.scr->acc[epoch & 1u]; };
        if (warp == 8) {
            epoch = __shfl_sync(0xffffffffu, epoch, 0);
            int s = 0, ph = 0;
#pragma unroll 1
            for (int j = 0; j < 15; j++) {
                mbar_wait(bars + 8 * (B_EMPTY + s), ph);
                if (elect_one()) {
                    if (j < 13) load_stage(s, j + 3);
                    if (j < 2) {
                        prefetch_l2(P.wqkv + (size_t)(256 + j * 384 + blockIdx.x * 3) * 3 * D_, 18432);
                    } else if (j < 10) {
                        if (j == 2) asm volatile("mbarrier.arrive.shared::cta.b64 _, [%0];" :: "r"(bars + 8 * B_FF) : "memory");
                        const size_t o = (size_t)((j - 2) * 128 + blockIdx.x) * F_;
                        prefetch_l2(P.wg + o, F_ * 2); prefetch_l2(P.wu + o, F_ * 2);
                    }
                    if (j == JWO) prefetch_l2(P.wo + (size_t)blockIdx.x * 8 * D_, 16384);
                    if (j == 12) {
                        asm volatile("prefetch.tensormap [%0];" :: "l"(&tmO) : "memory");
                        asm volatile("prefetch.tensormap [%0];" :: "l"(&tmS.wd8) : "memory");
                        asm volatile("prefetch.tensormap [%0];" :: "l"(&tmWo) : "memory");
                        mbar_expect_tx(bars + 8 * B_WPHI, 4096);
                        tma_2d(sb + SM_WPHI, &tmPhi, bars + 8 * B_WPHI, 0, hp * 64);
                    }
                    if (j >= 13) {
                        if (blockIdx.x >= 112 || j == 13) { load_wo(2 * j - 26); load_wo(2 * j - 25); }
                        else {
                            mbar_expect_tx(bars + 8 * (B_DN + 1), 32768);
                            tma_3d(sb + 6 * 16384, &tmS.wd8, bars + 8 * (B_DN + 1), 0, blockIdx.x * 32, 8);
                        }
                    }
                }
                __syncwarp();
                if (++s == 3) { s = 0; ph ^= 1; }
                if (j == 12 && hp == 0 && lane < 4) P.scr->hint[rb * 32 + lane] = 0u;
                if (j >= 3 && j < 11) {
                    uint4* zp = reinterpret_cast<uint4*>(P.o + (size_t)((~epoch & 1u) * S_ + blockIdx.x * 16 + (j - 3) * 2) * D_) + lane;
#pragma unroll
                    for (int i = 0; i < 2; i++) zp[i * 128] = make_uint4(0, 0, 0, 0);
                    const int i = (j - 3) * 32 + lane;
                    if (i < ACC_VEC_PER_CTA) reinterpret_cast<uint4*>(&P.scr->acc[~epoch & 1u])[blockIdx.x * ACC_VEC_PER_CTA + i] = make_uint4(0, 0, 0, 0);
                }
            }
            TLP(elect, 20);
        } else {
            const bool ffn = blockIdx.x < 112;
            const uint32_t fbuf = sb + SM_FB + 4096 + aw * 12288, fbar = bars + 8 * (B_FF + 1 + aw * 3);
        const int nc = aw == 0 ? NC0 : (aw == 1 ? 12 - NC0 - NC2 : NC2), c0 = aw == 0 ? 0 : (aw == 1 ? NC0 : 12 - NC2);
        const int ng = !ffn ? 0 : (aw == 0 ? NG0 : (aw == 1 ? NG1 : 32 - NG0 - NG1)), g0 = aw == 0 ? 0 : (aw == 1 ? NG0 : NG0 + NG1);
        auto issue = [&](int i, int b) {
            __syncwarp();
            if (i < nc + ng && elect_one()) {
                mbar_expect_tx(fbar + b * 8, 4096);
                if (i < nc) {
                    tma_2d(fbuf + b * 4096, &tmS.wc, fbar + b * 8, ((c0 + i) >> 2) * 1024 + hp * 64, rb * 128 + ((c0 + i) & 3) * 32);
                } else {
                    tma_2d(fbuf + b * 4096, &tmS.wg, fbar + b * 8, blockIdx.x * 32, (g0 + i - nc) * 32);
                    tma_2d(fbuf + b * 4096 + 2048, &tmS.wu, fbar + b * 8, blockIdx.x * 32, (g0 + i - nc) * 32);
                }
            }
            __syncwarp();
        };
            {
                uint4 wv[4];
#pragma unroll
                for (int i = 0; i < 4; i++) wv[i] = __ldg(reinterpret_cast<const uint4*>(P.wr) + i * 32 + lane);
                const uint32_t* ww = reinterpret_cast<const uint32_t*>(wv);
                float sw = 0.f;
#pragma unroll
                for (int i = 0; i < 16; i++) sw += bf_lo(ww[i]) + bf_hi(ww[i]);
#pragma unroll 1
                for (int o = 16; o > 0; o >>= 1) sw += __shfl_xor_sync(0xffffffffu, sw, o);
                sts32(sb + SM_MISC + 20, __float_as_uint(sw));
                if (aw == 2) {
#pragma unroll
                    for (int i = 0; i < 3; i++) P.scr->kv[(hp * 8 + rb) * 96 + i * 32 + lane] = make_uint4(0, 0, 0, 0);
                    asm volatile("fence.acq_rel.gpu;" ::: "memory");
                    __syncwarp();
                }
                mbar_wait(bars + 8 * B_XR, 0);
#pragma unroll 1
                for (int r = aw * 6; r < min(aw * 6 + 6, 16); r++) {
                    const uint32_t buf = sb + SM_FB + 4096 + r * 2048;
                    uint4 xv[4];
                    uint32_t c2 = lds32(buf);
#pragma unroll
                    for (int i = 0; i < 4; i++) xv[i] = lds128(buf + i * 512 + lane * 16);
                    sts32(sb + SM_MISC + 12, 0u);
                    c2 = fabsf(bf_lo(c2) - bf_hi(c2)) < 0.25f * fabsf(bf_lo(c2)) ? dup_lo(c2) : 0u;
                    const uint32_t* xw = reinterpret_cast<const uint32_t*>(xv);
                    uint32_t d2[2] = {0u, 0u};
                    float s0 = 0.f, s1 = 0.f, q0 = 0.f, q1 = 0.f;
#pragma unroll
                    for (int i = 0; i < 16; i++) {
                        const uint32_t a = hsub2(xw[i], c2);
                        s0 += bf_lo(a); s1 += bf_hi(a);
                        d2[i & 1] = hfma2(a, ww[i], d2[i & 1]);
                        q0 = fmaf(bf_lo(a), bf_lo(a), q0); q1 = fmaf(bf_hi(a), bf_hi(a), q1);
                    }
                    sts128(sb + SM_SP + r * 512 + lane * 16, __float_as_uint(s0 + s1), __float_as_uint(q0 + q1),
                           __float_as_uint((bf_lo(d2[0]) + bf_hi(d2[0])) + (bf_lo(d2[1]) + bf_hi(d2[1]))), c2 << 16);
                }
                epoch = __shfl_sync(0xffffffffu, epoch, 0);
                if (aw < 2) nb_arrive(NB_FFN, 96);
                mbar_wait(bars + 8 * B_FF, 0);
#pragma unroll 1
                for (int i = 0; i < 3; i++) issue(i, i);
                const unsigned tag = epoch + 1u;
                if (aw == 2) {
                    nb_sync(NB_FFN, 96);
                    TLP(elect, 23);
                    float s = 0.f, q = 0.f, dt = 0.f, x0;
#pragma unroll 8
                    for (int j = 0; j < 16; j++) {
                        const uint4 e = lds128(sb + SM_SP + lane * 256 + ((j + lane) & 15) * 16);
                        s += __uint_as_float(e.x); q += __uint_as_float(e.y); dt += __uint_as_float(e.z); x0 = __uint_as_float(e.w);
                    }
                    s += __shfl_xor_sync(0xffffffffu, s, 1); q += __shfl_xor_sync(0xffffffffu, q, 1); dt += __shfl_xor_sync(0xffffffffu, dt, 1);
                    const float ms = s * (1.0f / D_);
                    const float vb = round_bf16(fmaxf(q - s * ms, 0.f) * (1.0f / D_));
                    const uint32_t md = pack_bf16(x0 + ms, sqrt_a(round_bf16(vb + 1e-5f)));
                    const uint32_t rbits = pack_bf16((dt - (bf_lo(md) - x0) * ldsf(sb + SM_MISC + 20)) * rcp(bf_hi(md)), 0.f);
                    const int row = blockIdx.x * 16 + (lane >> 1);
                    const uint32_t key = ((((rbits & 0x8000u) ? (~rbits & 0xFFFFu) : (rbits | 0x8000u)) + 1u) << 11) | (uint32_t)(2047 - row);
                    asm volatile("st.relaxed.gpu.global.v2.u32 [%0], {%1, %2};" :: "l"(&P.scr->rows[row]), "r"(md), "r"(tag) : "memory");
                    if (key == __reduce_max_sync(0xffffffffu, key))
                        asm volatile("st.relaxed.gpu.global.v4.u32 [%0], {%1, %2, %3, %3};" :: "l"(&P.scr->best[blockIdx.x]), "r"(key), "r"(md), "r"(tag) : "memory");
                    TLP(elect, 24);
                }
                {
                    float a[8], sq = 0.f, wt = 0.f;
#pragma unroll
                    for (int i = 0; i < 8; i++) a[i] = 0.f;
#pragma unroll 1
                    for (int m = 0; m < nc; m++) {
                        const int b = m % 3, c = c0 + m;
                        mbar_wait(fbar + b * 8, (m / 3) & 1);
                        uint4 v[8];
#pragma unroll
                        for (int i = 0; i < 8; i++) v[i] = lds128(fbuf + b * 4096 + i * 512 + lane * 16);
                        sts32(sb + SM_MISC + 12, 0u);
                        colsum8<true>(a, sq, v);
                        fence_regs(a);
                        wt += 1.0f;
                        issue(m + 3, b);
                        if ((c & 3) == 3 || m == nc - 1) {
#pragma unroll 1
                            for (int o = 8; o <= 16; o <<= 1) {
#pragma unroll
                                for (int i = 0; i < 8; i++) a[i] += __shfl_xor_sync(0xffffffffu, a[i], o);
                                sq += __shfl_xor_sync(0xffffffffu, sq, o);
                            }
                            float4* dst = &get_acc()->cs[((c >> 2) * 16 + hp) * 24 + lane];
                            if (lane < 8) { red_v4(dst, a[0], a[1], a[2], wt); red_v4(dst + 8, a[3], a[4], a[5], wt); red_v4(dst + 16, a[6], a[7], sq, wt); }
#pragma unroll
                            for (int i = 0; i < 8; i++) a[i] = 0.f;
                            wt = 0.f;
                        }
                    }
                    TLP(tid == 288, 26); TLP(tid == 320, 15); TLP(tid == 352, 22);
                }
                if (aw == 0) {
                    uint4 v[4];
                    unsigned it = 0;
                    bool ok = true;
#pragma unroll 1
                    do {
                        if (!ok) __nanosleep(200);
#pragma unroll
                        for (int i = 0; i < 4; i++) v[i] = ld_gpu(&P.scr->best[i * 32 + lane]);
                        ok = v[0].z == tag && v[1].z == tag && v[2].z == tag && v[3].z == tag;
                    } while (!__all_sync(0xffffffffu, ok) && ++it < (1u << 20));
#pragma unroll
                    for (int i = 1; i < 4; i++) if (v[i].x > v[0].x) v[0] = v[i];
                    const uint32_t key = __reduce_max_sync(0xffffffffu, v[0].x);
                    const uint32_t md = __reduce_or_sync(0xffffffffu, v[0].x == key ? v[0].y : 0u);
                    const int sel = 2047 - (int)(key & 2047u);
                    const uint4* xp = reinterpret_cast<const uint4*>(P.x + (size_t)sel * D_) + lane;
#pragma unroll
                    for (int i = 0; i < 4; i++) v[i] = __ldg(xp + i * 32);
                    const uint32_t m2 = __byte_perm(md, 0, 0x1010);
                    const float rs = rcp(bf_hi(md));
                    const uint32_t ord = (key >> 11) - 1u;
                    const float r = __uint_as_float(((ord & 0x8000u) ? (ord & 0x7FFFu) : (~ord & 0xFFFFu)) << 16);
                    sts128(sb + SM_MISC, (uint32_t)sel, __float_as_uint(round_bf16(rcp(1.0f + ex2(-r * LOG2E)))), epoch, 0u);
#pragma unroll
                    for (int i = 0; i < 4; i++) {
                        const uint32_t e0 = ln_pair(v[i].x, m2, rs), e1 = ln_pair(v[i].y, m2, rs), e2 = ln_pair(v[i].z, m2, rs), e3 = ln_pair(v[i].w, m2, rs);
                        const uint32_t xa = sb + SM_XS + i * 512 + (lane >> 2) * 64 + (lane & 3) * 4;
                        sts32(xa, __byte_perm(e0, e2, 0x5410)); sts32(xa + 16, __byte_perm(e0, e2, 0x7632));
                        sts32(xa + 32, __byte_perm(e1, e3, 0x5410)); sts32(xa + 48, __byte_perm(e1, e3, 0x7632));
                    }
                    TLP(elect, 25);
                    __syncwarp();
                    mbar_arrive_if(elect, bars + 8 * B_XS);
                }
            }
            if (aw == 2) {
                    const int l = lane < 24 ? lane : 0;
                    const float4* src = &get_acc()->cs[((l >> 3) * 16 + hp) * 24 + (l & 7)];
                    float4 v0, v1, v2;
                    uint4 v[4];
                    unsigned it = 0;
                    bool ok;
#pragma unroll 1
                    do {
                        v0 = ld_gpu(src); v1 = ld_gpu(src + 8); v2 = ld_gpu(src + 16);
                        ok = v0.w == 32.0f && v1.w == 32.0f && v2.w == 32.0f;
#pragma unroll
                        for (int i = 0; i < 4; i++) v[i] = ld_gpu(reinterpret_cast<const uint4*>(&P.scr->rows[rb * 256]) + i * 32 + lane);
#pragma unroll
                        for (int i = 0; i < 4; i++) ok = ok && v[i].y == epoch + 1u && v[i].w == epoch + 1u;
                    } while (!__all_sync(0xffffffffu, ok) && ++it < (1u << 20));
#pragma unroll
                    for (int i = 0; i < 4; i++) {
                        const uint32_t o = i * 256 + lane * 8;
                        sts64(sb + SM_MD + o, v[i].x, v[i].z);
                        sts64(sb + SM_RS + o, __float_as_uint(rcp(bf_hi(v[i].x))), __float_as_uint(rcp(bf_hi(v[i].z))));
                        const uint32_t h0 = hmul2(dup_lo(v[i].x), 0xBF00BF00u), h1 = hmul2(dup_lo(v[i].z), 0xBF00BF00u);
                        sts128(sb + SM_AX + o * 4, h0, h0 & 0xFFFFu, 0u, 0u);
                        sts128(sb + SM_AX + o * 4 + 16, h1, h1 & 0xFFFFu, 0u, 0u);
                    }
                    sts128(sb + SM_H + lane * 16, 0u, 0u, 0u, 0u); sts128(sb + SM_H + 512 + lane * 16, 0u, 0u, 0u, 0u);
                    const uint32_t e2 = __reduce_max_sync(0xffffffffu, l >= 16 ? __float_as_uint(v2.z) : 0u) >> 23;
                    sts32(sb + SM_MISC + 16, (uint32_t)min(max(187 - (int)((e2 + 1) >> 1), 1), 180) << 23);
                    float cc[8] = {v0.x, v0.y, v0.z, v1.x, v1.y, v1.z, v2.x, v2.y};
                    const uint32_t bx = sb + SM_BX + (l >> 3) * 1024;
#pragma unroll 1
                    for (int k = 0; k < 8; k++) {
                        uint32_t w[4];
#pragma unroll
                        for (int i = 0; i < 4; i++) {
                            w[i] = pack_bf16(cc[2 * i], cc[2 * i + 1]);
                            cc[2 * i] -= bf_lo(w[i]); cc[2 * i + 1] -= bf_hi(w[i]);
                        }
                        sts128(bx + k * 128 + (((l & 7) ^ k) * 16), w[0], w[1], w[2], w[3]);
                    }
                    fence_async_smem();
                    __syncwarp();
                    mbar_arrive_if(elect, bars + 8 * B_LN);
                    TLP(elect, 28);
                }
            mbar_wait(bars + 8 * B_XS, 0);
            if (ffn) {
                float a[8];
#pragma unroll
                for (int i = 0; i < 8; i++) a[i] = 0.f;
                TLP(elect, 40 + aw);
                gemv_run<256>(a, ng, nc % 3, (nc / 3) & 1, fbuf + (lane >> 4) * 2048 + (lane & 15) * 16, sb + SM_XS + g0 * 64 + (lane & 12) * 4, 64, fbar, sb + SM_MISC + 12,
                              [&](int m, int b) { issue(nc + m + 3, b); });
                TLP(elect, 44 + aw);
#pragma unroll 1
                for (int o = 4; o <= 8; o <<= 1) {
#pragma unroll
                    for (int i = 0; i < 8; i++) a[i] += __shfl_xor_sync(0xffffffffu, a[i], o);
                }
                if ((lane & 12) == 0) {
                    const uint32_t ga = sb + SM_GU + aw * 256 + (lane >> 4) * 128 + (lane & 3) * 32;
                    sts128(ga, __float_as_uint(a[0]), __float_as_uint(a[1]), __float_as_uint(a[2]), __float_as_uint(a[3]));
                    sts128(ga + 16, __float_as_uint(a[4]), __float_as_uint(a[5]), __float_as_uint(a[6]), __float_as_uint(a[7]));
                }
                nb_sync(NB_AUX, 96);
                if (warp == 9) {
                    if (elect_one()) {
                        mbar_expect_tx(bars + 8 * B_DN, 32768);
                        tma_3d(sb + SM_FB + 8192, &tmS.wd8, bars + 8 * B_DN, 0, blockIdx.x * 32, 0);
                    }
                    const uint32_t ga = sb + SM_GU + lane * 4;
                    const float gg = round_bf16((ldsf(ga) + ldsf(ga + 256)) + ldsf(ga + 512));
                    const float uu = round_bf16((ldsf(ga + 128) + ldsf(ga + 384)) + ldsf(ga + 640));
                    asm volatile("st.shared.u16 [%0], %1;" :: "r"(sb + SM_H + (lane >> 3) * 256 + 112 + (lane & 7) * 2), "h"((uint16_t)pack_bf16(round_bf16(silu_f(gg)) * uu, 0.f)) : "memory");
                    fence_async_smem();
                }
                __syncwarp();
                TLP(tid == 288, 27);
            }
        }
        {
            TLP(tid == 288, 38);
            const int w4 = warp & 3;
            const uint32_t sp = sb + SM_FB + w4 * 1536;
            auto send = [&](int h) {
                if (elect_one()) {
                    asm volatile("cp.reduce.async.bulk.global.shared::cta.bulk_group.add.noftz.f16 [%0], [%1], 1536;"
                                 :: "l"(&P.scr->kv[(hp * 8 + h * 4 + w4) * 96]), "r"(sp) : "memory");
                    asm volatile("cp.async.bulk.commit_group;" ::: "memory");
                }
            };
            float ya[4] = {0.f, 0.f, 0.f, 0.f}, yb[4] = {0.f, 0.f, 0.f, 0.f};
            uint4 g0[3];
#pragma unroll 1
            for (int h = 0; h < 2; h++) {
                {
                    float d[20];
                    const uint32_t alo = dlo(sb + SM_PHI + h * 32768, 16), vlo = dlo(sb + SM_V + h * 20480, 16);
                    mbar_wait(bars + 8 * (B_PHI + h), 0);
                    wgmma_fence();
#pragma unroll
                    for (int k = 0; k < 16; k++)
                        wgmma_ss_n40(d, desc_from(alo + (k >> 2) * 512 + (k & 3) * 2, DH128), desc_from(vlo + (k >> 2) * 320 + (k & 3) * 2, DH128), k);
                    wgmma_commit();
#pragma unroll
                    for (int j = 0; j < 3; j++) g0[j] = ld_gpu(&P.scr->kv[(hp * 8 + w4) * 96 + j * 32 + lane]);
                    asm volatile("cp.async.bulk.wait_group.read 0;" ::: "memory");
                    __syncwarp();
                    const float ksc = ldsf(sb + SM_MISC + 16);
                    wgmma_wait<0>();
                    fence_regs(d);
#define U(x) pack_f16(d[x] * ksc, d[x + 1] * ksc)
                    sts128(sp + lane * 16, U(0), U(4), U(8), pack_f16(d[16], 1.0f));
                    sts128(sp + 512 + lane * 16, U(2), U(6), U(10), pack_f16(d[18], 1.0f));
                    sts128(sp + 1024 + lane * 16, U(12), U(14), 0u, 0x3C000000u);
#undef U
                    fence_async_smem();
                    __syncwarp();
                    send(h);
                    TLP(tid == 256, 30 + h);
                    nb_sync(NB_KV, 128);
                    if (h) break;
                    if (warp == 8 && elect_one()) {
                        mbar_expect_tx(bars + 8 * B_X, 32768);
                        tma_2d(sb, &tmX2, bars + 8 * B_X, (hp >> 1) * 128, rb * 256 + (hp & 1) * 128);
                        tma_2d(sb + 16384, &tmX2, bars + 8 * B_X, (hp >> 1) * 128 + 64, rb * 256 + (hp & 1) * 128);
                        load_wo(4);
                    }
                    __syncwarp();
                }
                if (blockIdx.x < 112) {
                    const uint32_t hlo = dlo(sb + SM_H, 256);
                    mbar_wait(bars + 8 * B_DN, 0);
                    mbar_wait(bars + 8 * (B_DN + 1), 0);
                    wgmma_fence();
#pragma unroll 2
                    for (int k = 0; k < 16; k++) {
                        wgmma_ss_n8_ta(yb, desc_from(dlo(sb + 6 * 16384, 16) + k * 128, DH128), desc_from(hlo + (k & 1) * 32 + 7 - (k >> 1), 8), k);
                        wgmma_ss_n8_ta(ya, desc_from(dlo(sb + SM_FB + 8192, 16) + k * 128, DH128), desc_from(hlo + (k & 1) * 32 + 7 - (k >> 1), 8), k);
                    }
                    wgmma_commit();
                    wgmma_wait<0>();
                    fence_regs(ya); fence_regs(yb);
                    if (warp == 8) {
                        nb_sync(NB_KV, 128);
                        if (elect_one()) { load_wo(2); load_wo(3); }
                        __syncwarp();
                    } else {
                        nb_arrive(NB_KV, 128);
                    }
                    TLP(tid == 288, 29);
                }
            }
            const float kus = __uint_as_float((254u << 23) - lds32(sb + SM_MISC + 16));
            kv_gather<1>(g0, &P.scr->kv[(hp * 8 + w4) * 96 + lane], sb + SM_KVOP + w4 * 256, lane, kus);
            mbar_arrive_if(elect, bars + 8 * B_KV);
            asm volatile("cp.async.bulk.wait_group.read 0;" ::: "memory");
            __syncwarp();
            if (blockIdx.x < 112) {
#define U(x) __float_as_uint(x)
                sts128(sp + lane * 16, U(ya[0]), U(ya[1]), U(ya[2]), U(1.0f));
                sts128(sp + 512 + lane * 16, U(ya[3]), U(yb[0]), U(yb[1]), U(1.0f));
                sts128(sp + 1024 + lane * 16, U(yb[2]), U(yb[3]), 0u, U(1.0f));
#undef U
                fence_async_smem();
                __syncwarp();
                if (elect_one()) {
                    asm volatile("cp.reduce.async.bulk.global.shared::cta.bulk_group.add.f32 [%0], [%1], 1536;"
                                 :: "l"(&get_acc()->y[((blockIdx.x & 3) * 4 + w4) * 96]), "r"(sp) : "memory");
                    asm volatile("cp.async.bulk.commit_group;" ::: "memory");
                }
                __syncwarp();
            }
            if (w4 >= 2) {
                uint4 g1[6];
#pragma unroll
                for (int j = 0; j < 6; j++) g1[j] = make_uint4(0, 0, 0, 0);
                kv_gather<2>(g1, &P.scr->kv[(hp * 8 + 2 * w4) * 96 + lane], sb + SM_KVOP - 5120 + (w4 - 2) * 512, lane, kus);
                mbar_arrive_if(lane < 2, bars + 8 * (B_KV + 1));
            }
            asm volatile("cp.async.bulk.wait_group.read 0;" ::: "memory");
            __syncwarp();
            mbar_arrive_if(elect, bars + 8 * B_S1);
        }
        if (warp == 8) {
            if (elect_one()) {
                const unsigned* flag = &get_acc()->cnt_o[rb * 128];
                uint4 hint = make_uint4(0, 0, 0, 0);
                mbar_wait(bars + 8 * B_O, 0);
#pragma unroll
                for (int i = 0; i < 16; i++) {
                    if (i < 4) {
                        unsigned it = 0;
#pragma unroll 1
                        while ((i == 0 ? hint.x : (i == 1 ? hint.y : (i == 2 ? hint.z : hint.w))) < 16u && ++it < (1u << 14)) hint = ld_gpu(reinterpret_cast<const uint4*>(&P.scr->hint[rb * 32]));
                    }
                    if (i == 4) poll_counter(flag + 32, 16);
                    if (i == 8) mbar_wait(bars + 8 * B_C1, 0);
                    if (i == 4 || i == 8) asm volatile("fence.proxy.async.global;" ::: "memory");
                    if ((i & 3) == 0 && i < 12) TL(i == 0 ? 21 : (i == 4 ? 34 : 36));
                    if (i == 4 || i > 5) mbar_wait(bars + 8 * (B_SD + max(i - 5, 0)), 0);
                    load_o(i, epoch & 1u);
                    if (i == 3) { load_wo(5); mbar_wait(bars + 8 * B_S1, 0); load_wo(6); }
                    if (i >= 5 && i < 14) load_wo(i + 2);
                }
            }
        } else if (warp == 9) {
            if (elect_one()) {
                unsigned* flag = &get_acc()->cnt_o[rb * 128];
                mbar_wait(bars + 8 * B_O, 0);
                asm volatile("red.release.gpu.global.add.u32 [%0], 1;" :: "l"(flag + 32) : "memory");
                TL(35);
            }
        } else if (warp == 10) {
            if (elect_one()) {
                unsigned* f = &get_acc()->cnt_o[rb * 128 + 96];
                mbar_wait(bars + 8 * (B_O + 1), 0);
                asm volatile("red.release.gpu.global.add.u32 [%0], 1;" :: "l"(f) : "memory");
                TL(37);
                poll_counter(f, 16);
                asm volatile("mbarrier.arrive.shared::cta.b64 _, [%0];" :: "r"(bars + 8 * B_C1) : "memory");
            }
        } else if (warp == 11) {
            const uint4 misc = lds128(sb + SM_MISC);
            if ((int)(misc.x >> 7) == rb * 2 + (hp & 1)) {
                float y[4] = {0.f, 0.f, 0.f, 0.f};
#pragma unroll 1
                for (int rep = 0; rep < 4; rep++) {
                    const float4* yp = &get_acc()->y[(rep * 4 + (lane >> 3)) * 96 + (hp >> 3) * 32 + (lane & 7) * 4 + ((hp >> 1) & 3)];
                    float4 u, v;
                    unsigned it = 0;
#pragma unroll 1
                    do { u = ld_gpu(yp); v = ld_gpu(yp + 32); } while (!__all_sync(0xffffffffu, u.w == 28.0f && v.w == 28.0f) && ++it < (1u << 20));
                    if (hp & 8) { y[0] += u.y; y[1] += v.x; y[2] += u.z; y[3] += v.y; } else { y[0] += u.x; y[1] += u.z; y[2] += u.y; y[3] += v.x; }
                }
                const uint32_t sg = __byte_perm(misc.y, 0, 0x3232), ya = sb + SM_Y + ((lane >> 3) * 16 + (lane & 7)) * 2;
                const uint32_t w0 = hmul2(pack_bf16(y[0], y[1]), sg), w1 = hmul2(pack_bf16(y[2], y[3]), sg);
                asm volatile("st.shared.u16 [%0], %1;" :: "r"(ya), "h"((uint16_t)w0) : "memory");
                asm volatile("st.shared.u16 [%0], %1;" :: "r"(ya + 16), "h"((uint16_t)(w0 >> 16)) : "memory");
                asm volatile("st.shared.u16 [%0], %1;" :: "r"(ya + 128), "h"((uint16_t)w1) : "memory");
                asm volatile("st.shared.u16 [%0], %1;" :: "r"(ya + 144), "h"((uint16_t)(w1 >> 16)) : "memory");
                __syncwarp();
                if (lane < 16) {
                    const uint4 xc = __ldg(reinterpret_cast<const uint4*>(P.x + (size_t)misc.x * D_ + (hp >> 1) * 128) + lane);
                    const uint32_t m2 = __byte_perm(lds32(sb + SM_MD + (misc.x & 255u) * 4), 0, 0x1010);
                    const float r = ldsf(sb + SM_RS + (misc.x & 255u) * 4);
                    const uint4 yv = lds128(sb + SM_Y + lane * 16);
                    sts128(sb + SM_Y + lane * 16, silu_pair(hadd2(ln_pair(xc.x, m2, r), yv.x)), silu_pair(hadd2(ln_pair(xc.y, m2, r), yv.y)),
                           silu_pair(hadd2(ln_pair(xc.z, m2, r), yv.z)), silu_pair(hadd2(ln_pair(xc.w, m2, r), yv.w)));
                    sts128(sb + SM_Y + 256 + lane * 16, xc.x, xc.y, xc.z, xc.w);
                }
                __syncwarp();
                mbar_arrive_if(elect, bars + 8 * B_Y);
                TLP(elect, 39);
            }
        }
    } else {
        const int wg = warp >> 2, w4 = warp & 3, g = lane >> 2;
        nb_sync(0, NTHREADS);
        asm volatile("setmaxnreg.inc.sync.aligned.u32 224;");
        TLP(tid == 0, 1);
        const int row0 = wg * 128 + w4 * 16 + g;
        float pq0[16], pq1[16];
        float rs[4];
        uint32_t f2[8], f3[8], q0[8], q1[8], q2[8], q3[8];
        const uint32_t wlo = dlo(sb + SM_WPHI, 16);
        const uint32_t sw0 = (uint32_t)(((w4 * 2) ^ (lane & 7)) * 16), sw1 = sw0 ^ 16u;
        {
            float acc0[96], acc1[96];
            {
                const uint32_t alo0 = dlo(sb + wg * 16384, 16), blo0 = dlo(sb + 32768, 8192);
                {
                    const uint32_t b0 = dlo(sb + 32768, 4096);
                    mbar_wait(bars + 8 * B_S0, 0);
                    mbar_wait(bars + 8 * (B_S0 + wg), 0);
                    TLP(tid == 0, 2); TLG(tid == 0, 49);
                    wgmma_fence();
#pragma unroll
                    for (int k = 0; k < 4; k++) {
                        if (k == 2) { wgmma_commit(); mbar_wait(bars + 8 * B_FULL, 0); wgmma_fence(); }
                        wgmma_ss_n192_tb(acc0, desc_from(alo0 + k * 2, DH128), desc_from(b0 + (k >> 1) * 768 + (k & 1) * 128, DH128), k);
                        wgmma_ss_n192_tb(acc1, desc_from(alo0 + 512 + k * 2, DH128), desc_from(b0 + (k >> 1) * 768 + (k & 1) * 128, DH128), k);
                    }
                    wgmma_commit();
                }
                int s = 1, ph = 0, ps = 0;
#pragma unroll 1
                for (int ks = 1; ks < 16; ks++) {
                    const bool hold = wg && ks == 15;
                    if (hold) {
                        wgmma_wait<0>();
                        mbar_arrive_if(elect, bars + 8 * (B_EMPTY + ps));
                        nb_sync(6, 256);
                    }
                    mbar_wait(bars + 8 * (B_FULL + s), ph);
                    const uint32_t alo = alo0 + s * (STAGE >> 4), blo = blo0 + s * (STAGE >> 4);
                    wgmma_fence();
#pragma unroll
                    for (int k = 0; k < 4; k++) {
                        if (k == 3 && !wg && ks == 15) nb_arrive(6, 256);
                        wgmma_ss_n192_tb(acc0, desc_from(alo + k * 2, DH128), desc_from(blo + k * 128, DH128), 1);
                        wgmma_ss_n192_tb(acc1, desc_from(alo + 512 + k * 2, DH128), desc_from(blo + k * 128, DH128), 1);
                        if (k == 0) {
                            wgmma_commit();
                            wgmma_wait<1>();
                            mbar_arrive_if(elect && !hold, bars + 8 * (B_EMPTY + ps));
                        }
                    }
                    wgmma_commit();
                    ps = s;
                    if (++s == 3) { s = 0; ph ^= 1; }
                }
            }
            mbar_wait(bars + 8 * B_LN, 0);
            wgmma_fence();
            wgmma_ss_n192_tb(acc0, desc_from(dlo(sb + SM_AX + wg * 2048, 0), 128u >> 4), desc_from(dlo(sb + SM_BX, 1024), 1u << 30), 1);
            wgmma_ss_n192_tb(acc1, desc_from(dlo(sb + SM_AX + wg * 2048 + 1024, 0), 128u >> 4), desc_from(dlo(sb + SM_BX, 1024), 1u << 30), 1);
            wgmma_commit();
            mbar_wait(bars + 8 * (B_EMPTY + 2), 0);
            mbar_wait(bars + 8 * B_WPHI, 0);
            {
                uint32_t md[4];
#pragma unroll
                for (int i = 0; i < 4; i++) {
                    const int r = row0 + (i >> 1) * 64 + (i & 1) * 8;
                    md[i] = __byte_perm(lds32(sb + SM_MD + r * 4), 0, 0x3232);
                    rs[i] = ldsf(sb + SM_RS + r * 4);
                }
                const uint32_t zb = sb + SM_V + wg * 10240 + (lane >> 4) * 5120 + 4096 + (lane & 7) * 128 + (sw0 ^ ((lane & 8) * 2));
                stsm_t(zb, md[0], md[1], md[2], md[3]);
                stsm_t(zb + 20480, md[0], md[1], md[2], md[3]);
            }
            wgmma_wait<0>();
            fence_regs(acc0); fence_regs(acc1);
            TLP(tid == 0, 3); TLG(tid == 0, 50);
            const uint32_t vb = sb + SM_V + wg * 10240 + lane * 128;
            uint32_t f0[8], f1[8], v[8];
            pack_head<64>(acc0, v); stsm_t(vb + sw0, v[0], v[2], v[4], v[6]); stsm_t(vb + sw1, v[1], v[3], v[5], v[7]);
            pack_head<64>(acc1, v); stsm_t(vb + 5120 + sw0, v[0], v[2], v[4], v[6]); stsm_t(vb + 5120 + sw1, v[1], v[3], v[5], v[7]);
#pragma unroll
            for (int i = 32; i < 48; i++) { asm volatile("" : "+f"(acc0[i]) :: "memory"); asm volatile("" : "+f"(acc1[i]) :: "memory"); }
            pack_head<32>(acc0, f0); pack_head<32>(acc1, f1);
            wgmma_fence();
            feat_mma(pq0, f0, wlo); feat_mma(pq1, f1, wlo);
            wgmma_commit();
            pack_head<80>(acc0, v); stsm_t(vb + 20480 + sw0, v[0], v[2], v[4], v[6]); stsm_t(vb + 20480 + sw1, v[1], v[3], v[5], v[7]);
            pack_head<80>(acc1, v); stsm_t(vb + 25600 + sw0, v[0], v[2], v[4], v[6]); stsm_t(vb + 25600 + sw1, v[1], v[3], v[5], v[7]);
            pack_head<48>(acc0, f2); pack_head<48>(acc1, f3);
            pack_head<0>(acc0, q0); pack_head<0>(acc1, q1); pack_head<16>(acc0, q2); pack_head<16>(acc1, q3);
            fence_regs(f2); fence_regs(f3); fence_regs(q0); fence_regs(q1); fence_regs(q2); fence_regs(q3);
            wgmma_wait<0>();
            fence_regs(pq0); fence_regs(pq1); fence_regs(f0); fence_regs(f1);
            mbar_arrive_if(elect, bars + 8 * B_T);
            TLP(tid == 0, 4);
        }
#pragma unroll 1
        for (int h = 0; h < 2; h++) {
            const uint32_t pb = sb + SM_PHI + wg * 16384 + lane * 128 + h * 32768;
            key_head(pq0, pq1, rs, pb + sw0, pb + sw1);
            wgmma_fence();
            feat_mma(pq0, f2, wlo + 128 - h * 128); feat_mma(pq1, f3, wlo + 128 - h * 128);
            wgmma_commit();
            fence_async_smem();
            __syncwarp();
            mbar_arrive_if(elect, bars + 8 * (B_PHI + h));
            TLP(tid == 0, 6 + 2 * h);
            mbar_wait(bars + 8 * B_T, 0);
            wgmma_wait<0>();
            fence_regs(pq0); fence_regs(pq1); fence_regs(f2); fence_regs(f3);
#pragma unroll
            for (int j = 0; j < 8; j++) { f2[j] = q0[j]; f3[j] = q1[j]; }
            fence_regs(f2); fence_regs(f3);
        }
        const uint32_t par = lds32(sb + SM_MISC + 8) & 1u;
        unsigned* flag = &P.scr->acc[par].cnt_o[rb * 128];
        const int orow = (hp & 1) * 128 + wg * 64 + w4 * 16 + (lane >> 4);
        const size_t goff = (size_t)(rb * 256 + orow) * D_ + (hp >> 1) * 128 + (lane & 15) * 8;
        uint4 gv[8], xv[8];
#pragma unroll
        for (int i = 0; i < 8; i++) xv[i] = make_uint4(0, 0, 0, 0);
#pragma unroll
        for (int i = 0; i < GSPLIT2; i++) gv[i] = make_uint4(0, 0, 0, 0);
        const uint32_t rowc = sb + ((lane >> 3) & 1) * 16384 + (wg * 64 + w4 * 16 + (lane >> 4)) * 128;
        {
            uint32_t hbump;
            asm volatile("mov.u32 %0, %1;" : "=r"(hbump) : "r"((uint32_t)(hp < 8 && elect)));
            __nv_bfloat16* od = P.o + (size_t)(par * S_ + rb * 256 + row0) * D_ + hp * 32 + (lane & 3) * 8;
#pragma unroll 1
            for (int h = 0; h < 2; h++) {
                uint32_t pa[8], na[8], pb[8], nb[8];
                features(pq0, pq1, rs, pa, na, pb, nb);
                TLP(tid == 0, 16 + h);
                if (h == 0) {
                    wgmma_fence();
                    feat_mma(pq0, q2, wlo + 128); feat_mma(pq1, q3, wlo + 128);
                    wgmma_commit();
                    mbar_wait(bars + 8 * B_X, 0);
#pragma unroll
                    for (int i = 0; i < 8; i++) xv[i] = lds128(rowc + i * 256 + (((lane & 7) ^ ((2 * i + (lane >> 4)) & 7)) * 16));
#pragma unroll
                    for (int i = 0; i < GSPLIT; i++) { gv[i] = xv[i]; gate_item(gv[i], sb, orow + 2 * i); }
                    wgmma_wait<0>();
                    fence_regs(pq0); fence_regs(pq1); fence_regs(q2); fence_regs(q3);
                    TLP(tid == 0, 18);
                } else {
#pragma unroll
                    for (int i = GSPLIT; i < GSPLIT2; i++) { gv[i] = xv[i]; gate_item(gv[i], sb, orow + 2 * i); }
                    TLP(tid == 0, 10);
                }
                {
                    float d0[20], e0[20], d1[20], e1[20];
                    const uint32_t klo = dlo(sb + SM_KVOP - h * 5120, 128);
                    fence_regs(pa); fence_regs(na); fence_regs(pb); fence_regs(nb);
                    mbar_wait(bars + 8 * (B_KV + h), 0);
                    TLP(tid == 0, 32 + h);
                    wgmma_fence();
                    o_mma(d0, e0, pa, na, klo);
                    o_mma(d1, e1, pb, nb, klo);
                    wgmma_commit();
                    wgmma_wait<0>();
                    fence_regs(d0); fence_regs(e0); fence_regs(pa); fence_regs(na);
                    fence_regs(d1); fence_regs(e1); fence_regs(pb); fence_regs(nb);
                    o_store(d0, e0, od + h * 512);
                    o_store(d1, e1, od + h * 512 + 64 * D_);
                    __syncwarp();
                    asm volatile("{\n.reg .pred q;\nsetp.gt.s32 q, %1, %2;\n@q red.relaxed.gpu.global.add.u32 [%0], %1;\n}" :: "l"(&P.scr->hint[rb * 32 + (hp >> 1) + lane]), "r"(hbump), "r"(h) : "memory");
                    mbar_arrive_if(elect, bars + 8 * (B_O + h));
                }
                TLP(tid == 0, 9 + 2 * h);
            }
        }
        float ghr[8], ghm[8];
#pragma unroll
        for (int i = GSPLIT2; i < 8; i++) { ghr[i] = 0.5f * ldsf(sb + SM_RS + (orow + 2 * i) * 4); ghm[i] = -bf_lo(lds32(sb + SM_MD + (orow + 2 * i) * 4)) * ghr[i]; }
        float acc[64];
        {
            const uint32_t alo0 = dlo(sb + wg * 8192, 16), blo0 = dlo(sb, 8192);
            const uint32_t ta0 = sb + (wg * 64 + w4 * 16) * 128 + lane * 16;
            uint4 cv[2][4];
#pragma unroll
            for (int i = 0; i < 1; i++) {
                mbar_wait(bars + 8 * (B_OF + i), 0);
#pragma unroll
                for (int j = 0; j < 4; j++) cv[i][j] = lds128(ta0 + i * 16384 + j * 512);
            }
#pragma unroll
            for (int i = 0; i < 16; i++) {
                const uint32_t alo = alo0 + o_slot(i) * 1024, blo = blo0 + wo_slot(i) * 1024;
                if (i < 4) {
                    bool bad = false;
#pragma unroll
                    for (int j = 0; j < 4; j++) bad |= (cv[i & 1][j].x | cv[i & 1][j].y | cv[i & 1][j].z | cv[i & 1][j].w) == 0u;
                    if (__builtin_expect(__any_sync(0xffffffffu, bad), 0)) {
                        poll_counter(flag + 32, 16);
#pragma unroll 1
                        for (int j = 0; j < 4; j++) {
                            const int r = j * 4 + (lane >> 3);
                            const uint4 v = ld_gpu(reinterpret_cast<const uint4*>(P.o + (size_t)(par * S_ + rb * 256 + (orow & ~1) + r) * D_ + i * 64) + ((lane ^ r) & 7));
                            sts128(ta0 + (i & 3) * 16384 + j * 512, v.x, v.y, v.z, v.w);
                        }
                        fence_async_smem();
                        __syncwarp();
                    }
                } else {
                    mbar_wait(bars + 8 * (B_OF + i), 0);
                }
                if (i == OSTAG && wg == 0) nb_sync(NB_STAG, 256);
                wgmma_fence();
#pragma unroll
                for (int k = 0; k < 4; k++) {
                    if (i == 15 && k == OARR && wg) nb_arrive(NB_STAG, 256);
                    wgmma_ss_n128_tb(acc, desc_from(alo + k * 2, DH128), desc_from(blo + k * 128, DH128), k | i);
                    if (k == OREL) {
                        if (i > 0 && i < 12) {
                            wgmma_commit();
                            wgmma_wait<1>();
                            mbar_arrive_if(elect, bars + 8 * (B_SD + i - 1));
                        }
                    }
                }
                wgmma_commit();
                if (i == 0) { TLP(tid == 0, 12); TLG(tid == 0, 51); }
                if (i < 3) {
                    mbar_wait(bars + 8 * (B_OF + i + 1), 0);
#pragma unroll
                    for (int j = 0; j < 4; j++) cv[~i & 1][j] = lds128(ta0 + (i + 1) * 16384 + j * 512);
                }
                static_assert(2 * (8 - GSPLIT2) <= 16 - GST, "");
                if (i >= GST && GSPLIT2 + (i - GST) / 2 < 8) {
                    const int q = GSPLIT2 + (i - GST) / 2;
                    if ((i - GST) & 1) { gv[q].z = gate_pair(xv[q].z, ghr[q], ghm[q]); gv[q].w = gate_pair(xv[q].w, ghr[q], ghm[q]); asm volatile("" : "+r"(gv[q].z), "+r"(gv[q].w) :: "memory"); }
                    else { gv[q].x = gate_pair(xv[q].x, ghr[q], ghm[q]); gv[q].y = gate_pair(xv[q].y, ghr[q], ghm[q]); asm volatile("" : "+r"(gv[q].x), "+r"(gv[q].y) :: "memory"); }
                }
            }
        }
        wgmma_wait<0>();
        fence_regs(acc);
        TLP(tid == 0, 13); TLG(tid == 0, 52);
        {
            const uint32_t stg = sb + (wg * 64 + w4 * 16) * 128;
            const int rr = lane & 7;
#pragma unroll
            for (int c = 0; c < 4; c++) {
                const uint32_t a0 = stg + (c >> 1) * 16384 + rr * 128 + ((((c & 1) * 4 + (lane >> 3)) ^ rr) * 16);
                stsm(a0, pack_bf16(acc[c * 16 + 0], acc[c * 16 + 1]), pack_bf16(acc[c * 16 + 4], acc[c * 16 + 5]),
                     pack_bf16(acc[c * 16 + 8], acc[c * 16 + 9]), pack_bf16(acc[c * 16 + 12], acc[c * 16 + 13]));
                stsm(a0 + 1024, pack_bf16(acc[c * 16 + 2], acc[c * 16 + 3]), pack_bf16(acc[c * 16 + 6], acc[c * 16 + 7]),
                     pack_bf16(acc[c * 16 + 10], acc[c * 16 + 11]), pack_bf16(acc[c * 16 + 14], acc[c * 16 + 15]));
            }
            __syncwarp();
#pragma unroll
            for (int i = 0; i < 8; i++) {
                const uint4 sv = lds128(rowc + i * 256 + (((lane & 7) ^ ((2 * i + (lane >> 4)) & 7)) * 16));
                uint4 o;
                o.x = hadd2(xv[i].x, hmul2(sv.x, gv[i].x)); o.y = hadd2(xv[i].y, hmul2(sv.y, gv[i].y));
                o.z = hadd2(xv[i].z, hmul2(sv.z, gv[i].z)); o.w = hadd2(xv[i].w, hmul2(sv.w, gv[i].w));
                *reinterpret_cast<uint4*>(P.out + goff + (size_t)i * 2 * D_) = o;
            }
            const uint32_t sel = lds32(sb + SM_MISC);
            if ((int)(sel >> 4) == rb * 16 + (orow >> 4)) {
                mbar_wait(bars + 8 * B_Y, 0);
                if ((sel & 1u) == (uint32_t)(lane >> 4)) {
                    const int i = (sel & 15u) >> 1;
                    const uint4 sv = lds128(rowc + i * 256 + (((lane & 7) ^ (sel & 7u)) * 16));
                    const uint4 gq = lds128(sb + SM_Y + (lane & 15) * 16), xq = lds128(sb + SM_Y + 256 + (lane & 15) * 16);
                    *reinterpret_cast<uint4*>(P.out + goff + (size_t)i * 2 * D_) = make_uint4(hadd2(xq.x, hmul2(sv.x, gq.x)), hadd2(xq.y, hmul2(sv.y, gq.y)), hadd2(xq.z, hmul2(sv.z, gq.z)), hadd2(xq.w, hmul2(sv.w, gq.w)));
                }
            }
        }
        TLG(tid == 0, 53);
        if (tid == 0) { TL(14); TL_DUMP(); }
        if (blockIdx.x == 0 && tid == 0) asm volatile("st.relaxed.gpu.global.u32 [%0], %1;" :: "l"(&P.scr->epoch), "r"(lds32(sb + SM_MISC + 8) + 1u) : "memory");
    }
}

typedef CUresult (*PFN_encodeTiled)(CUtensorMap*, CUtensorMapDataType, cuuint32_t, void*, const cuuint64_t*, const cuuint64_t*,
                                    const cuuint32_t*, const cuuint32_t*, CUtensorMapInterleave, CUtensorMapSwizzle,
                                    CUtensorMapL2promotion, CUtensorMapFloatOOBfill);

void make_map(PFN_encodeTiled fn, CUtensorMap* m, const void* ptr, int rank, const cuuint64_t* dims, const cuuint64_t* strides, const cuuint32_t* box, CUtensorMapSwizzle sw) {
    const cuuint32_t es[5] = {1, 1, 1, 1, 1};
    fn(m, CU_TENSOR_MAP_DATA_TYPE_BFLOAT16, rank, const_cast<void*>(ptr), dims, strides, box, es, CU_TENSOR_MAP_INTERLEAVE_NONE,
       sw, CU_TENSOR_MAP_L2_PROMOTION_L2_256B, CU_TENSOR_MAP_FLOAT_OOB_FILL_NONE);
}
void make_2d(PFN_encodeTiled fn, CUtensorMap* m, const void* ptr, uint64_t rows, uint64_t cols, uint32_t box_rows, uint32_t box_cols, CUtensorMapSwizzle sw) {
    const cuuint64_t gd[2] = {cols, rows}, gs[1] = {cols * 2};
    const cuuint32_t bd[2] = {box_cols, box_rows};
    make_map(fn, m, ptr, 2, gd, gs, bd, sw);
}

}

extern "C" void kernel_launch(void* const* d_in, const int* in_sizes, int n_in, void* d_out, int out_size) {
    (void)in_sizes; (void)n_in; (void)out_size;
    static PFN_encodeTiled fn = nullptr;
    static void* o_ptr = nullptr;
    static void* scr_ptr = nullptr;
    static void* tl_ptr = nullptr;
    if (!fn) {
        void* p = nullptr;
        cudaDriverEntryPointQueryResult st;
        cudaGetDriverEntryPoint("cuTensorMapEncodeTiled", &p, cudaEnableDefault, &st);
        fn = (PFN_encodeTiled)p;
        cudaGetSymbolAddress(&o_ptr, g_o);
        cudaGetSymbolAddress(&scr_ptr, g_scr);
        cudaFuncSetAttribute(fused_kernel, cudaFuncAttributeMaxDynamicSharedMemorySize, SM_TOTAL);
    }
    CUtensorMap tmX, tmW, tmPhi, tmWo, tmO, tmX2, tmW0;
    SideMaps tmS;
    make_2d(fn, &tmX, d_in[0], S_, D_, 256, 64, CU_TENSOR_MAP_SWIZZLE_128B);
    {
        const cuuint64_t gd[3] = {1024, 1024, 3}, gs[2] = {6144, 2048};
        const cuuint32_t bd[3] = {64, 64, 3};
        make_map(fn, &tmW, d_in[1], 3, gd, gs, bd, CU_TENSOR_MAP_SWIZZLE_128B);
        const cuuint32_t bd0[3] = {64, 32, 3};
        make_map(fn, &tmW0, d_in[1], 3, gd, gs, bd0, CU_TENSOR_MAP_SWIZZLE_128B);
    }
    make_2d(fn, &tmS.wc, d_in[1], D_, 3 * D_, 32, 64, CU_TENSOR_MAP_SWIZZLE_NONE);
    make_2d(fn, &tmPhi, d_in[2], 1024, 32, 64, 32, CU_TENSOR_MAP_SWIZZLE_64B);
    make_2d(fn, &tmS.wg, d_in[6], D_, F_, 32, 32, CU_TENSOR_MAP_SWIZZLE_NONE);
    make_2d(fn, &tmS.wu, d_in[7], D_, F_, 32, 32, CU_TENSOR_MAP_SWIZZLE_NONE);
    {
        const cuuint64_t gd[3] = {64, F_, 16}, gs[2] = {2048, 128};
        const cuuint32_t bd[3] = {64, 32, 8};
        make_map(fn, &tmS.wd8, d_in[8], 3, gd, gs, bd, CU_TENSOR_MAP_SWIZZLE_128B);
    }
    {
        const cuuint64_t gd[4] = {64, 64, 16, 16}, gs[3] = {2048, 64 * 2048, 128};
        const cuuint32_t bd[4] = {64, 32, 2, 2};
        make_map(fn, &tmWo, d_in[3], 4, gd, gs, bd, CU_TENSOR_MAP_SWIZZLE_128B);
    }
    make_2d(fn, &tmO, o_ptr, 2 * S_, D_, 128, 64, CU_TENSOR_MAP_SWIZZLE_128B);
    make_2d(fn, &tmX2, d_in[0], S_, D_, 128, 64, CU_TENSOR_MAP_SWIZZLE_128B);
    Params P;
    P.x = (const __nv_bfloat16*)d_in[0];
    P.wr = (const __nv_bfloat16*)d_in[5];
    P.wqkv = (const __nv_bfloat16*)d_in[1];
    P.wg = (const __nv_bfloat16*)d_in[6];
    P.wu = (const __nv_bfloat16*)d_in[7];
    P.wd = (const __nv_bfloat16*)d_in[8];
    P.wo = (const __nv_bfloat16*)d_in[3];
    P.out = (__nv_bfloat16*)d_out;
    P.o = (__nv_bfloat16*)o_ptr;
    P.scr = (Scratch*)scr_ptr;
    P.tl = (unsigned long long*)tl_ptr;
    cudaLaunchConfig_t cfg = {};
    cfg.gridDim = dim3(NCTA); cfg.blockDim = dim3(NTHREADS); cfg.dynamicSmemBytes = SM_TOTAL; cfg.stream = cudaStreamPerThread;
    cudaLaunchAttribute at[1];
    at[0].id = cudaLaunchAttributeCooperative; at[0].val.cooperative = 1;
    cfg.attrs = at; cfg.numAttrs = 1;
    cudaLaunchKernelEx(&cfg, fused_kernel, tmW0, tmX2, tmX, tmW, P, tmS, tmPhi, tmWo, tmO);
}
```

```cpp
#include <cuda_runtime.h>
#include <cuda_bf16.h>
#include <cuda.h>
#include <stdint.h>

namespace {

constexpr int S_ = 2048, D_ = 1024, F_ = 3584;
constexpr int NCTA = 128, NTHREADS = 384;
#define POLL_NS 100
#define OREL 1
#define OSTAG 12
#define OARR 2
#define NC0 3
#define NC2 4
#define NG0 12
#define NG1 12
#define GSPLIT 1
#define GSPLIT2 2
#define GST 3
#define JWO 12

constexpr int STAGE = 57344;
constexpr int SM_PHI = 0;
constexpr int SM_V = 131072;
constexpr int SM_AX = 172032;
constexpr int SM_BX = 176128;
constexpr int SM_SP = 172032;
constexpr int SM_FB = 180224;
constexpr int SM_XS = 221184;
constexpr int SM_KVOP = 172032;
constexpr int SM_MD = 223232;
constexpr int SM_RS = 224256;
constexpr int SM_Y = 225280;
constexpr int SM_GU = 225536;
constexpr int SM_MISC = 226688;
constexpr int SM_H = 179200;
constexpr int SM_BARS = 226816;
constexpr int SM_WPHI = 227840;
constexpr int SM_TOTAL = 232448;

constexpr int B_FULL = 0, B_EMPTY = 3, B_OF = 6, B_SD = 22, B_O = 33, B_PHI = 35, B_T = 37, B_WPHI = 38, B_Y = 39, B_KV = 40, B_LN = 42, B_S1 = 43, B_FF = 44, B_X = 54, B_C1 = 55, B_DN = 56, B_XS = 58, B_COUNT = 59, B_XR = 59;
constexpr int NB_KV = 1, NB_FFN = 2, NB_AUX = 3, NB_DN = 4, NB_STAG = 5;
__device__ __forceinline__ int o_slot(int i) { const int r = i % 5; return r == 4 ? 10 : r; }
__device__ __forceinline__ int wo_slot(int i) { const int r = i % 7; return r == 6 ? 11 : 4 + r; }

struct __align__(128) Acc {
    float4 cs[48 * 8 * 3];
    float4 y[4 * 4 * 3 * 32];
    unsigned cnt_o[16 * 64];
};
constexpr int ACC_VEC_PER_CTA = (int)(sizeof(Acc) / 16 / NCTA);
static_assert(sizeof(Acc) == ACC_VEC_PER_CTA * 16 * NCTA && ACC_VEC_PER_CTA <= 256, "");
struct __align__(128) Scratch {
    Acc acc[2];
    uint4 kv[32 * 4 * 3 * 32];
    unsigned hint[8 * 32];
    uint2 rows[S_];
    uint4 best[NCTA];
    unsigned epoch;
};
__device__ Scratch g_scr;
__device__ __align__(1024) __nv_bfloat16 g_o[2 * S_ * D_];

#define TL(e) do {} while (0)
#define TLP(c, e) do {} while (0)
#define TLG(c, e) do {} while (0)
#define TL_DUMP() do {} while (0)

struct SideMaps { CUtensorMap wc, wg, wu, wd8; };
struct Params {
    const __nv_bfloat16* x;
    const __nv_bfloat16* wr;
    const __nv_bfloat16* wqkv;
    const __nv_bfloat16* wg;
    const __nv_bfloat16* wu;
    const __nv_bfloat16* wd;
    const __nv_bfloat16* wo;
    __nv_bfloat16* out;
    __nv_bfloat16* o;
    Scratch* scr;
    unsigned long long* tl;
};

__device__ __forceinline__ bool elect_one() {
    uint32_t p; asm volatile("{\n.reg .pred q;\nelect.sync _|q, 0xffffffff;\nselp.u32 %0, 1, 0, q;\n}" : "=r"(p)); return p;
}
__device__ __forceinline__ uint32_t smem_u32(const void* p) { return (uint32_t)__cvta_generic_to_shared(p); }
__device__ __forceinline__ void mbar_init(uint32_t bar, uint32_t cnt) { asm volatile("mbarrier.init.shared::cta.b64 [%0], %1;" :: "r"(bar), "r"(cnt) : "memory"); }
__device__ __forceinline__ void mbar_expect_tx(uint32_t bar, uint32_t bytes) { asm volatile("mbarrier.arrive.expect_tx.shared::cta.b64 _, [%0], %1;" :: "r"(bar), "r"(bytes) : "memory"); }
__device__ __forceinline__ void mbar_arrive_if(bool p, uint32_t bar) {
    asm volatile("{\n.reg .pred q;\nsetp.ne.b32 q, %1, 0;\n@q mbarrier.arrive.shared::cta.b64 _, [%0];\n}" :: "r"(bar), "r"((int)p) : "memory");
}
__device__ __forceinline__ void mbar_wait(uint32_t bar, uint32_t parity) {
    asm volatile("{\n.reg .pred p;\n.reg .u32 n;\nmov.u32 n, 0;\n"
                 "WAIT_LOOP:\nmbarrier.try_wait.parity.shared::cta.b64 p, [%0], %1;\n@p bra WAIT_DONE;\n"
                 "add.u32 n, n, 1;\nsetp.lt.u32 p, n, 0x40000;\n@p bra WAIT_LOOP;\nWAIT_DONE:\n}" :: "r"(bar), "r"(parity) : "memory");
}
__device__ __forceinline__ bool mbar_test(uint32_t bar, uint32_t parity) {
    uint32_t ok;
    asm volatile("{\n.reg .pred p;\nmbarrier.test_wait.parity.shared::cta.b64 p, [%1], %2;\nselp.u32 %0, 1, 0, p;\n}" : "=r"(ok) : "r"(bar), "r"(parity) : "memory");
    return __all_sync(0xffffffffu, ok);
}
__device__ __forceinline__ void tma_2d(uint32_t dst, const CUtensorMap* tm, uint32_t bar, int c0, int c1) {
    asm volatile("cp.async.bulk.tensor.2d.shared::cluster.global.mbarrier::complete_tx::bytes [%0], [%1, {%3, %4}], [%2];"
        :: "r"(dst), "l"(tm), "r"(bar), "r"(c0), "r"(c1) : "memory");
}
__device__ __forceinline__ void tma_3d(uint32_t dst, const CUtensorMap* tm, uint32_t bar, int c0, int c1, int c2) {
    asm volatile("cp.async.bulk.tensor.3d.shared::cluster.global.mbarrier::complete_tx::bytes [%0], [%1, {%3, %4, %5}], [%2];"
        :: "r"(dst), "l"(tm), "r"(bar), "r"(c0), "r"(c1), "r"(c2) : "memory");
}
__device__ __forceinline__ void tma_4d(uint32_t dst, const CUtensorMap* tm, uint32_t bar, int c0, int c1, int c2, int c3) {
    asm volatile("cp.async.bulk.tensor.4d.shared::cluster.global.mbarrier::complete_tx::bytes [%0], [%1, {%3, %4, %5, %6}], [%2];"
        :: "r"(dst), "l"(tm), "r"(bar), "r"(c0), "r"(c1), "r"(c2), "r"(c3) : "memory");
}
__device__ __forceinline__ void prefetch_l2(const void* p, uint32_t bytes) { asm volatile("cp.async.bulk.prefetch.L2.global [%0], %1;" :: "l"(p), "r"(bytes) : "memory"); }
__device__ __forceinline__ void wgmma_fence() { asm volatile("wgmma.fence.sync.aligned;" ::: "memory"); }
__device__ __forceinline__ void wgmma_commit() { asm volatile("wgmma.commit_group.sync.aligned;" ::: "memory"); }
template <int N> __device__ __forceinline__ void wgmma_wait() { asm volatile("wgmma.wait_group.sync.aligned %0;" :: "n"(N) : "memory"); }
template <int N> __device__ __forceinline__ void fence_regs(float (&a)[N]) {
#pragma unroll
    for (int i = 0; i < N; i++) asm volatile("" : "+f"(a[i]) :: "memory");
}
template <int N> __device__ __forceinline__ void fence_regs(uint32_t (&a)[N]) {
#pragma unroll
    for (int i = 0; i < N; i++) asm volatile("" : "+r"(a[i]) :: "memory");
}
__device__ __forceinline__ uint64_t desc_from(uint32_t lo, uint32_t hi) { uint64_t d; asm("mov.b64 %0, {%1, %2};" : "=l"(d) : "r"(lo), "r"(hi)); return d; }
__device__ __forceinline__ uint32_t dlo(uint32_t addr, uint32_t lbo) { return ((addr & 0x3FFFF) >> 4) | ((lbo >> 4) << 16); }
__device__ __forceinline__ void nb_sync(int id, int cnt) { asm volatile("bar.sync %0, %1;" :: "r"(id), "r"(cnt) : "memory"); }
__device__ __forceinline__ void nb_arrive(int id, int cnt) { asm volatile("bar.arrive %0, %1;" :: "r"(id), "r"(cnt) : "memory"); }
__device__ __forceinline__ void fence_async_smem() { asm volatile("fence.proxy.async.shared::cta;" ::: "memory"); }
__device__ __forceinline__ void red_v4(float4* p, float a, float b, float c, float d) {
    asm volatile("red.relaxed.gpu.global.add.v4.f32 [%0], {%1, %2, %3, %4};" :: "l"(p), "f"(a), "f"(b), "f"(c), "f"(d) : "memory");
}
__device__ __forceinline__ void red_h8(uint4* p, uint32_t a, uint32_t b, uint32_t c, uint32_t d) {
    asm volatile("red.relaxed.gpu.global.add.noftz.v4.f16x2 [%0], {%1, %2, %3, %4};" :: "l"(p), "r"(a), "r"(b), "r"(c), "r"(d) : "memory");
}
__device__ __forceinline__ float4 ld_gpu(const float4* p) {
    float4 v; asm volatile("ld.relaxed.gpu.global.v4.f32 {%0, %1, %2, %3}, [%4];" : "=f"(v.x), "=f"(v.y), "=f"(v.z), "=f"(v.w) : "l"(p) : "memory"); return v;
}
__device__ __forceinline__ uint4 ld_gpu(const uint4* p) {
    uint4 v; asm volatile("ld.relaxed.gpu.global.v4.u32 {%0, %1, %2, %3}, [%4];" : "=r"(v.x), "=r"(v.y), "=r"(v.z), "=r"(v.w) : "l"(p) : "memory"); return v;
}
__device__ __forceinline__ void poll_counter(const unsigned* p, unsigned target) {
    unsigned it = 0, v;
#pragma unroll 1
    do {
        asm volatile("ld.acquire.gpu.global.u32 %0, [%1];" : "=r"(v) : "l"(p) : "memory");
    } while (v < target && ++it < (1u << 20));
}
__device__ __forceinline__ uint32_t pack_bf16(float lo, float hi) { uint32_t r; asm("cvt.rn.bf16x2.f32 %0, %1, %2;" : "=r"(r) : "f"(hi), "f"(lo)); return r; }
__device__ __forceinline__ uint32_t pack_f16(float lo, float hi) { uint32_t r; asm("cvt.rn.f16x2.f32 %0, %1, %2;" : "=r"(r) : "f"(hi), "f"(lo)); return r; }
__device__ __forceinline__ float2 unpack_f16(uint32_t v) { float2 r; asm("{\n.reg .f16 l, h;\nmov.b32 {l, h}, %2;\ncvt.f32.f16 %0, l;\ncvt.f32.f16 %1, h;\n}" : "=f"(r.x), "=f"(r.y) : "r"(v)); return r; }
__device__ __forceinline__ float bf_lo(uint32_t v) { return __uint_as_float(v << 16); }
__device__ __forceinline__ float bf_hi(uint32_t v) { return __uint_as_float(v & 0xFFFF0000u); }
__device__ __forceinline__ float round_bf16(float v) { return bf_lo(pack_bf16(v, 0.f)); }
__device__ __forceinline__ float ex2(float v) { float r; asm("ex2.approx.ftz.f32 %0, %1;" : "=f"(r) : "f"(v)); return r; }
__device__ __forceinline__ float rcp(float v) { float r; asm("rcp.approx.ftz.f32 %0, %1;" : "=f"(r) : "f"(v)); return r; }
__device__ __forceinline__ float sqrt_a(float v) { float r; asm("sqrt.approx.f32 %0, %1;" : "=f"(r) : "f"(v)); return r; }
__device__ __forceinline__ void stsm(uint32_t addr, uint32_t r0, uint32_t r1, uint32_t r2, uint32_t r3) {
    asm volatile("stmatrix.sync.aligned.m8n8.x4.shared.b16 [%0], {%1, %2, %3, %4};" :: "r"(addr), "r"(r0), "r"(r1), "r"(r2), "r"(r3) : "memory");
}
__device__ __forceinline__ void stsm_t(uint32_t addr, uint32_t r0, uint32_t r1, uint32_t r2, uint32_t r3) {
    asm volatile("stmatrix.sync.aligned.m8n8.x4.trans.shared.b16 [%0], {%1, %2, %3, %4};" :: "r"(addr), "r"(r0), "r"(r1), "r"(r2), "r"(r3) : "memory");
}
__device__ __forceinline__ uint4 lds128(uint32_t addr) {
    uint4 v; asm volatile("ld.shared.v4.u32 {%0, %1, %2, %3}, [%4];" : "=r"(v.x), "=r"(v.y), "=r"(v.z), "=r"(v.w) : "r"(addr) : "memory"); return v;
}
__device__ __forceinline__ void sts128(uint32_t addr, uint32_t a, uint32_t b, uint32_t c, uint32_t d) {
    asm volatile("st.shared.v4.u32 [%0], {%1, %2, %3, %4};" :: "r"(addr), "r"(a), "r"(b), "r"(c), "r"(d) : "memory");
}
__device__ __forceinline__ void sts64(uint32_t addr, uint32_t a, uint32_t b) { asm volatile("st.shared.v2.u32 [%0], {%1, %2};" :: "r"(addr), "r"(a), "r"(b) : "memory"); }
__device__ __forceinline__ uint32_t lds32(uint32_t addr) { uint32_t v; asm volatile("ld.shared.u32 %0, [%1];" : "=r"(v) : "r"(addr) : "memory"); return v; }
__device__ __forceinline__ float ldsf(uint32_t addr) { return __uint_as_float(lds32(addr)); }
__device__ __forceinline__ void sts32(uint32_t addr, uint32_t v) { asm volatile("st.shared.u32 [%0], %1;" :: "r"(addr), "r"(v) : "memory"); }
__device__ __forceinline__ uint32_t hmul2(uint32_t a, uint32_t b) { uint32_t r; asm("mul.rn.bf16x2 %0, %1, %2;" : "=r"(r) : "r"(a), "r"(b)); return r; }
__device__ __forceinline__ uint32_t hadd2(uint32_t a, uint32_t b) { uint32_t r; asm("add.rn.bf16x2 %0, %1, %2;" : "=r"(r) : "r"(a), "r"(b)); return r; }
__device__ __forceinline__ uint32_t hsub2(uint32_t a, uint32_t b) { uint32_t r; asm("sub.rn.bf16x2 %0, %1, %2;" : "=r"(r) : "r"(a), "r"(b)); return r; }

__device__ __forceinline__ void wgmma_ss_n192_tb(float (&d)[96], uint64_t da, uint64_t db, int scale_d) {
    asm volatile(
        "{\n.reg .pred p;\nsetp.ne.b32 p, %98, 0;\n"
        "wgmma.mma_async.sync.aligned.m64n192k16.f32.bf16.bf16 "
        "{%0, %1, %2, %3, %4, %5, %6, %7, %8, %9, %10, %11, %12, %13, %14, %15, %16, %17, %18, %19, %20, %21, %22, %23, %24, %25, %26, %27, %28, %29, %30, %31, %32, %33, %34, %35, %36, %37, %38, %39, %40, %41, %42, %43, %44, %45, %46, %47, %48, %49, %50, %51, %52, %53, %54, %55, %56, %57, %58, %59, %60, %61, %62, %63, %64, %65, %66, %67, %68, %69, %70, %71, %72, %73, %74, %75, %76, %77, %78, %79, %80, %81, %82, %83, %84, %85, %86, %87, %88, %89, %90, %91, %92, %93, %94, %95}, %96, %97, p, 1, 1, 0, 1;\n}\n"
        : "+f"(d[0]), "+f"(d[1]), "+f"(d[2]), "+f"(d[3]), "+f"(d[4]), "+f"(d[5]), "+f"(d[6]), "+f"(d[7]), "+f"(d[8]), "+f"(d[9]), "+f"(d[10]), "+f"(d[11]), "+f"(d[12]), "+f"(d[13]), "+f"(d[14]), "+f"(d[15]), "+f"(d[16]), "+f"(d[17]), "+f"(d[18]), "+f"(d[19]), "+f"(d[20]), "+f"(d[21]), "+f"(d[22]), "+f"(d[23]), "+f"(d[24]), "+f"(d[25]), "+f"(d[26]), "+f"(d[27]), "+f"(d[28]), "+f"(d[29]), "+f"(d[30]), "+f"(d[31]), "+f"(d[32]), "+f"(d[33]), "+f"(d[34]), "+f"(d[35]), "+f"(d[36]), "+f"(d[37]), "+f"(d[38]), "+f"(d[39]), "+f"(d[40]), "+f"(d[41]), "+f"(d[42]), "+f"(d[43]), "+f"(d[44]), "+f"(d[45]), "+f"(d[46]), "+f"(d[47]), "+f"(d[48]), "+f"(d[49]), "+f"(d[50]), "+f"(d[51]), "+f"(d[52]), "+f"(d[53]), "+f"(d[54]), "+f"(d[55]), "+f"(d[56]), "+f"(d[57]), "+f"(d[58]), "+f"(d[59]), "+f"(d[60]), "+f"(d[61]), "+f"(d[62]), "+f"(d[63]), "+f"(d[64]), "+f"(d[65]), "+f"(d[66]), "+f"(d[67]), "+f"(d[68]), "+f"(d[69]), "+f"(d[70]), "+f"(d[71]), "+f"(d[72]), "+f"(d[73]), "+f"(d[74]), "+f"(d[75]), "+f"(d[76]), "+f"(d[77]), "+f"(d[78]), "+f"(d[79]), "+f"(d[80]), "+f"(d[81]), "+f"(d[82]), "+f"(d[83]), "+f"(d[84]), "+f"(d[85]), "+f"(d[86]), "+f"(d[87]), "+f"(d[88]), "+f"(d[89]), "+f"(d[90]), "+f"(d[91]), "+f"(d[92]), "+f"(d[93]), "+f"(d[94]), "+f"(d[95])
        : "l"(da), "l"(db), "r"(scale_d));
}
__device__ __forceinline__ void wgmma_ss_n128_tb(float (&d)[64], uint64_t da, uint64_t db, int scale_d) {
    asm volatile(
        "{\n.reg .pred p;\nsetp.ne.b32 p, %66, 0;\n"
        "wgmma.mma_async.sync.aligned.m64n128k16.f32.bf16.bf16 "
        "{%0, %1, %2, %3, %4, %5, %6, %7, %8, %9, %10, %11, %12, %13, %14, %15, %16, %17, %18, %19, %20, %21, %22, %23, %24, %25, %26, %27, %28, %29, %30, %31, %32, %33, %34, %35, %36, %37, %38, %39, %40, %41, %42, %43, %44, %45, %46, %47, %48, %49, %50, %51, %52, %53, %54, %55, %56, %57, %58, %59, %60, %61, %62, %63}, %64, %65, p, 1, 1, 0, 1;\n}\n"
        : "+f"(d[0]), "+f"(d[1]), "+f"(d[2]), "+f"(d[3]), "+f"(d[4]), "+f"(d[5]), "+f"(d[6]), "+f"(d[7]), "+f"(d[8]), "+f"(d[9]), "+f"(d[10]), "+f"(d[11]), "+f"(d[12]), "+f"(d[13]), "+f"(d[14]), "+f"(d[15]), "+f"(d[16]), "+f"(d[17]), "+f"(d[18]), "+f"(d[19]), "+f"(d[20]), "+f"(d[21]), "+f"(d[22]), "+f"(d[23]), "+f"(d[24]), "+f"(d[25]), "+f"(d[26]), "+f"(d[27]), "+f"(d[28]), "+f"(d[29]), "+f"(d[30]), "+f"(d[31]), "+f"(d[32]), "+f"(d[33]), "+f"(d[34]), "+f"(d[35]), "+f"(d[36]), "+f"(d[37]), "+f"(d[38]), "+f"(d[39]), "+f"(d[40]), "+f"(d[41]), "+f"(d[42]), "+f"(d[43]), "+f"(d[44]), "+f"(d[45]), "+f"(d[46]), "+f"(d[47]), "+f"(d[48]), "+f"(d[49]), "+f"(d[50]), "+f"(d[51]), "+f"(d[52]), "+f"(d[53]), "+f"(d[54]), "+f"(d[55]), "+f"(d[56]), "+f"(d[57]), "+f"(d[58]), "+f"(d[59]), "+f"(d[60]), "+f"(d[61]), "+f"(d[62]), "+f"(d[63])
        : "l"(da), "l"(db), "r"(scale_d));
}
__device__ __forceinline__ void wgmma_ss_n40(float (&d)[20], uint64_t da, uint64_t db, int scale_d) {
    asm volatile(
        "{\n.reg .pred p;\nsetp.ne.b32 p, %22, 0;\n"
        "wgmma.mma_async.sync.aligned.m64n40k16.f32.bf16.bf16 "
        "{%0, %1, %2, %3, %4, %5, %6, %7, %8, %9, %10, %11, %12, %13, %14, %15, %16, %17, %18, %19}, %20, %21, p, 1, 1, 0, 0;\n}\n"
        : "+f"(d[0]), "+f"(d[1]), "+f"(d[2]), "+f"(d[3]), "+f"(d[4]), "+f"(d[5]), "+f"(d[6]), "+f"(d[7]), "+f"(d[8]), "+f"(d[9]), "+f"(d[10]), "+f"(d[11]), "+f"(d[12]), "+f"(d[13]), "+f"(d[14]), "+f"(d[15]), "+f"(d[16]), "+f"(d[17]), "+f"(d[18]), "+f"(d[19])
        : "l"(da), "l"(db), "r"(scale_d));
}
__device__ __forceinline__ void wgmma_ss_n8_ta(float (&d)[4], uint64_t da, uint64_t db, int scale_d) {
    asm volatile(
        "{\n.reg .pred p;\nsetp.ne.b32 p, %6, 0;\n"
        "wgmma.mma_async.sync.aligned.m64n8k16.f32.bf16.bf16 "
        "{%0, %1, %2, %3}, %4, %5, p, 1, 1, 1, 0;\n}\n"
        : "+f"(d[0]), "+f"(d[1]), "+f"(d[2]), "+f"(d[3])
        : "l"(da), "l"(db), "r"(scale_d));
}
__device__ __forceinline__ void wgmma_rs_n32_tb(float (&d)[16], uint32_t a0, uint32_t a1, uint32_t a2, uint32_t a3, uint64_t db, int scale_d) {
    asm volatile(
        "{\n.reg .pred p;\nsetp.ne.b32 p, %21, 0;\n"
        "wgmma.mma_async.sync.aligned.m64n32k16.f32.bf16.bf16 "
        "{%0, %1, %2, %3, %4, %5, %6, %7, %8, %9, %10, %11, %12, %13, %14, %15}, {%16, %17, %18, %19}, %20, p, 1, 1, 1;\n}\n"
        : "+f"(d[0]), "+f"(d[1]), "+f"(d[2]), "+f"(d[3]), "+f"(d[4]), "+f"(d[5]), "+f"(d[6]), "+f"(d[7]), "+f"(d[8]), "+f"(d[9]), "+f"(d[10]), "+f"(d[11]), "+f"(d[12]), "+f"(d[13]), "+f"(d[14]), "+f"(d[15])
        : "r"(a0), "r"(a1), "r"(a2), "r"(a3), "l"(db), "r"(scale_d));
}
__device__ __forceinline__ void wgmma_rs_n40_tb(float (&d)[20], uint32_t a0, uint32_t a1, uint32_t a2, uint32_t a3, uint64_t db, int scale_d) {
    asm volatile(
        "{\n.reg .pred p;\nsetp.ne.b32 p, %25, 0;\n"
        "wgmma.mma_async.sync.aligned.m64n40k16.f32.bf16.bf16 "
        "{%0, %1, %2, %3, %4, %5, %6, %7, %8, %9, %10, %11, %12, %13, %14, %15, %16, %17, %18, %19}, {%20, %21, %22, %23}, %24, p, 1, 1, 1;\n}\n"
        : "+f"(d[0]), "+f"(d[1]), "+f"(d[2]), "+f"(d[3]), "+f"(d[4]), "+f"(d[5]), "+f"(d[6]), "+f"(d[7]), "+f"(d[8]), "+f"(d[9]), "+f"(d[10]), "+f"(d[11]), "+f"(d[12]), "+f"(d[13]), "+f"(d[14]), "+f"(d[15]), "+f"(d[16]), "+f"(d[17]), "+f"(d[18]), "+f"(d[19])
        : "r"(a0), "r"(a1), "r"(a2), "r"(a3), "l"(db), "r"(scale_d));
}

constexpr float LOG2E = 1.4426950408889634f;
constexpr uint32_t DH128 = (1024u >> 4) | (1u << 30);

__device__ __forceinline__ float silu_f(float v) { return v * rcp(1.0f + ex2(-v * LOG2E)); }
__device__ __forceinline__ float silu_t(float v) { const float h = 0.5f * v; float th; asm("tanh.approx.f32 %0, %1;" : "=f"(th) : "f"(h)); return fmaf(h, th, h); }
__device__ __forceinline__ uint32_t ln_pair(uint32_t xv, uint32_t m2, float rs) { const uint32_t a = hsub2(xv, m2); return pack_bf16(bf_lo(a) * rs, bf_hi(a) * rs); }
__device__ __forceinline__ uint32_t silu_pair(uint32_t v) { return pack_bf16(silu_t(bf_lo(v)), silu_t(bf_hi(v))); }
__device__ __forceinline__ uint32_t gate_pair(uint32_t v, float hr, float hm) {
    const float a = fmaf(bf_lo(v), hr, hm), b = fmaf(bf_hi(v), hr, hm);
    float ta, tb;
    asm("tanh.approx.f32 %0, %1;" : "=f"(ta) : "f"(a)); asm("tanh.approx.f32 %0, %1;" : "=f"(tb) : "f"(b));
    return pack_bf16(fmaf(a, ta, a), fmaf(b, tb, b));
}
__device__ __forceinline__ void gate_item(uint4& v, uint32_t sb, int row) {
    const float hr = 0.5f * ldsf(sb + SM_RS + row * 4), hm = -bf_lo(lds32(sb + SM_MD + row * 4)) * hr;
    v.x = gate_pair(v.x, hr, hm); v.y = gate_pair(v.y, hr, hm); v.z = gate_pair(v.z, hr, hm); v.w = gate_pair(v.w, hr, hm);
    asm volatile("" : "+r"(v.x), "+r"(v.y), "+r"(v.z), "+r"(v.w) :: "memory");
}
__device__ __forceinline__ uint32_t hfma2(uint32_t a, uint32_t b, uint32_t c) { uint32_t r; asm("fma.rn.bf16x2 %0, %1, %2, %3;" : "=r"(r) : "r"(a), "r"(b), "r"(c)); return r; }
__device__ __forceinline__ uint32_t dup_lo(uint32_t v) { uint32_t r; asm("{\n.reg .b16 l, h;\nmov.b32 {l, h}, %1;\nmov.b32 %0, {l, l};\n}" : "=r"(r) : "r"(v)); return r; }
__device__ __forceinline__ uint32_t dup_hi(uint32_t v) { uint32_t r; asm("{\n.reg .b16 l, h;\nmov.b32 {l, h}, %1;\nmov.b32 %0, {h, h};\n}" : "=r"(r) : "r"(v)); return r; }
__device__ __forceinline__ uint32_t hmax2(uint32_t a, uint32_t b) { uint32_t r; asm("max.NaN.bf16x2 %0, %1, %2;" : "=r"(r) : "r"(a), "r"(b)); return r; }
template <bool SQ> __device__ __forceinline__ void colsum8(float (&a)[8], float& sq, const uint4 (&v)[8]) {
    uint32_t q = 0;
#pragma unroll
    for (int i = 0; i < 8; i++) {
        a[0] += bf_lo(v[i].x); a[1] += bf_hi(v[i].x); a[2] += bf_lo(v[i].y); a[3] += bf_hi(v[i].y);
        a[4] += bf_lo(v[i].z); a[5] += bf_hi(v[i].z); a[6] += bf_lo(v[i].w); a[7] += bf_hi(v[i].w);
        if (SQ) q = hfma2(v[i].x, v[i].x, hfma2(v[i].y, v[i].y, hfma2(v[i].z, v[i].z, hfma2(v[i].w, v[i].w, q))));
    }
    if (SQ) sq += bf_lo(q) + bf_hi(q);
}
__device__ __forceinline__ void hfma8(uint4& h, uint32_t w, const uint4& v) { h.x = hfma2(v.x, w, h.x); h.y = hfma2(v.y, w, h.y); h.z = hfma2(v.z, w, h.z); h.w = hfma2(v.w, w, h.w); }
template <int ST, class F>
__device__ __forceinline__ void gemv_run(float (&a)[8], int cnt, int b, uint32_t ph, uint32_t lo, uint32_t wa, uint32_t ws, uint32_t bar0, uint32_t pin, F done) {
    uint32_t rdy = 0;
#pragma unroll 1
    for (int m = 0; m < cnt; m++) {
        if (!rdy) mbar_wait(bar0 + b * 8, ph);
        uint4 A[8];
        const uint4 w = lds128(wa);
#pragma unroll
        for (int i = 0; i < 8; i++) A[i] = lds128(lo + b * 4096 + i * ST);
        const int bc = b;
        if (++b == 3) { b = 0; ph ^= 1; }
        asm volatile("{\n.reg .pred p;\nmbarrier.test_wait.parity.shared::cta.b64 p, [%1], %2;\nselp.u32 %0, 1, 0, p;\n}" : "=r"(rdy) : "r"(bar0 + b * 8), "r"(ph) : "memory");
        sts32(pin, 0u);
        wa += ws;
        uint4 h = make_uint4(0, 0, 0, 0);
        hfma8(h, dup_lo(w.x), A[0]); hfma8(h, dup_hi(w.x), A[1]); hfma8(h, dup_lo(w.y), A[2]); hfma8(h, dup_hi(w.y), A[3]);
        hfma8(h, dup_lo(w.z), A[4]); hfma8(h, dup_hi(w.z), A[5]); hfma8(h, dup_lo(w.w), A[6]); hfma8(h, dup_hi(w.w), A[7]);
        a[0] += bf_lo(h.x); a[1] += bf_hi(h.x); a[2] += bf_lo(h.y); a[3] += bf_hi(h.y);
        a[4] += bf_lo(h.z); a[5] += bf_hi(h.z); a[6] += bf_lo(h.w); a[7] += bf_hi(h.w);
        fence_regs(a);
        done(m, bc);
    }
}
template <int OFF> __device__ __forceinline__ void pack_head(const float (&acc)[96], uint32_t (&f)[8]) {
#pragma unroll
    for (int i = 0; i < 8; i++) f[i] = pack_bf16(acc[OFF + 2 * i], acc[OFF + 2 * i + 1]);
}
__device__ __forceinline__ void feat_mma(float (&p)[16], const uint32_t (&f)[8], uint32_t wlo) {
    constexpr uint32_t DH = (512u >> 4) | (2u << 30);
    wgmma_rs_n32_tb(p, f[0], f[1], f[2], f[3], desc_from(wlo, DH), 0);
    wgmma_rs_n32_tb(p, f[4], f[5], f[6], f[7], desc_from(wlo + 64, DH), 1);
}
template <int S> __device__ __forceinline__ void row_ext(const float (&p)[16], float& a, float& b) {
    auto op = [](float x, float y) { return S > 0 ? fmaxf(x, y) : fminf(x, y); };
    a = op(op(op(p[0], p[1]), op(p[4], p[5])), op(op(p[8], p[9]), op(p[12], p[13])));
    b = op(op(op(p[2], p[3]), op(p[6], p[7])), op(op(p[10], p[11]), op(p[14], p[15])));
#pragma unroll
    for (int o = 1; o <= 2; o <<= 1) { a = op(a, __shfl_xor_sync(0xffffffffu, a, o)); b = op(b, __shfl_xor_sync(0xffffffffu, b, o)); }
}
__device__ __forceinline__ void dual_exp(const float (&p)[16], float scA, float scB, uint32_t (&pos)[8], uint32_t (&neg)[8], uint32_t& chk) {
#pragma unroll
    for (int j = 0; j < 8; j += 2) {
        const float a0 = ex2(p[2 * j] * scA), a1 = ex2(p[2 * j + 1] * scA);
        const float b0 = ex2(p[2 * j + 2] * scB), b1 = ex2(p[2 * j + 3] * scB);
        const float pa = a0 * a1, pb = b0 * b1, R = rcp(pa * pb);
        const uint32_t r = pack_bf16(R * pb, R * pa);
        pos[j] = pack_bf16(a0, a1); pos[j + 1] = pack_bf16(b0, b1);
        neg[j] = hmul2(pos[j], dup_lo(r)); neg[j + 1] = hmul2(pos[j + 1], dup_hi(r));
        chk = hadd2(chk, hadd2(hadd2(pos[j], neg[j]), hadd2(pos[j + 1], neg[j + 1])));
    }
}
template <int S> __device__ __forceinline__ void exact_exp(const float (&p)[16], float scA, float scB, uint32_t (&o)[8]) {
    float mA, mB;
    row_ext<S>(p, mA, mB);
#pragma unroll
    for (int j = 0; j < 8; j++) {
        const float sc = S * ((j & 1) ? scB : scA), m = (j & 1) ? mB : mA;
        const float u = ex2((p[2 * j] - m) * sc), v = ex2((p[2 * j + 1] - m) * sc);
        o[j] = S > 0 ? pack_bf16(u, v) : pack_bf16(v, u);
    }
}
__device__ __forceinline__ void features(const float (&p0)[16], const float (&p1)[16], const float (&rs)[4],
                                         uint32_t (&pa)[8], uint32_t (&na)[8], uint32_t (&pb)[8], uint32_t (&nb)[8]) {
    uint32_t chk = 0;
    dual_exp(p0, rs[0] * LOG2E, rs[1] * LOG2E, pa, na, chk);
    dual_exp(p1, rs[2] * LOG2E, rs[3] * LOG2E, pb, nb, chk);
    if (__builtin_expect(!__all_sync(0xffffffffu, bf_lo(chk) + bf_hi(chk) < 1.0e9f), 0)) {
        exact_exp<1>(p0, rs[0] * LOG2E, rs[1] * LOG2E, pa); exact_exp<-1>(p0, rs[0] * LOG2E, rs[1] * LOG2E, na);
        exact_exp<1>(p1, rs[2] * LOG2E, rs[3] * LOG2E, pb); exact_exp<-1>(p1, rs[2] * LOG2E, rs[3] * LOG2E, nb);
    }
}
__device__ __forceinline__ float quad_sum(float v) { v += __shfl_xor_sync(0xffffffffu, v, 1); return v + __shfl_xor_sync(0xffffffffu, v, 2); }
__device__ __forceinline__ float key_block(const float (&p)[16], float rsA, float rsB, uint32_t d0, uint32_t d1, uint32_t off) {
    float r[8], sp[2], sn[2];
    uint32_t pos[8], neg[8];
    const float scA = rsA * LOG2E, scB = rsB * LOG2E;
#pragma unroll
    for (int j = 0; j < 8; j += 2) {
        const float a0 = ex2(p[2 * j] * scA), a1 = ex2(p[2 * j + 1] * scA);
        const float b0 = ex2(p[2 * j + 2] * scB), b1 = ex2(p[2 * j + 3] * scB);
        const float pa = a0 * a1, pb = b0 * b1, R = rcp(pa * pb), ta = a0 + a1, tb = b0 + b1;
        r[j] = R * pb; r[j + 1] = R * pa;
        if (j == 0) { sp[0] = ta; sp[1] = tb; sn[0] = r[0] * ta; sn[1] = r[1] * tb; }
        else { sp[0] += ta; sp[1] += tb; sn[0] = fmaf(r[j], ta, sn[0]); sn[1] = fmaf(r[j + 1], tb, sn[1]); }
        pos[j] = pack_bf16(a0, a1); pos[j + 1] = pack_bf16(b0, b1);
    }
    const float qa = quad_sum(sp[0]), qb = quad_sum(sp[1]), na = quad_sum(sn[0]), nb = quad_sum(sn[1]);
    const float iq = rcp(qa * qb), nA = rsA * rcp(na), nB = rsB * rcp(nb);
    const uint32_t fp = pack_bf16(rsA * qb * iq, rsB * qa * iq);
#pragma unroll
    for (int j = 0; j < 8; j += 2) {
        const uint32_t rn = pack_bf16(r[j] * nA, r[j + 1] * nB);
        neg[j] = hmul2(pos[j], dup_lo(rn)); neg[j + 1] = hmul2(pos[j + 1], dup_hi(rn));
        pos[j] = hmul2(pos[j], dup_lo(fp)); pos[j + 1] = hmul2(pos[j + 1], dup_hi(fp));
    }
    stsm_t(d0 + 4096, neg[0], neg[2], neg[4], neg[6]); stsm_t(d1 + 4096, neg[1], neg[3], neg[5], neg[7]);
    stsm_t(d0 + off, pos[0], pos[2], pos[4], pos[6]); stsm_t(d1 + off, pos[1], pos[3], pos[5], pos[7]);
    return (qa + qb) + (na + nb);
}
__device__ __forceinline__ void shift_max(float (&p)[16]) {
    float mA, mB;
    row_ext<1>(p, mA, mB);
#pragma unroll
    for (int j = 0; j < 16; j++) p[j] -= (j & 2) ? mB : mA;
}
__device__ __forceinline__ void key_head(float (&p0)[16], float (&p1)[16], const float (&rs)[4], uint32_t d0, uint32_t d1) {
    uint32_t st;
    asm volatile("mov.u32 %0, 0;" : "=r"(st));
    bool again;
#pragma unroll 1
    do {
        const uint32_t off = (st & 2u) << 11;
        const float chk = key_block(p0, rs[0], rs[1], d0, d1, off) + key_block(p1, rs[2], rs[3], d0 + 8192, d1 + 8192, off);
        again = st == 1u || (st == 0u && !__all_sync(0xffffffffu, chk < 1.0e9f));
        if (__builtin_expect(again, 0)) {
            if (st) {
#pragma unroll
                for (int j = 0; j < 16; j += 2) {
                    float t = p0[j]; p0[j] = -p0[j + 1]; p0[j + 1] = -t;
                    t = p1[j]; p1[j] = -p1[j + 1]; p1[j + 1] = -t;
                }
            }
            shift_max(p0); shift_max(p1);
            st++;
        }
        asm volatile("" ::: "memory");
    } while (again);
}
__device__ __forceinline__ void o_mma(float (&d)[20], float (&e)[20], const uint32_t (&pos)[8], const uint32_t (&neg)[8], uint32_t klo) {
    wgmma_rs_n40_tb(d, pos[0], pos[1], pos[2], pos[3], desc_from(klo, 1024u >> 4), 0);
    wgmma_rs_n40_tb(e, neg[0], neg[1], neg[2], neg[3], desc_from(klo + 32, 1024u >> 4), 0);
    wgmma_rs_n40_tb(d, pos[4], pos[5], pos[6], pos[7], desc_from(klo + 16, 1024u >> 4), 1);
    wgmma_rs_n40_tb(e, neg[4], neg[5], neg[6], neg[7], desc_from(klo + 48, 1024u >> 4), 1);
}
__device__ __forceinline__ void o_store(const float (&d)[20], const float (&e)[20], __nv_bfloat16* dst) {
    const float iA = rcp(fmaf(d[16], e[17], fmaf(e[16], d[17], 1e-6f * d[17] * e[17])));
    const float iB = rcp(fmaf(d[18], e[19], fmaf(e[18], d[19], 1e-6f * d[19] * e[19])));
    const float pA = e[17] * iA, nA = d[17] * iA, pB = e[19] * iB, nB = d[19] * iB;
    uint32_t oa[4], ob[4];
#pragma unroll
    for (int j = 0; j < 4; j++) {
        oa[j] = pack_bf16(fmaf(d[j * 4], pA, e[j * 4] * nA), fmaf(d[j * 4 + 1], pA, e[j * 4 + 1] * nA));
        ob[j] = pack_bf16(fmaf(d[j * 4 + 2], pB, e[j * 4 + 2] * nB), fmaf(d[j * 4 + 3], pB, e[j * 4 + 3] * nB));
    }
    *reinterpret_cast<uint4*>(dst) = make_uint4(oa[0], oa[1], oa[2], oa[3]);
    *reinterpret_cast<uint4*>(dst + 8 * D_) = make_uint4(ob[0], ob[1], ob[2], ob[3]);
}

template <int N> __device__ __forceinline__ void kv_gather(uint4 (&v)[3 * N], const uint4* src, uint32_t dst, int lane, float us) {
    unsigned it = 0;
#pragma unroll 1
    while (++it < (1u << 20)) {
        bool ok = true;
#pragma unroll
        for (int j = 0; j < 3 * N; j++) ok = ok && (v[j].w >> 16) == 0x4800u;
        if (__all_sync(0xffffffffu, ok)) break;
#pragma unroll
        for (int j = 0; j < 3 * N; j++) v[j] = ld_gpu(src + j * 32);
    }
    dst += (lane >> 2) * 16;
    auto cv = [&](uint32_t w) { const float2 f = unpack_f16(w); return pack_bf16(f.x * us, f.y * us); };
#pragma unroll
    for (int n = 0; n < N; n++) {
        sts128(dst + (lane & 3) * 1024 + n * 256, cv(v[3 * n].x), cv(v[3 * n].y), cv(v[3 * n].z), cv(v[3 * n + 2].x));
        sts128(dst + (lane & 3) * 1024 + n * 256 + 128, cv(v[3 * n + 1].x), cv(v[3 * n + 1].y), cv(v[3 * n + 1].z), cv(v[3 * n + 2].y));
        sts32(dst + 4096 + n * 256 + (lane & 3) * 4, pack_bf16(unpack_f16(v[3 * n].w).x, 1.0f));
        sts32(dst + 4096 + n * 256 + 128 + (lane & 3) * 4, pack_bf16(unpack_f16(v[3 * n + 1].w).x, 1.0f));
    }
    fence_async_smem();
    __syncwarp();
}

__global__ void __launch_bounds__(NTHREADS, 1)
fused_kernel(const Params P, const __grid_constant__ CUtensorMap tmX, const __grid_constant__ CUtensorMap tmW, const __grid_constant__ CUtensorMap tmX2,
             const __grid_constant__ SideMaps tmS, const __grid_constant__ CUtensorMap tmPhi,
             const __grid_constant__ CUtensorMap tmWo, const __grid_constant__ CUtensorMap tmO) {
    extern __shared__ __align__(1024) uint8_t smem_raw[];
    constexpr uint32_t sb = 1024;
    if (smem_u32(smem_raw) != sb) return;
    constexpr uint32_t bars = sb + SM_BARS;
    const int rb = blockIdx.x >> 4, hp = blockIdx.x & 15;
    TLP(threadIdx.x == 32, 0); TLG(threadIdx.x == 32, 48);
    auto load_stage = [&](int s, int ks) {
        mbar_expect_tx(bars + 8 * (B_FULL + s), STAGE);
        tma_2d(sb + s * STAGE, &tmX, bars + 8 * (B_FULL + s), ks * 64, rb * 256);
        tma_3d(sb + s * STAGE + 32768, &tmW, bars + 8 * (B_FULL + s), hp * 64, ks * 64, 0);
    };
    if (threadIdx.x < 256) {
        const uint32_t t = threadIdx.x, r = t >> 3, sw = ((t ^ r) & 7) * 16;
        const __nv_bfloat16* wp = P.wqkv + (size_t)r * 3 * D_ + hp * 64 + (t & 7) * 8;
        const __nv_bfloat16* xp = P.x + (size_t)(rb * 256 + (t >> 7) * 128 + (r & 15)) * D_ + (t & 7) * 8;
#pragma unroll
        for (int i = 0; i < 3; i++) asm volatile("cp.async.cg.shared.global [%0], [%1], 16;" :: "r"(sb + 32768 + i * 8192 + r * 128 + sw), "l"(wp + i * D_) : "memory");
#pragma unroll
        for (int i = 0; i < 8; i++) asm volatile("cp.async.cg.shared.global [%0], [%1], 16;" :: "r"(sb + (t >> 7) * 16384 + ((r & 15) + i * 16) * 128 + sw), "l"(xp + i * 16 * D_) : "memory");
        asm volatile("cp.async.commit_group;" ::: "memory");
#pragma unroll
        for (int i = 0; i < 3; i++) asm volatile("cp.async.cg.shared.global [%0], [%1], 16;" :: "r"(sb + 36864 + i * 8192 + r * 128 + sw), "l"(wp + 96 * D_ + i * D_) : "memory");
        asm volatile("cp.async.commit_group;" ::: "memory");
    }
    const int tid = threadIdx.x, warp = __shfl_sync(0xffffffffu, tid >> 5, 0), lane = tid & 31;
    const bool elect = lane == 0;

    if (warp >= 8) {
        const int aw = warp - 9;
        auto load_o = [&](int i, unsigned par) {
            mbar_expect_tx(bars + 8 * (B_OF + i), 16384);
            tma_2d(sb + o_slot(i) * 16384, &tmO, bars + 8 * (B_OF + i), i * 64, par * S_ + rb * 256 + (hp & 1) * 128);
        };
        auto load_wo = [&](int i) {
            mbar_expect_tx(bars + 8 * (B_OF + i), 16384);
            tma_4d(sb + wo_slot(i) * 16384, &tmWo, bars + 8 * (B_OF + i), 0, (i >> 3) * 32, (i & 7) * 2, hp & 14);
        };
        if (warp == 9) {
            if (elect_one()) {
#pragma unroll
                for (int i = B_OF; i < B_COUNT; i++)
                    mbar_init(bars + 8 * i, i < B_SD ? 2 : (i < B_WPHI ? 8 : ((i < B_KV || i >= B_FF || i == B_LN) ? 1 : 4)));
                asm volatile("fence.mbarrier_init.release.cluster;" ::: "memory");
            }
        }
        if (warp == 8) {
            if (elect_one()) {
#pragma unroll
                for (int i = 0; i < 3; i++) { mbar_init(bars + 8 * (B_FULL + i), 1); mbar_init(bars + 8 * (B_EMPTY + i), 8); }
                mbar_init(bars + 8 * B_XR, 1);
                asm volatile("fence.mbarrier_init.release.cluster;" ::: "memory");
                asm volatile("mbarrier.arrive.shared::cta.b64 _, [%0];" :: "r"(bars + 8 * B_FULL) : "memory");
            }
            __syncwarp();
            nb_arrive(0, NTHREADS);
        } else {
            __syncwarp();
            nb_sync(0, NTHREADS);
        }
        asm volatile("setmaxnreg.dec.sync.aligned.u32 56;");
        if (warp == 8 && elect_one()) {
            load_stage(1, 1); load_stage(2, 2);
            mbar_expect_tx(bars + 8 * B_XR, 32768);
            asm volatile("cp.async.bulk.shared::cluster.global.mbarrier::complete_tx::bytes [%0], [%1], 32768, [%2];"
                         :: "r"(sb + SM_FB + 4096), "l"(P.x + (size_t)blockIdx.x * 16 * D_), "r"(bars + 8 * B_XR) : "memory");
        }
        __syncwarp();
        nb_sync(NB_KV, 128);
        unsigned epoch;
        asm volatile("ld.relaxed.gpu.global.u32 %0, [%1];" : "=r"(epoch) : "l"(&P.scr->epoch) : "memory");
        auto get_acc = [&]() { return &P.scr->acc[epoch & 1u]; };
        if (warp == 8) {
            epoch = __shfl_sync(0xffffffffu, epoch, 0);
            int s = 0, ph = 0;
#pragma unroll 1
            for (int j = 0; j < 15; j++) {
                mbar_wait(bars + 8 * (B_EMPTY + s), ph);
                if (elect_one()) {
                    if (j < 13) load_stage(s, j + 3);
                    if (j < 2) {
                        prefetch_l2(P.wqkv + (size_t)(256 + j * 384 + blockIdx.x * 3) * 3 * D_, 18432);
                    } else if (j < 10) {
                        if (j == 2) asm volatile("mbarrier.arrive.shared::cta.b64 _, [%0];" :: "r"(bars + 8 * B_FF) : "memory");
                        const size_t o = (size_t)((j - 2) * 128 + blockIdx.x) * F_;
                        prefetch_l2(P.wg + o, F_ * 2); prefetch_l2(P.wu + o, F_ * 2);
                    }
                    if (j == JWO) prefetch_l2(P.wo + (size_t)blockIdx.x * 8 * D_, 16384);
                    if (j == 12) {
                        asm volatile("prefetch.tensormap [%0];" :: "l"(&tmO) : "memory");
                        asm volatile("prefetch.tensormap [%0];" :: "l"(&tmS.wd8) : "memory");
                        asm volatile("prefetch.tensormap [%0];" :: "l"(&tmWo) : "memory");
                        mbar_expect_tx(bars + 8 * B_WPHI, 4096);
                        tma_2d(sb + SM_WPHI, &tmPhi, bars + 8 * B_WPHI, 0, hp * 64);
                    }
                    if (j >= 13) {
                        if (blockIdx.x >= 112 || j == 13) { load_wo(2 * j - 26); load_wo(2 * j - 25); }
                        else {
                            mbar_expect_tx(bars + 8 * (B_DN + 1), 32768);
                            tma_3d(sb + 6 * 16384, &tmS.wd8, bars + 8 * (B_DN + 1), 0, blockIdx.x * 32, 8);
                        }
                    }
                }
                __syncwarp();
                if (++s == 3) { s = 0; ph ^= 1; }
                if (j == 12 && hp == 0 && lane < 4) P.scr->hint[rb * 32 + lane] = 0u;
                if (j >= 3 && j < 11) {
                    uint4* zp = reinterpret_cast<uint4*>(P.o + (size_t)((~epoch & 1u) * S_ + blockIdx.x * 16 + (j - 3) * 2) * D_) + lane;
#pragma unroll
                    for (int i = 0; i < 2; i++) zp[i * 128] = make_uint4(0, 0, 0, 0);
                    const int i = (j - 3) * 32 + lane;
                    if (i < ACC_VEC_PER_CTA) reinterpret_cast<uint4*>(&P.scr->acc[~epoch & 1u])[blockIdx.x * ACC_VEC_PER_CTA + i] = make_uint4(0, 0, 0, 0);
                }
            }
            TLP(elect, 20);
        } else {
            const bool ffn = blockIdx.x < 112;
            const uint32_t fbuf = sb + SM_FB + 4096 + aw * 12288, fbar = bars + 8 * (B_FF + 1 + aw * 3);
        const int nc = aw == 0 ? NC0 : (aw == 1 ? 12 - NC0 - NC2 : NC2), c0 = aw == 0 ? 0 : (aw == 1 ? NC0 : 12 - NC2);
        const int ng = !ffn ? 0 : (aw == 0 ? NG0 : (aw == 1 ? NG1 : 32 - NG0 - NG1)), g0 = aw == 0 ? 0 : (aw == 1 ? NG0 : NG0 + NG1);
        auto issue = [&](int i, int b) {
            __syncwarp();
            if (i < nc + ng && elect_one()) {
                mbar_expect_tx(fbar + b * 8, 4096);
                if (i < nc) {
                    tma_2d(fbuf + b * 4096, &tmS.wc, fbar + b * 8, ((c0 + i) >> 2) * 1024 + hp * 64, rb * 128 + ((c0 + i) & 3) * 32);
                } else {
                    tma_2d(fbuf + b * 4096, &tmS.wg, fbar + b * 8, blockIdx.x * 32, (g0 + i - nc) * 32);
                    tma_2d(fbuf + b * 4096 + 2048, &tmS.wu, fbar + b * 8, blockIdx.x * 32, (g0 + i - nc) * 32);
                }
            }
            __syncwarp();
        };
            {
                uint4 wv[4];
#pragma unroll
                for (int i = 0; i < 4; i++) wv[i] = __ldg(reinterpret_cast<const uint4*>(P.wr) + i * 32 + lane);
                const uint32_t* ww = reinterpret_cast<const uint32_t*>(wv);
                float sw = 0.f;
#pragma unroll
                for (int i = 0; i < 16; i++) sw += bf_lo(ww[i]) + bf_hi(ww[i]);
#pragma unroll 1
                for (int o = 16; o > 0; o >>= 1) sw += __shfl_xor_sync(0xffffffffu, sw, o);
                sts32(sb + SM_MISC + 20, __float_as_uint(sw));
                if (aw == 2) {
#pragma unroll
                    for (int i = 0; i < 3; i++) P.scr->kv[(hp * 8 + rb) * 96 + i * 32 + lane] = make_uint4(0, 0, 0, 0);
                    asm volatile("fence.acq_rel.gpu;" ::: "memory");
                    __syncwarp();
                }
                mbar_wait(bars + 8 * B_XR, 0);
#pragma unroll 1
                for (int r = aw * 6; r < min(aw * 6 + 6, 16); r++) {
                    const uint32_t buf = sb + SM_FB + 4096 + r * 2048;
                    uint4 xv[4];
                    uint32_t c2 = lds32(buf);
#pragma unroll
                    for (int i = 0; i < 4; i++) xv[i] = lds128(buf + i * 512 + lane * 16);
                    sts32(sb + SM_MISC + 12, 0u);
                    c2 = fabsf(bf_lo(c2) - bf_hi(c2)) < 0.25f * fabsf(bf_lo(c2)) ? dup_lo(c2) : 0u;
                    const uint32_t* xw = reinterpret_cast<const uint32_t*>(xv);
                    uint32_t d2[2] = {0u, 0u};
                    float s0 = 0.f, s1 = 0.f, q0 = 0.f, q1 = 0.f;
#pragma unroll
                    for (int i = 0; i < 16; i++) {
                        const uint32_t a = hsub2(xw[i], c2);
                        s0 += bf_lo(a); s1 += bf_hi(a);
                        d2[i & 1] = hfma2(a, ww[i], d2[i & 1]);
                        q0 = fmaf(bf_lo(a), bf_lo(a), q0); q1 = fmaf(bf_hi(a), bf_hi(a), q1);
                    }
                    sts128(sb + SM_SP + r * 512 + lane * 16, __float_as_uint(s0 + s1), __float_as_uint(q0 + q1),
                           __float_as_uint((bf_lo(d2[0]) + bf_hi(d2[0])) + (bf_lo(d2[1]) + bf_hi(d2[1]))), c2 << 16);
                }
                epoch = __shfl_sync(0xffffffffu, epoch, 0);
                if (aw < 2) nb_arrive(NB_FFN, 96);
                mbar_wait(bars + 8 * B_FF, 0);
#pragma unroll 1
                for (int i = 0; i < 3; i++) issue(i, i);
                const unsigned tag = epoch + 1u;
                if (aw == 2) {
                    nb_sync(NB_FFN, 96);
                    TLP(elect, 23);
                    float s = 0.f, q = 0.f, dt = 0.f, x0;
#pragma unroll 8
                    for (int j = 0; j < 16; j++) {
                        const uint4 e = lds128(sb + SM_SP + lane * 256 + ((j + lane) & 15) * 16);
                        s += __uint_as_float(e.x); q += __uint_as_float(e.y); dt += __uint_as_float(e.z); x0 = __uint_as_float(e.w);
                    }
                    s += __shfl_xor_sync(0xffffffffu, s, 1); q += __shfl_xor_sync(0xffffffffu, q, 1); dt += __shfl_xor_sync(0xffffffffu, dt, 1);
                    const float ms = s * (1.0f / D_);
                    const float vb = round_bf16(fmaxf(q - s * ms, 0.f) * (1.0f / D_));
                    const uint32_t md = pack_bf16(x0 + ms, sqrt_a(round_bf16(vb + 1e-5f)));
                    const uint32_t rbits = pack_bf16((dt - (bf_lo(md) - x0) * ldsf(sb + SM_MISC + 20)) * rcp(bf_hi(md)), 0.f);
                    const int row = blockIdx.x * 16 + (lane >> 1);
                    const uint32_t key = ((((rbits & 0x8000u) ? (~rbits & 0xFFFFu) : (rbits | 0x8000u)) + 1u) << 11) | (uint32_t)(2047 - row);
                    asm volatile("st.relaxed.gpu.global.v2.u32 [%0], {%1, %2};" :: "l"(&P.scr->rows[row]), "r"(md), "r"(tag) : "memory");
                    if (key == __reduce_max_sync(0xffffffffu, key))
                        asm volatile("st.relaxed.gpu.global.v4.u32 [%0], {%1, %2, %3, %3};" :: "l"(&P.scr->best[blockIdx.x]), "r"(key), "r"(md), "r"(tag) : "memory");
                    TLP(elect, 24);
                }
                {
                    float a[8], sq = 0.f, wt = 0.f;
#pragma unroll
                    for (int i = 0; i < 8; i++) a[i] = 0.f;
#pragma unroll 1
                    for (int m = 0; m < nc; m++) {
                        const int b = m % 3, c = c0 + m;
                        mbar_wait(fbar + b * 8, (m / 3) & 1);
                        uint4 v[8];
#pragma unroll
                        for (int i = 0; i < 8; i++) v[i] = lds128(fbuf + b * 4096 + i * 512 + lane * 16);
                        sts32(sb + SM_MISC + 12, 0u);
                        colsum8<true>(a, sq, v);
                        fence_regs(a);
                        wt += 1.0f;
                        issue(m + 3, b);
                        if ((c & 3) == 3 || m == nc - 1) {
#pragma unroll 1
                            for (int o = 8; o <= 16; o <<= 1) {
#pragma unroll
                                for (int i = 0; i < 8; i++) a[i] += __shfl_xor_sync(0xffffffffu, a[i], o);
                                sq += __shfl_xor_sync(0xffffffffu, sq, o);
                            }
                            float4* dst = &get_acc()->cs[((c >> 2) * 16 + hp) * 24 + lane];
                            if (lane < 8) { red_v4(dst, a[0], a[1], a[2], wt); red_v4(dst + 8, a[3], a[4], a[5], wt); red_v4(dst + 16, a[6], a[7], sq, wt); }
#pragma unroll
                            for (int i = 0; i < 8; i++) a[i] = 0.f;
                            wt = 0.f;
                        }
                    }
                    TLP(tid == 288, 26); TLP(tid == 320, 15); TLP(tid == 352, 22);
                }
                if (aw == 0) {
                    uint4 v[4];
                    unsigned it = 0;
                    bool ok = true;
#pragma unroll 1
                    do {
                        if (!ok) __nanosleep(200);
#pragma unroll
                        for (int i = 0; i < 4; i++) v[i] = ld_gpu(&P.scr->best[i * 32 + lane]);
                        ok = v[0].z == tag && v[1].z == tag && v[2].z == tag && v[3].z == tag;
                    } while (!__all_sync(0xffffffffu, ok) && ++it < (1u << 20));
#pragma unroll
                    for (int i = 1; i < 4; i++) if (v[i].x > v[0].x) v[0] = v[i];
                    const uint32_t key = __reduce_max_sync(0xffffffffu, v[0].x);
                    const uint32_t md = __reduce_or_sync(0xffffffffu, v[0].x == key ? v[0].y : 0u);
                    const int sel = 2047 - (int)(key & 2047u);
                    const uint4* xp = reinterpret_cast<const uint4*>(P.x + (size_t)sel * D_) + lane;
#pragma unroll
                    for (int i = 0; i < 4; i++) v[i] = __ldg(xp + i * 32);
                    const uint32_t m2 = __byte_perm(md, 0, 0x1010);
                    const float rs = rcp(bf_hi(md));
                    const uint32_t ord = (key >> 11) - 1u;
                    const float r = __uint_as_float(((ord & 0x8000u) ? (ord & 0x7FFFu) : (~ord & 0xFFFFu)) << 16);
                    sts128(sb + SM_MISC, (uint32_t)sel, __float_as_uint(round_bf16(rcp(1.0f + ex2(-r * LOG2E)))), epoch, 0u);
#pragma unroll
                    for (int i = 0; i < 4; i++) {
                        const uint32_t e0 = ln_pair(v[i].x, m2, rs), e1 = ln_pair(v[i].y, m2, rs), e2 = ln_pair(v[i].z, m2, rs), e3 = ln_pair(v[i].w, m2, rs);
                        const uint32_t xa = sb + SM_XS + i * 512 + (lane >> 2) * 64 + (lane & 3) * 4;
                        sts32(xa, __byte_perm(e0, e2, 0x5410)); sts32(xa + 16, __byte_perm(e0, e2, 0x7632));
                        sts32(xa + 32, __byte_perm(e1, e3, 0x5410)); sts32(xa + 48, __byte_perm(e1, e3, 0x7632));
                    }
                    TLP(elect, 25);
                    __syncwarp();
                    mbar_arrive_if(elect, bars + 8 * B_XS);
                }
            }
            if (aw == 2) {
                    const int l = lane < 24 ? lane : 0;
                    const float4* src = &get_acc()->cs[((l >> 3) * 16 + hp) * 24 + (l & 7)];
                    float4 v0, v1, v2;
                    uint4 v[4];
                    unsigned it = 0;
                    bool ok;
#pragma unroll 1
                    do {
                        v0 = ld_gpu(src); v1 = ld_gpu(src + 8); v2 = ld_gpu(src + 16);
                        ok = v0.w == 32.0f && v1.w == 32.0f && v2.w == 32.0f;
#pragma unroll
                        for (int i = 0; i < 4; i++) v[i] = ld_gpu(reinterpret_cast<const uint4*>(&P.scr->rows[rb * 256]) + i * 32 + lane);
#pragma unroll
                        for (int i = 0; i < 4; i++) ok = ok && v[i].y == epoch + 1u && v[i].w == epoch + 1u;
                    } while (!__all_sync(0xffffffffu, ok) && ++it < (1u << 20));
#pragma unroll
                    for (int i = 0; i < 4; i++) {
                        const uint32_t o = i * 256 + lane * 8;
                        sts64(sb + SM_MD + o, v[i].x, v[i].z);
                        sts64(sb + SM_RS + o, __float_as_uint(rcp(bf_hi(v[i].x))), __float_as_uint(rcp(bf_hi(v[i].z))));
                        const uint32_t h0 = hmul2(dup_lo(v[i].x), 0xBF00BF00u), h1 = hmul2(dup_lo(v[i].z), 0xBF00BF00u);
                        sts128(sb + SM_AX + o * 4, h0, h0 & 0xFFFFu, 0u, 0u);
                        sts128(sb + SM_AX + o * 4 + 16, h1, h1 & 0xFFFFu, 0u, 0u);
                    }
                    sts128(sb + SM_H + lane * 16, 0u, 0u, 0u, 0u); sts128(sb + SM_H + 512 + lane * 16, 0u, 0u, 0u, 0u);
                    const uint32_t e2 = __reduce_max_sync(0xffffffffu, l >= 16 ? __float_as_uint(v2.z) : 0u) >> 23;
                    sts32(sb + SM_MISC + 16, (uint32_t)min(max(187 - (int)((e2 + 1) >> 1), 1), 180) << 23);
                    float cc[8] = {v0.x, v0.y, v0.z, v1.x, v1.y, v1.z, v2.x, v2.y};
                    const uint32_t bx = sb + SM_BX + (l >> 3) * 1024;
#pragma unroll 1
                    for (int k = 0; k < 8; k++) {
                        uint32_t w[4];
#pragma unroll
                        for (int i = 0; i < 4; i++) {
                            w[i] = pack_bf16(cc[2 * i], cc[2 * i + 1]);
                            cc[2 * i] -= bf_lo(w[i]); cc[2 * i + 1] -= bf_hi(w[i]);
                        }
                        sts128(bx + k * 128 + (((l & 7) ^ k) * 16), w[0], w[1], w[2], w[3]);
                    }
                    fence_async_smem();
                    __syncwarp();
                    mbar_arrive_if(elect, bars + 8 * B_LN);
                    TLP(elect, 28);
                }
            mbar_wait(bars + 8 * B_XS, 0);
            if (ffn) {
                float a[8];
#pragma unroll
                for (int i = 0; i < 8; i++) a[i] = 0.f;
                TLP(elect, 40 + aw);
                gemv_run<256>(a, ng, nc % 3, (nc / 3) & 1, fbuf + (lane >> 4) * 2048 + (lane & 15) * 16, sb + SM_XS + g0 * 64 + (lane & 12) * 4, 64, fbar, sb + SM_MISC + 12,
                              [&](int m, int b) { issue(nc + m + 3, b); });
                TLP(elect, 44 + aw);
#pragma unroll 1
                for (int o = 4; o <= 8; o <<= 1) {
#pragma unroll
                    for (int i = 0; i < 8; i++) a[i] += __shfl_xor_sync(0xffffffffu, a[i], o);
                }
                if ((lane & 12) == 0) {
                    const uint32_t ga = sb + SM_GU + aw * 256 + (lane >> 4) * 128 + (lane & 3) * 32;
                    sts128(ga, __float_as_uint(a[0]), __float_as_uint(a[1]), __float_as_uint(a[2]), __float_as_uint(a[3]));
                    sts128(ga + 16, __float_as_uint(a[4]), __float_as_uint(a[5]), __float_as_uint(a[6]), __float_as_uint(a[7]));
                }
                nb_sync(NB_AUX, 96);
                if (warp == 9) {
                    if (elect_one()) {
                        mbar_expect_tx(bars + 8 * B_DN, 32768);
                        tma_3d(sb + SM_FB + 8192, &tmS.wd8, bars + 8 * B_DN, 0, blockIdx.x * 32, 0);
                    }
                    const uint32_t ga = sb + SM_GU + lane * 4;
                    const float gg = round_bf16((ldsf(ga) + ldsf(ga + 256)) + ldsf(ga + 512));
                    const float uu = round_bf16((ldsf(ga + 128) + ldsf(ga + 384)) + ldsf(ga + 640));
                    asm volatile("st.shared.u16 [%0], %1;" :: "r"(sb + SM_H + (lane >> 3) * 256 + 112 + (lane & 7) * 2), "h"((uint16_t)pack_bf16(round_bf16(silu_f(gg)) * uu, 0.f)) : "memory");
                    fence_async_smem();
                }
                __syncwarp();
                TLP(tid == 288, 27);
            }
        }
        {
            TLP(tid == 288, 38);
            const int w4 = warp & 3;
            const uint32_t sp = sb + SM_FB + w4 * 1536;
            auto send = [&](int h) {
                if (elect_one()) {
                    asm volatile("cp.reduce.async.bulk.global.shared::cta.bulk_group.add.noftz.f16 [%0], [%1], 1536;"
                                 :: "l"(&P.scr->kv[(hp * 8 + h * 4 + w4) * 96]), "r"(sp) : "memory");
                    asm volatile("cp.async.bulk.commit_group;" ::: "memory");
                }
            };
            float ya[4] = {0.f, 0.f, 0.f, 0.f}, yb[4] = {0.f, 0.f, 0.f, 0.f};
            uint4 g0[3];
#pragma unroll 1
            for (int h = 0; h < 2; h++) {
                {
                    float d[20];
                    const uint32_t alo = dlo(sb + SM_PHI + h * 32768, 16), vlo = dlo(sb + SM_V + h * 20480, 16);
                    mbar_wait(bars + 8 * (B_PHI + h), 0);
                    wgmma_fence();
#pragma unroll
                    for (int k = 0; k < 16; k++)
                        wgmma_ss_n40(d, desc_from(alo + (k >> 2) * 512 + (k & 3) * 2, DH128), desc_from(vlo + (k >> 2) * 320 + (k & 3) * 2, DH128), k);
                    wgmma_commit();
#pragma unroll
                    for (int j = 0; j < 3; j++) g0[j] = ld_gpu(&P.scr->kv[(hp * 8 + w4) * 96 + j * 32 + lane]);
                    asm volatile("cp.async.bulk.wait_group.read 0;" ::: "memory");
                    __syncwarp();
                    const float ksc = ldsf(sb + SM_MISC + 16);
                    wgmma_wait<0>();
                    fence_regs(d);
#define U(x) pack_f16(d[x] * ksc, d[x + 1] * ksc)
                    sts128(sp + lane * 16, U(0), U(4), U(8), pack_f16(d[16], 1.0f));
                    sts128(sp + 512 + lane * 16, U(2), U(6), U(10), pack_f16(d[18], 1.0f));
                    sts128(sp + 1024 + lane * 16, U(12), U(14), 0u, 0x3C000000u);
#undef U
                    fence_async_smem();
                    __syncwarp();
                    send(h);
                    TLP(tid == 256, 30 + h);
                    nb_sync(NB_KV, 128);
                    if (h) break;
                    if (warp == 8 && elect_one()) {
                        mbar_expect_tx(bars + 8 * B_X, 32768);
                        tma_2d(sb, &tmX2, bars + 8 * B_X, (hp >> 1) * 128, rb * 256 + (hp & 1) * 128);
                        tma_2d(sb + 16384, &tmX2, bars + 8 * B_X, (hp >> 1) * 128 + 64, rb * 256 + (hp & 1) * 128);
                        load_wo(4);
                    }
                    __syncwarp();
                }
                if (blockIdx.x < 112) {
                    const uint32_t hlo = dlo(sb + SM_H, 256);
                    mbar_wait(bars + 8 * B_DN, 0);
                    mbar_wait(bars + 8 * (B_DN + 1), 0);
                    wgmma_fence();
#pragma unroll 2
                    for (int k = 0; k < 16; k++) {
                        wgmma_ss_n8_ta(yb, desc_from(dlo(sb + 6 * 16384, 16) + k * 128, DH128), desc_from(hlo + (k & 1) * 32 + 7 - (k >> 1), 8), k);
                        wgmma_ss_n8_ta(ya, desc_from(dlo(sb + SM_FB + 8192, 16) + k * 128, DH128), desc_from(hlo + (k & 1) * 32 + 7 - (k >> 1), 8), k);
                    }
                    wgmma_commit();
                    wgmma_wait<0>();
                    fence_regs(ya); fence_regs(yb);
                    if (warp == 8) {
                        nb_sync(NB_KV, 128);
                        if (elect_one()) { load_wo(2); load_wo(3); }
                        __syncwarp();
                    } else {
                        nb_arrive(NB_KV, 128);
                    }
                    TLP(tid == 288, 29);
                }
            }
            const float kus = __uint_as_float((254u << 23) - lds32(sb + SM_MISC + 16));
            kv_gather<1>(g0, &P.scr->kv[(hp * 8 + w4) * 96 + lane], sb + SM_KVOP + w4 * 256, lane, kus);
            mbar_arrive_if(elect, bars + 8 * B_KV);
            asm volatile("cp.async.bulk.wait_group.read 0;" ::: "memory");
            __syncwarp();
            if (blockIdx.x < 112) {
#define U(x) __float_as_uint(x)
                sts128(sp + lane * 16, U(ya[0]), U(ya[1]), U(ya[2]), U(1.0f));
                sts128(sp + 512 + lane * 16, U(ya[3]), U(yb[0]), U(yb[1]), U(1.0f));
                sts128(sp + 1024 + lane * 16, U(yb[2]), U(yb[3]), 0u, U(1.0f));
#undef U
                fence_async_smem();
                __syncwarp();
                if (elect_one()) {
                    asm volatile("cp.reduce.async.bulk.global.shared::cta.bulk_group.add.f32 [%0], [%1], 1536;"
                                 :: "l"(&get_acc()->y[((blockIdx.x & 3) * 4 + w4) * 96]), "r"(sp) : "memory");
                    asm volatile("cp.async.bulk.commit_group;" ::: "memory");
                }
                __syncwarp();
            }
            if (w4 >= 2) {
                uint4 g1[6];
#pragma unroll
                for (int j = 0; j < 6; j++) g1[j] = make_uint4(0, 0, 0, 0);
                kv_gather<2>(g1, &P.scr->kv[(hp * 8 + 2 * w4) * 96 + lane], sb + SM_KVOP - 5120 + (w4 - 2) * 512, lane, kus);
                mbar_arrive_if(lane < 2, bars + 8 * (B_KV + 1));
            }
            asm volatile("cp.async.bulk.wait_group.read 0;" ::: "memory");
            __syncwarp();
            mbar_arrive_if(elect, bars + 8 * B_S1);
        }
        if (warp == 8) {
            if (elect_one()) {
                const unsigned* flag = &get_acc()->cnt_o[rb * 128];
                uint4 hint = make_uint4(0, 0, 0, 0);
                mbar_wait(bars + 8 * B_O, 0);
#pragma unroll
                for (int i = 0; i < 16; i++) {
                    if (i < 4) {
                        unsigned it = 0;
#pragma unroll 1
                        while ((i == 0 ? hint.x : (i == 1 ? hint.y : (i == 2 ? hint.z : hint.w))) < 16u && ++it < (1u << 14)) hint = ld_gpu(reinterpret_cast<const uint4*>(&P.scr->hint[rb * 32]));
                    }
                    if (i == 4) poll_counter(flag + 32, 16);
                    if (i == 8) mbar_wait(bars + 8 * B_C1, 0);
                    if (i == 4 || i == 8) asm volatile("fence.proxy.async.global;" ::: "memory");
                    if ((i & 3) == 0 && i < 12) TL(i == 0 ? 21 : (i == 4 ? 34 : 36));
                    if (i == 4 || i > 5) mbar_wait(bars + 8 * (B_SD + max(i - 5, 0)), 0);
                    load_o(i, epoch & 1u);
                    if (i == 3) { load_wo(5); mbar_wait(bars + 8 * B_S1, 0); load_wo(6); }
                    if (i >= 5 && i < 14) load_wo(i + 2);
                }
            }
        } else if (warp == 9) {
            if (elect_one()) {
                unsigned* flag = &get_acc()->cnt_o[rb * 128];
                mbar_wait(bars + 8 * B_O, 0);
                asm volatile("red.release.gpu.global.add.u32 [%0], 1;" :: "l"(flag + 32) : "memory");
                TL(35);
            }
        } else if (warp == 10) {
            if (elect_one()) {
                unsigned* f = &get_acc()->cnt_o[rb * 128 + 96];
                mbar_wait(bars + 8 * (B_O + 1), 0);
                asm volatile("red.release.gpu.global.add.u32 [%0], 1;" :: "l"(f) : "memory");
                TL(37);
                poll_counter(f, 16);
                asm volatile("mbarrier.arrive.shared::cta.b64 _, [%0];" :: "r"(bars + 8 * B_C1) : "memory");
            }
        } else if (warp == 11) {
            const uint4 misc = lds128(sb + SM_MISC);
            if ((int)(misc.x >> 7) == rb * 2 + (hp & 1)) {
                float y[4] = {0.f, 0.f, 0.f, 0.f};
#pragma unroll 1
                for (int rep = 0; rep < 4; rep++) {
                    const float4* yp = &get_acc()->y[(rep * 4 + (lane >> 3)) * 96 + (hp >> 3) * 32 + (lane & 7) * 4 + ((hp >> 1) & 3)];
                    float4 u, v;
                    unsigned it = 0;
#pragma unroll 1
                    do { u = ld_gpu(yp); v = ld_gpu(yp + 32); } while (!__all_sync(0xffffffffu, u.w == 28.0f && v.w == 28.0f) && ++it < (1u << 20));
                    if (hp & 8) { y[0] += u.y; y[1] += v.x; y[2] += u.z; y[3] += v.y; } else { y[0] += u.x; y[1] += u.z; y[2] += u.y; y[3] += v.x; }
                }
                const uint32_t sg = __byte_perm(misc.y, 0, 0x3232), ya = sb + SM_Y + ((lane >> 3) * 16 + (lane & 7)) * 2;
                const uint32_t w0 = hmul2(pack_bf16(y[0], y[1]), sg), w1 = hmul2(pack_bf16(y[2], y[3]), sg);
                asm volatile("st.shared.u16 [%0], %1;" :: "r"(ya), "h"((uint16_t)w0) : "memory");
                asm volatile("st.shared.u16 [%0], %1;" :: "r"(ya + 16), "h"((uint16_t)(w0 >> 16)) : "memory");
                asm volatile("st.shared.u16 [%0], %1;" :: "r"(ya + 128), "h"((uint16_t)w1) : "memory");
                asm volatile("st.shared.u16 [%0], %1;" :: "r"(ya + 144), "h"((uint16_t)(w1 >> 16)) : "memory");
                __syncwarp();
                if (lane < 16) {
                    const uint4 xc = __ldg(reinterpret_cast<const uint4*>(P.x + (size_t)misc.x * D_ + (hp >> 1) * 128) + lane);
                    const uint32_t m2 = __byte_perm(lds32(sb + SM_MD + (misc.x & 255u) * 4), 0, 0x1010);
                    const float r = ldsf(sb + SM_RS + (misc.x & 255u) * 4);
                    const uint4 yv = lds128(sb + SM_Y + lane * 16);
                    sts128(sb + SM_Y + lane * 16, silu_pair(hadd2(ln_pair(xc.x, m2, r), yv.x)), silu_pair(hadd2(ln_pair(xc.y, m2, r), yv.y)),
                           silu_pair(hadd2(ln_pair(xc.z, m2, r), yv.z)), silu_pair(hadd2(ln_pair(xc.w, m2, r), yv.w)));
                    sts128(sb + SM_Y + 256 + lane * 16, xc.x, xc.y, xc.z, xc.w);
                }
                __syncwarp();
                mbar_arrive_if(elect, bars + 8 * B_Y);
                TLP(elect, 39);
            }
        }
    } else {
        const int wg = warp >> 2, w4 = warp & 3, g = lane >> 2;
        nb_sync(0, NTHREADS);
        asm volatile("setmaxnreg.inc.sync.aligned.u32 224;");
        TLP(tid == 0, 1);
        const int row0 = wg * 128 + w4 * 16 + g;
        float pq0[16], pq1[16];
        float rs[4];
        uint32_t f2[8], f3[8], q0[8], q1[8], q2[8], q3[8];
        float qa[16], qb[16];
        const uint32_t wlo = dlo(sb + SM_WPHI, 16);
        const uint32_t sw0 = (uint32_t)(((w4 * 2) ^ (lane & 7)) * 16), sw1 = sw0 ^ 16u;
        {
            float acc0[96], acc1[96];
            {
                const uint32_t alo0 = dlo(sb + wg * 16384, 16), blo0 = dlo(sb + 32768, 8192);
                {
#pragma unroll
                    for (int k = 0; k < 4; k++) {
                        if (k == 0) asm volatile("cp.async.wait_group 1;" ::: "memory");
                        if (k == 2) { wgmma_commit(); asm volatile("cp.async.wait_group 0;" ::: "memory"); }
                        if (!(k & 1)) { fence_async_smem(); nb_sync(NB_STAG, 256); wgmma_fence(); }
                        if (k == 0) { TLP(tid == 0, 2); TLG(tid == 0, 49); }
                        wgmma_ss_n192_tb(acc0, desc_from(alo0 + k * 2, DH128), desc_from(blo0 + k * 128, DH128), k);
                        wgmma_ss_n192_tb(acc1, desc_from(alo0 + 512 + k * 2, DH128), desc_from(blo0 + k * 128, DH128), k);
                    }
                    wgmma_commit();
                }
                int s = 1, ph = 0, ps = 0;
#pragma unroll 1
                for (int ks = 1; ks < 16; ks++) {
                    const bool hold = wg && ks == 15;
                    if (hold) {
                        wgmma_wait<0>();
                        mbar_arrive_if(elect, bars + 8 * (B_EMPTY + ps));
                        nb_sync(6, 256);
                    }
                    mbar_wait(bars + 8 * (B_FULL + s), ph);
                    const uint32_t alo = alo0 + s * (STAGE >> 4), blo = blo0 + s * (STAGE >> 4);
                    wgmma_fence();
#pragma unroll
                    for (int k = 0; k < 4; k++) {
                        if (k == 3 && !wg && ks == 15) nb_arrive(6, 256);
                        wgmma_ss_n192_tb(acc0, desc_from(alo + k * 2, DH128), desc_from(blo + k * 128, DH128), 1);
                        wgmma_ss_n192_tb(acc1, desc_from(alo + 512 + k * 2, DH128), desc_from(blo + k * 128, DH128), 1);
                        if (k == 0) {
                            wgmma_commit();
                            wgmma_wait<1>();
                            mbar_arrive_if(elect && !hold, bars + 8 * (B_EMPTY + ps));
                        }
                    }
                    wgmma_commit();
                    ps = s;
                    if (++s == 3) { s = 0; ph ^= 1; }
                }
            }
            mbar_wait(bars + 8 * B_LN, 0);
            wgmma_fence();
            wgmma_ss_n192_tb(acc0, desc_from(dlo(sb + SM_AX + wg * 2048, 0), 128u >> 4), desc_from(dlo(sb + SM_BX, 1024), 1u << 30), 1);
            wgmma_ss_n192_tb(acc1, desc_from(dlo(sb + SM_AX + wg * 2048 + 1024, 0), 128u >> 4), desc_from(dlo(sb + SM_BX, 1024), 1u << 30), 1);
            wgmma_commit();
            mbar_wait(bars + 8 * (B_EMPTY + 2), 0);
            mbar_wait(bars + 8 * B_WPHI, 0);
            {
                uint32_t md[4];
#pragma unroll
                for (int i = 0; i < 4; i++) {
                    const int r = row0 + (i >> 1) * 64 + (i & 1) * 8;
                    md[i] = __byte_perm(lds32(sb + SM_MD + r * 4), 0, 0x3232);
                    rs[i] = ldsf(sb + SM_RS + r * 4);
                }
                const uint32_t zb = sb + SM_V + wg * 10240 + (lane >> 4) * 5120 + 4096 + (lane & 7) * 128 + (sw0 ^ ((lane & 8) * 2));
                stsm_t(zb, md[0], md[1], md[2], md[3]);
                stsm_t(zb + 20480, md[0], md[1], md[2], md[3]);
            }
            wgmma_wait<0>();
            fence_regs(acc0); fence_regs(acc1);
            TLP(tid == 0, 3); TLG(tid == 0, 50);
            const uint32_t vb = sb + SM_V + wg * 10240 + lane * 128;
            uint32_t f0[8], f1[8], v[8];
            pack_head<64>(acc0, v); stsm_t(vb + sw0, v[0], v[2], v[4], v[6]); stsm_t(vb + sw1, v[1], v[3], v[5], v[7]);
            pack_head<64>(acc1, v); stsm_t(vb + 5120 + sw0, v[0], v[2], v[4], v[6]); stsm_t(vb + 5120 + sw1, v[1], v[3], v[5], v[7]);
#pragma unroll
            for (int i = 32; i < 48; i++) { asm volatile("" : "+f"(acc0[i]) :: "memory"); asm volatile("" : "+f"(acc1[i]) :: "memory"); }
            pack_head<32>(acc0, f0); pack_head<32>(acc1, f1);
            wgmma_fence();
            feat_mma(pq0, f0, wlo); feat_mma(pq1, f1, wlo);
            wgmma_commit();
            pack_head<80>(acc0, v); stsm_t(vb + 20480 + sw0, v[0], v[2], v[4], v[6]); stsm_t(vb + 20480 + sw1, v[1], v[3], v[5], v[7]);
            pack_head<80>(acc1, v); stsm_t(vb + 25600 + sw0, v[0], v[2], v[4], v[6]); stsm_t(vb + 25600 + sw1, v[1], v[3], v[5], v[7]);
            pack_head<48>(acc0, f2); pack_head<48>(acc1, f3);
            pack_head<0>(acc0, q0); pack_head<0>(acc1, q1);
#pragma unroll
            for (int i = 0; i < 16; i++) { qa[i] = acc0[16 + i]; qb[i] = acc1[16 + i]; }
            fence_regs(f2); fence_regs(f3); fence_regs(q0); fence_regs(q1);
            wgmma_wait<0>();
            fence_regs(pq0); fence_regs(pq1); fence_regs(f0); fence_regs(f1);
            mbar_arrive_if(elect, bars + 8 * B_T);
            TLP(tid == 0, 4);
        }
#pragma unroll 1
        for (int h = 0; h < 2; h++) {
            const uint32_t pb = sb + SM_PHI + wg * 16384 + lane * 128 + h * 32768;
            key_head(pq0, pq1, rs, pb + sw0, pb + sw1);
            wgmma_fence();
            feat_mma(pq0, f2, wlo + 128 - h * 128); feat_mma(pq1, f3, wlo + 128 - h * 128);
            wgmma_commit();
            fence_async_smem();
            __syncwarp();
            mbar_arrive_if(elect, bars + 8 * (B_PHI + h));
            TLP(tid == 0, 6 + 2 * h);
            mbar_wait(bars + 8 * B_T, 0);
            wgmma_wait<0>();
            fence_regs(pq0); fence_regs(pq1); fence_regs(f2); fence_regs(f3);
#pragma unroll
            for (int j = 0; j < 8; j++) { f2[j] = q0[j]; f3[j] = q1[j]; }
            fence_regs(f2); fence_regs(f3);
        }
#pragma unroll
        for (int j = 0; j < 8; j++) { q2[j] = pack_bf16(qa[2 * j], qa[2 * j + 1]); q3[j] = pack_bf16(qb[2 * j], qb[2 * j + 1]); }
        const uint32_t par = lds32(sb + SM_MISC + 8) & 1u;
        unsigned* flag = &P.scr->acc[par].cnt_o[rb * 128];
        const int orow = (hp & 1) * 128 + wg * 64 + w4 * 16 + (lane >> 4);
        const size_t goff = (size_t)(rb * 256 + orow) * D_ + (hp >> 1) * 128 + (lane & 15) * 8;
        uint4 gv[8], xv[8];
#pragma unroll
        for (int i = 0; i < 8; i++) xv[i] = make_uint4(0, 0, 0, 0);
#pragma unroll
        for (int i = 0; i < GSPLIT2; i++) gv[i] = make_uint4(0, 0, 0, 0);
        const uint32_t rowc = sb + ((lane >> 3) & 1) * 16384 + (wg * 64 + w4 * 16 + (lane >> 4)) * 128;
        {
            uint32_t hbump;
            asm volatile("mov.u32 %0, %1;" : "=r"(hbump) : "r"((uint32_t)(hp < 8 && elect)));
            __nv_bfloat16* od = P.o + (size_t)(par * S_ + rb * 256 + row0) * D_ + hp * 32 + (lane & 3) * 8;
#pragma unroll 1
            for (int h = 0; h < 2; h++) {
                uint32_t pa[8], na[8], pb[8], nb[8];
                features(pq0, pq1, rs, pa, na, pb, nb);
                TLP(tid == 0, 16 + h);
                if (h == 0) {
                    wgmma_fence();
                    feat_mma(pq0, q2, wlo + 128); feat_mma(pq1, q3, wlo + 128);
                    wgmma_commit();
                    mbar_wait(bars + 8 * B_X, 0);
#pragma unroll
                    for (int i = 0; i < 8; i++) xv[i] = lds128(rowc + i * 256 + (((lane & 7) ^ ((2 * i + (lane >> 4)) & 7)) * 16));
#pragma unroll
                    for (int i = 0; i < GSPLIT; i++) { gv[i] = xv[i]; gate_item(gv[i], sb, orow + 2 * i); }
                    wgmma_wait<0>();
                    fence_regs(pq0); fence_regs(pq1); fence_regs(q2); fence_regs(q3);
                    TLP(tid == 0, 18);
                } else {
#pragma unroll
                    for (int i = GSPLIT; i < GSPLIT2; i++) { gv[i] = xv[i]; gate_item(gv[i], sb, orow + 2 * i); }
                    TLP(tid == 0, 10);
                }
                {
                    float d0[20], e0[20], d1[20], e1[20];
                    const uint32_t klo = dlo(sb + SM_KVOP - h * 5120, 128);
                    fence_regs(pa); fence_regs(na); fence_regs(pb); fence_regs(nb);
                    mbar_wait(bars + 8 * (B_KV + h), 0);
                    TLP(tid == 0, 32 + h);
                    wgmma_fence();
                    o_mma(d0, e0, pa, na, klo);
                    o_mma(d1, e1, pb, nb, klo);
                    wgmma_commit();
                    wgmma_wait<0>();
                    fence_regs(d0); fence_regs(e0); fence_regs(pa); fence_regs(na);
                    fence_regs(d1); fence_regs(e1); fence_regs(pb); fence_regs(nb);
                    o_store(d0, e0, od + h * 512);
                    o_store(d1, e1, od + h * 512 + 64 * D_);
                    __syncwarp();
                    asm volatile("{\n.reg .pred q;\nsetp.gt.s32 q, %1, %2;\n@q red.relaxed.gpu.global.add.u32 [%0], %1;\n}" :: "l"(&P.scr->hint[rb * 32 + (hp >> 1) + lane]), "r"(hbump), "r"(h) : "memory");
                    mbar_arrive_if(elect, bars + 8 * (B_O + h));
                }
                TLP(tid == 0, 9 + 2 * h);
            }
        }
        float ghr[8], ghm[8];
#pragma unroll
        for (int i = GSPLIT2; i < 8; i++) { ghr[i] = 0.5f * ldsf(sb + SM_RS + (orow + 2 * i) * 4); ghm[i] = -bf_lo(lds32(sb + SM_MD + (orow + 2 * i) * 4)) * ghr[i]; }
        float acc[64];
        {
            const uint32_t alo0 = dlo(sb + wg * 8192, 16), blo0 = dlo(sb, 8192);
            const uint32_t ta0 = sb + (wg * 64 + w4 * 16) * 128 + lane * 16;
            uint4 cv[2][4];
#pragma unroll
            for (int i = 0; i < 1; i++) {
                mbar_wait(bars + 8 * (B_OF + i), 0);
#pragma unroll
                for (int j = 0; j < 4; j++) cv[i][j] = lds128(ta0 + i * 16384 + j * 512);
            }
#pragma unroll
            for (int i = 0; i < 16; i++) {
                const uint32_t alo = alo0 + o_slot(i) * 1024, blo = blo0 + wo_slot(i) * 1024;
                if (i < 4) {
                    bool bad = false;
#pragma unroll
                    for (int j = 0; j < 4; j++) bad |= (cv[i & 1][j].x | cv[i & 1][j].y | cv[i & 1][j].z | cv[i & 1][j].w) == 0u;
                    if (__builtin_expect(__any_sync(0xffffffffu, bad), 0)) {
                        poll_counter(flag + 32, 16);
#pragma unroll 1
                        for (int j = 0; j < 4; j++) {
                            const int r = j * 4 + (lane >> 3);
                            const uint4 v = ld_gpu(reinterpret_cast<const uint4*>(P.o + (size_t)(par * S_ + rb * 256 + (orow & ~1) + r) * D_ + i * 64) + ((lane ^ r) & 7));
                            sts128(ta0 + (i & 3) * 16384 + j * 512, v.x, v.y, v.z, v.w);
                        }
                        fence_async_smem();
                        __syncwarp();
                    }
                } else {
                    mbar_wait(bars + 8 * (B_OF + i), 0);
                }
                if (i == OSTAG && wg == 0) nb_sync(NB_STAG, 256);
                wgmma_fence();
#pragma unroll
                for (int k = 0; k < 4; k++) {
                    if (i == 15 && k == OARR && wg) nb_arrive(NB_STAG, 256);
                    wgmma_ss_n128_tb(acc, desc_from(alo + k * 2, DH128), desc_from(blo + k * 128, DH128), k | i);
                    if (k == OREL) {
                        if (i > 0 && i < 12) {
                            wgmma_commit();
                            wgmma_wait<1>();
                            mbar_arrive_if(elect, bars + 8 * (B_SD + i - 1));
                        }
                    }
                }
                wgmma_commit();
                if (i == 0) { TLP(tid == 0, 12); TLG(tid == 0, 51); }
                if (i < 3) {
                    mbar_wait(bars + 8 * (B_OF + i + 1), 0);
#pragma unroll
                    for (int j = 0; j < 4; j++) cv[~i & 1][j] = lds128(ta0 + (i + 1) * 16384 + j * 512);
                }
                static_assert(2 * (8 - GSPLIT2) <= 16 - GST, "");
                if (i >= GST && GSPLIT2 + (i - GST) / 2 < 8) {
                    const int q = GSPLIT2 + (i - GST) / 2;
                    if ((i - GST) & 1) { gv[q].z = gate_pair(xv[q].z, ghr[q], ghm[q]); gv[q].w = gate_pair(xv[q].w, ghr[q], ghm[q]); asm volatile("" : "+r"(gv[q].z), "+r"(gv[q].w) :: "memory"); }
                    else { gv[q].x = gate_pair(xv[q].x, ghr[q], ghm[q]); gv[q].y = gate_pair(xv[q].y, ghr[q], ghm[q]); asm volatile("" : "+r"(gv[q].x), "+r"(gv[q].y) :: "memory"); }
                }
            }
        }
        wgmma_wait<0>();
        fence_regs(acc);
        TLP(tid == 0, 13); TLG(tid == 0, 52);
        {
            const uint32_t stg = sb + (wg * 64 + w4 * 16) * 128;
            const int rr = lane & 7;
#pragma unroll
            for (int c = 0; c < 4; c++) {
                const uint32_t a0 = stg + (c >> 1) * 16384 + rr * 128 + ((((c & 1) * 4 + (lane >> 3)) ^ rr) * 16);
                stsm(a0, pack_bf16(acc[c * 16 + 0], acc[c * 16 + 1]), pack_bf16(acc[c * 16 + 4], acc[c * 16 + 5]),
                     pack_bf16(acc[c * 16 + 8], acc[c * 16 + 9]), pack_bf16(acc[c * 16 + 12], acc[c * 16 + 13]));
                stsm(a0 + 1024, pack_bf16(acc[c * 16 + 2], acc[c * 16 + 3]), pack_bf16(acc[c * 16 + 6], acc[c * 16 + 7]),
                     pack_bf16(acc[c * 16 + 10], acc[c * 16 + 11]), pack_bf16(acc[c * 16 + 14], acc[c * 16 + 15]));
            }
            __syncwarp();
#pragma unroll
            for (int i = 0; i < 8; i++) {
                const uint4 sv = lds128(rowc + i * 256 + (((lane & 7) ^ ((2 * i + (lane >> 4)) & 7)) * 16));
                uint4 o;
                o.x = hadd2(xv[i].x, hmul2(sv.x, gv[i].x)); o.y = hadd2(xv[i].y, hmul2(sv.y, gv[i].y));
                o.z = hadd2(xv[i].z, hmul2(sv.z, gv[i].z)); o.w = hadd2(xv[i].w, hmul2(sv.w, gv[i].w));
                *reinterpret_cast<uint4*>(P.out + goff + (size_t)i * 2 * D_) = o;
            }
            const uint32_t sel = lds32(sb + SM_MISC);
            if ((int)(sel >> 4) == rb * 16 + (orow >> 4)) {
                mbar_wait(bars + 8 * B_Y, 0);
                if ((sel & 1u) == (uint32_t)(lane >> 4)) {
                    const int i = (sel & 15u) >> 1;
                    const uint4 sv = lds128(rowc + i * 256 + (((lane & 7) ^ (sel & 7u)) * 16));
                    const uint4 gq = lds128(sb + SM_Y + (lane & 15) * 16), xq = lds128(sb + SM_Y + 256 + (lane & 15) * 16);
                    *reinterpret_cast<uint4*>(P.out + goff + (size_t)i * 2 * D_) = make_uint4(hadd2(xq.x, hmul2(sv.x, gq.x)), hadd2(xq.y, hmul2(sv.y, gq.y)), hadd2(xq.z, hmul2(sv.z, gq.z)), hadd2(xq.w, hmul2(sv.w, gq.w)));
                }
            }
        }
        TLG(tid == 0, 53);
        if (tid == 0) { TL(14); TL_DUMP(); }
        if (blockIdx.x == 0 && tid == 0) asm volatile("st.relaxed.gpu.global.u32 [%0], %1;" :: "l"(&P.scr->epoch), "r"(lds32(sb + SM_MISC + 8) + 1u) : "memory");
    }
}

typedef CUresult (*PFN_encodeTiled)(CUtensorMap*, CUtensorMapDataType, cuuint32_t, void*, const cuuint64_t*, const cuuint64_t*,
                                    const cuuint32_t*, const cuuint32_t*, CUtensorMapInterleave, CUtensorMapSwizzle,
                                    CUtensorMapL2promotion, CUtensorMapFloatOOBfill);

void make_map(PFN_encodeTiled fn, CUtensorMap* m, const void* ptr, int rank, const cuuint64_t* dims, const cuuint64_t* strides, const cuuint32_t* box, CUtensorMapSwizzle sw) {
    const cuuint32_t es[5] = {1, 1, 1, 1, 1};
    fn(m, CU_TENSOR_MAP_DATA_TYPE_BFLOAT16, rank, const_cast<void*>(ptr), dims, strides, box, es, CU_TENSOR_MAP_INTERLEAVE_NONE,
       sw, CU_TENSOR_MAP_L2_PROMOTION_L2_256B, CU_TENSOR_MAP_FLOAT_OOB_FILL_NONE);
}
void make_2d(PFN_encodeTiled fn, CUtensorMap* m, const void* ptr, uint64_t rows, uint64_t cols, uint32_t box_rows, uint32_t box_cols, CUtensorMapSwizzle sw) {
    const cuuint64_t gd[2] = {cols, rows}, gs[1] = {cols * 2};
    const cuuint32_t bd[2] = {box_cols, box_rows};
    make_map(fn, m, ptr, 2, gd, gs, bd, sw);
}

}

extern "C" void kernel_launch(void* const* d_in, const int* in_sizes, int n_in, void* d_out, int out_size) {
    (void)in_sizes; (void)n_in; (void)out_size;
    static PFN_encodeTiled fn = nullptr;
    static void* o_ptr = nullptr;
    static void* scr_ptr = nullptr;
    static void* tl_ptr = nullptr;
    if (!fn) {
        void* p = nullptr;
        cudaDriverEntryPointQueryResult st;
        cudaGetDriverEntryPoint("cuTensorMapEncodeTiled", &p, cudaEnableDefault, &st);
        fn = (PFN_encodeTiled)p;
        cudaGetSymbolAddress(&o_ptr, g_o);
        cudaGetSymbolAddress(&scr_ptr, g_scr);
        cudaFuncSetAttribute(fused_kernel, cudaFuncAttributeMaxDynamicSharedMemorySize, SM_TOTAL);
    }
    CUtensorMap tmX, tmW, tmPhi, tmWo, tmO, tmX2;
    SideMaps tmS;
    make_2d(fn, &tmX, d_in[0], S_, D_, 256, 64, CU_TENSOR_MAP_SWIZZLE_128B);
    {
        const cuuint64_t gd[3] = {1024, 1024, 3}, gs[2] = {6144, 2048};
        const cuuint32_t bd[3] = {64, 64, 3};
        make_map(fn, &tmW, d_in[1], 3, gd, gs, bd, CU_TENSOR_MAP_SWIZZLE_128B);
    }
    make_2d(fn, &tmS.wc, d_in[1], D_, 3 * D_, 32, 64, CU_TENSOR_MAP_SWIZZLE_NONE);
    make_2d(fn, &tmPhi, d_in[2], 1024, 32, 64, 32, CU_TENSOR_MAP_SWIZZLE_64B);
    make_2d(fn, &tmS.wg, d_in[6], D_, F_, 32, 32, CU_TENSOR_MAP_SWIZZLE_NONE);
    make_2d(fn, &tmS.wu, d_in[7], D_, F_, 32, 32, CU_TENSOR_MAP_SWIZZLE_NONE);
    {
        const cuuint64_t gd[3] = {64, F_, 16}, gs[2] = {2048, 128};
        const cuuint32_t bd[3] = {64, 32, 8};
        make_map(fn, &tmS.wd8, d_in[8], 3, gd, gs, bd, CU_TENSOR_MAP_SWIZZLE_128B);
    }
    {
        const cuuint64_t gd[4] = {64, 64, 16, 16}, gs[3] = {2048, 64 * 2048, 128};
        const cuuint32_t bd[4] = {64, 32, 2, 2};
        make_map(fn, &tmWo, d_in[3], 4, gd, gs, bd, CU_TENSOR_MAP_SWIZZLE_128B);
    }
    make_2d(fn, &tmO, o_ptr, 2 * S_, D_, 128, 64, CU_TENSOR_MAP_SWIZZLE_128B);
    make_2d(fn, &tmX2, d_in[0], S_, D_, 128, 64, CU_TENSOR_MAP_SWIZZLE_128B);
    Params P;
    P.x = (const __nv_bfloat16*)d_in[0];
    P.wr = (const __nv_bfloat16*)d_in[5];
    P.wqkv = (const __nv_bfloat16*)d_in[1];
    P.wg = (const __nv_bfloat16*)d_in[6];
    P.wu = (const __nv_bfloat16*)d_in[7];
    P.wd = (const __nv_bfloat16*)d_in[8];
    P.wo = (const __nv_bfloat16*)d_in[3];
    P.out = (__nv_bfloat16*)d_out;
    P.o = (__nv_bfloat16*)o_ptr;
    P.scr = (Scratch*)scr_ptr;
    P.tl = (unsigned long long*)tl_ptr;
    cudaLaunchConfig_t cfg = {};
    cfg.gridDim = dim3(NCTA); cfg.blockDim = dim3(NTHREADS); cfg.dynamicSmemBytes = SM_TOTAL; cfg.stream = cudaStreamPerThread;
    cudaLaunchAttribute at[1];
    at[0].id = cudaLaunchAttributeCooperative; at[0].val.cooperative = 1;
    cfg.attrs = at; cfg.numAttrs = 1;
    cudaLaunchKernelEx(&cfg, fused_kernel, P, tmX, tmW, tmX2, tmS, tmPhi, tmWo, tmO);
}
```

```cpp
#include <cuda_runtime.h>
#include <cuda_bf16.h>
#include <cuda.h>
#include <stdint.h>

namespace {

constexpr int S_ = 2048, D_ = 1024, F_ = 3584;
constexpr int NCTA = 128, NTHREADS = 384;
#define POLL_NS 100
#define OREL 2
#define OSTAG 12
#define OARR 3
#define NC0 3
#define NC2 4
#define NG0 12
#define NG1 12
#define GSPLIT 1
#define GSPLIT2 2
#define GST 3
#define SARR 3
#define JWO 12

constexpr int STAGE = 57344;
constexpr int SM_PHI = 0;
constexpr int SM_V = 131072;
constexpr int SM_AX = 172032;
constexpr int SM_BX = 176128;
constexpr int SM_SP = 172032;
constexpr int SM_FB = 180224;
constexpr int SM_XS = 221184;
constexpr int SM_KVOP = 172032;
constexpr int SM_MD = 223232;
constexpr int SM_RS = 224256;
constexpr int SM_Y = 225280;
constexpr int SM_GU = 225536;
constexpr int SM_MISC = 226688;
constexpr int SM_H = 179200;
constexpr int SM_BARS = 226816;
constexpr int SM_WPHI = 227840;
constexpr int SM_TOTAL = 232448;

constexpr int B_FULL = 0, B_EMPTY = 3, B_OF = 6, B_SD = 22, B_O = 33, B_PHI = 35, B_T = 37, B_WPHI = 38, B_Y = 39, B_KV = 40, B_LN = 42, B_S1 = 43, B_FF = 44, B_X = 54, B_C1 = 55, B_DN = 56, B_XS = 58, B_COUNT = 59, B_XR = 59;
constexpr int NB_KV = 1, NB_FFN = 2, NB_AUX = 3, NB_DN = 4, NB_STAG = 5;
__device__ __forceinline__ int o_slot(int i) { const int r = i % 5; return r == 4 ? 10 : r; }
__device__ __forceinline__ int wo_slot(int i) { const int r = i % 7; return r == 6 ? 11 : 4 + r; }

struct __align__(128) Acc {
    float4 cs[48 * 8 * 3];
    float4 y[4 * 4 * 3 * 32];
    unsigned cnt_o[16 * 64];
};
constexpr int ACC_VEC_PER_CTA = (int)(sizeof(Acc) / 16 / NCTA);
static_assert(sizeof(Acc) == ACC_VEC_PER_CTA * 16 * NCTA && ACC_VEC_PER_CTA <= 256, "");
struct __align__(128) Scratch {
    Acc acc[2];
    uint4 kv[32 * 4 * 3 * 32];
    unsigned hint[8 * 32];
    uint2 rows[S_];
    uint4 best[NCTA];
    unsigned epoch;
};
__device__ Scratch g_scr;
__device__ __align__(1024) __nv_bfloat16 g_o[2 * S_ * D_];

#define TL(e) do {} while (0)
#define TLP(c, e) do {} while (0)
#define TLG(c, e) do {} while (0)
#define TL_DUMP() do {} while (0)

struct SideMaps { CUtensorMap wc, wg, wu, wd8; };
struct Params {
    const __nv_bfloat16* x;
    const __nv_bfloat16* wr;
    const __nv_bfloat16* wqkv;
    const __nv_bfloat16* wg;
    const __nv_bfloat16* wu;
    const __nv_bfloat16* wd;
    const __nv_bfloat16* wo;
    __nv_bfloat16* out;
    __nv_bfloat16* o;
    Scratch* scr;
    unsigned long long* tl;
};

__device__ __forceinline__ bool elect_one() {
    uint32_t p; asm volatile("{\n.reg .pred q;\nelect.sync _|q, 0xffffffff;\nselp.u32 %0, 1, 0, q;\n}" : "=r"(p)); return p;
}
__device__ __forceinline__ uint32_t smem_u32(const void* p) { return (uint32_t)__cvta_generic_to_shared(p); }
__device__ __forceinline__ void mbar_init(uint32_t bar, uint32_t cnt) { asm volatile("mbarrier.init.shared::cta.b64 [%0], %1;" :: "r"(bar), "r"(cnt) : "memory"); }
__device__ __forceinline__ void mbar_expect_tx(uint32_t bar, uint32_t bytes) { asm volatile("mbarrier.arrive.expect_tx.shared::cta.b64 _, [%0], %1;" :: "r"(bar), "r"(bytes) : "memory"); }
__device__ __forceinline__ void mbar_arrive_if(bool p, uint32_t bar) {
    asm volatile("{\n.reg .pred q;\nsetp.ne.b32 q, %1, 0;\n@q mbarrier.arrive.shared::cta.b64 _, [%0];\n}" :: "r"(bar), "r"((int)p) : "memory");
}
__device__ __forceinline__ void mbar_wait(uint32_t bar, uint32_t parity) {
    asm volatile("{\n.reg .pred p;\n.reg .u32 n;\nmov.u32 n, 0;\n"
                 "WAIT_LOOP:\nmbarrier.try_wait.parity.shared::cta.b64 p, [%0], %1;\n@p bra WAIT_DONE;\n"
                 "add.u32 n, n, 1;\nsetp.lt.u32 p, n, 0x40000;\n@p bra WAIT_LOOP;\nWAIT_DONE:\n}" :: "r"(bar), "r"(parity) : "memory");
}
__device__ __forceinline__ bool mbar_test(uint32_t bar, uint32_t parity) {
    uint32_t ok;
    asm volatile("{\n.reg .pred p;\nmbarrier.test_wait.parity.shared::cta.b64 p, [%1], %2;\nselp.u32 %0, 1, 0, p;\n}" : "=r"(ok) : "r"(bar), "r"(parity) : "memory");
    return __all_sync(0xffffffffu, ok);
}
__device__ __forceinline__ void tma_2d(uint32_t dst, const CUtensorMap* tm, uint32_t bar, int c0, int c1) {
    asm volatile("cp.async.bulk.tensor.2d.shared::cluster.global.mbarrier::complete_tx::bytes [%0], [%1, {%3, %4}], [%2];"
        :: "r"(dst), "l"(tm), "r"(bar), "r"(c0), "r"(c1) : "memory");
}
__device__ __forceinline__ void tma_3d(uint32_t dst, const CUtensorMap* tm, uint32_t bar, int c0, int c1, int c2) {
    asm volatile("cp.async.bulk.tensor.3d.shared::cluster.global.mbarrier::complete_tx::bytes [%0], [%1, {%3, %4, %5}], [%2];"
        :: "r"(dst), "l"(tm), "r"(bar), "r"(c0), "r"(c1), "r"(c2) : "memory");
}
__device__ __forceinline__ void tma_4d(uint32_t dst, const CUtensorMap* tm, uint32_t bar, int c0, int c1, int c2, int c3) {
    asm volatile("cp.async.bulk.tensor.4d.shared::cluster.global.mbarrier::complete_tx::bytes [%0], [%1, {%3, %4, %5, %6}], [%2];"
        :: "r"(dst), "l"(tm), "r"(bar), "r"(c0), "r"(c1), "r"(c2), "r"(c3) : "memory");
}
__device__ __forceinline__ void prefetch_l2(const void* p, uint32_t bytes) { asm volatile("cp.async.bulk.prefetch.L2.global [%0], %1;" :: "l"(p), "r"(bytes) : "memory"); }
__device__ __forceinline__ void wgmma_fence() { asm volatile("wgmma.fence.sync.aligned;" ::: "memory"); }
__device__ __forceinline__ void wgmma_commit() { asm volatile("wgmma.commit_group.sync.aligned;" ::: "memory"); }
template <int N> __device__ __forceinline__ void wgmma_wait() { asm volatile("wgmma.wait_group.sync.aligned %0;" :: "n"(N) : "memory"); }
template <int N> __device__ __forceinline__ void fence_regs(float (&a)[N]) {
#pragma unroll
    for (int i = 0; i < N; i++) asm volatile("" : "+f"(a[i]) :: "memory");
}
template <int N> __device__ __forceinline__ void fence_regs(uint32_t (&a)[N]) {
#pragma unroll
    for (int i = 0; i < N; i++) asm volatile("" : "+r"(a[i]) :: "memory");
}
__device__ __forceinline__ uint64_t desc_from(uint32_t lo, uint32_t hi) { uint64_t d; asm("mov.b64 %0, {%1, %2};" : "=l"(d) : "r"(lo), "r"(hi)); return d; }
__device__ __forceinline__ uint32_t dlo(uint32_t addr, uint32_t lbo) { return ((addr & 0x3FFFF) >> 4) | ((lbo >> 4) << 16); }
__device__ __forceinline__ void nb_sync(int id, int cnt) { asm volatile("bar.sync %0, %1;" :: "r"(id), "r"(cnt) : "memory"); }
__device__ __forceinline__ void nb_arrive(int id, int cnt) { asm volatile("bar.arrive %0, %1;" :: "r"(id), "r"(cnt) : "memory"); }
__device__ __forceinline__ void fence_async_smem() { asm volatile("fence.proxy.async.shared::cta;" ::: "memory"); }
__device__ __forceinline__ void red_v4(float4* p, float a, float b, float c, float d) {
    asm volatile("red.relaxed.gpu.global.add.v4.f32 [%0], {%1, %2, %3, %4};" :: "l"(p), "f"(a), "f"(b), "f"(c), "f"(d) : "memory");
}
__device__ __forceinline__ void red_h8(uint4* p, uint32_t a, uint32_t b, uint32_t c, uint32_t d) {
    asm volatile("red.relaxed.gpu.global.add.noftz.v4.f16x2 [%0], {%1, %2, %3, %4};" :: "l"(p), "r"(a), "r"(b), "r"(c), "r"(d) : "memory");
}
__device__ __forceinline__ float4 ld_gpu(const float4* p) {
    float4 v; asm volatile("ld.relaxed.gpu.global.v4.f32 {%0, %1, %2, %3}, [%4];" : "=f"(v.x), "=f"(v.y), "=f"(v.z), "=f"(v.w) : "l"(p) : "memory"); return v;
}
__device__ __forceinline__ uint4 ld_gpu(const uint4* p) {
    uint4 v; asm volatile("ld.relaxed.gpu.global.v4.u32 {%0, %1, %2, %3}, [%4];" : "=r"(v.x), "=r"(v.y), "=r"(v.z), "=r"(v.w) : "l"(p) : "memory"); return v;
}
__device__ __forceinline__ void poll_counter(const unsigned* p, unsigned target) {
    unsigned it = 0, v;
#pragma unroll 1
    do {
        asm volatile("ld.acquire.gpu.global.u32 %0, [%1];" : "=r"(v) : "l"(p) : "memory");
    } while (v < target && ++it < (1u << 20));
}
__device__ __forceinline__ uint32_t pack_bf16(float lo, float hi) { uint32_t r; asm("cvt.rn.bf16x2.f32 %0, %1, %2;" : "=r"(r) : "f"(hi), "f"(lo)); return r; }
__device__ __forceinline__ uint32_t pack_f16(float lo, float hi) { uint32_t r; asm("cvt.rn.f16x2.f32 %0, %1, %2;" : "=r"(r) : "f"(hi), "f"(lo)); return r; }
__device__ __forceinline__ float2 unpack_f16(uint32_t v) { float2 r; asm("{\n.reg .f16 l, h;\nmov.b32 {l, h}, %2;\ncvt.f32.f16 %0, l;\ncvt.f32.f16 %1, h;\n}" : "=f"(r.x), "=f"(r.y) : "r"(v)); return r; }
__device__ __forceinline__ float bf_lo(uint32_t v) { return __uint_as_float(v << 16); }
__device__ __forceinline__ float bf_hi(uint32_t v) { return __uint_as_float(v & 0xFFFF0000u); }
__device__ __forceinline__ float round_bf16(float v) { return bf_lo(pack_bf16(v, 0.f)); }
__device__ __forceinline__ float ex2(float v) { float r; asm("ex2.approx.ftz.f32 %0, %1;" : "=f"(r) : "f"(v)); return r; }
__device__ __forceinline__ float rcp(float v) { float r; asm("rcp.approx.ftz.f32 %0, %1;" : "=f"(r) : "f"(v)); return r; }
__device__ __forceinline__ float sqrt_a(float v) { float r; asm("sqrt.approx.f32 %0, %1;" : "=f"(r) : "f"(v)); return r; }
__device__ __forceinline__ void stsm(uint32_t addr, uint32_t r0, uint32_t r1, uint32_t r2, uint32_t r3) {
    asm volatile("stmatrix.sync.aligned.m8n8.x4.shared.b16 [%0], {%1, %2, %3, %4};" :: "r"(addr), "r"(r0), "r"(r1), "r"(r2), "r"(r3) : "memory");
}
__device__ __forceinline__ void stsm_t(uint32_t addr, uint32_t r0, uint32_t r1, uint32_t r2, uint32_t r3) {
    asm volatile("stmatrix.sync.aligned.m8n8.x4.trans.shared.b16 [%0], {%1, %2, %3, %4};" :: "r"(addr), "r"(r0), "r"(r1), "r"(r2), "r"(r3) : "memory");
}
__device__ __forceinline__ uint4 lds128(uint32_t addr) {
    uint4 v; asm volatile("ld.shared.v4.u32 {%0, %1, %2, %3}, [%4];" : "=r"(v.x), "=r"(v.y), "=r"(v.z), "=r"(v.w) : "r"(addr) : "memory"); return v;
}
__device__ __forceinline__ void sts128(uint32_t addr, uint32_t a, uint32_t b, uint32_t c, uint32_t d) {
    asm volatile("st.shared.v4.u32 [%0], {%1, %2, %3, %4};" :: "r"(addr), "r"(a), "r"(b), "r"(c), "r"(d) : "memory");
}
__device__ __forceinline__ void sts64(uint32_t addr, uint32_t a, uint32_t b) { asm volatile("st.shared.v2.u32 [%0], {%1, %2};" :: "r"(addr), "r"(a), "r"(b) : "memory"); }
__device__ __forceinline__ uint32_t lds32(uint32_t addr) { uint32_t v; asm volatile("ld.shared.u32 %0, [%1];" : "=r"(v) : "r"(addr) : "memory"); return v; }
__device__ __forceinline__ float ldsf(uint32_t addr) { return __uint_as_float(lds32(addr)); }
__device__ __forceinline__ void sts32(uint32_t addr, uint32_t v) { asm volatile("st.shared.u32 [%0], %1;" :: "r"(addr), "r"(v) : "memory"); }
__device__ __forceinline__ uint32_t hmul2(uint32_t a, uint32_t b) { uint32_t r; asm("mul.rn.bf16x2 %0, %1, %2;" : "=r"(r) : "r"(a), "r"(b)); return r; }
__device__ __forceinline__ uint32_t hadd2(uint32_t a, uint32_t b) { uint32_t r; asm("add.rn.bf16x2 %0, %1, %2;" : "=r"(r) : "r"(a), "r"(b)); return r; }
__device__ __forceinline__ uint32_t hsub2(uint32_t a, uint32_t b) { uint32_t r; asm("sub.rn.bf16x2 %0, %1, %2;" : "=r"(r) : "r"(a), "r"(b)); return r; }

__device__ __forceinline__ void wgmma_ss_n192_tb(float (&d)[96], uint64_t da, uint64_t db, int scale_d) {
    asm volatile(
        "{\n.reg .pred p;\nsetp.ne.b32 p, %98, 0;\n"
        "wgmma.mma_async.sync.aligned.m64n192k16.f32.bf16.bf16 "
        "{%0, %1, %2, %3, %4, %5, %6, %7, %8, %9, %10, %11, %12, %13, %14, %15, %16, %17, %18, %19, %20, %21, %22, %23, %24, %25, %26, %27, %28, %29, %30, %31, %32, %33, %34, %35, %36, %37, %38, %39, %40, %41, %42, %43, %44, %45, %46, %47, %48, %49, %50, %51, %52, %53, %54, %55, %56, %57, %58, %59, %60, %61, %62, %63, %64, %65, %66, %67, %68, %69, %70, %71, %72, %73, %74, %75, %76, %77, %78, %79, %80, %81, %82, %83, %84, %85, %86, %87, %88, %89, %90, %91, %92, %93, %94, %95}, %96, %97, p, 1, 1, 0, 1;\n}\n"
        : "+f"(d[0]), "+f"(d[1]), "+f"(d[2]), "+f"(d[3]), "+f"(d[4]), "+f"(d[5]), "+f"(d[6]), "+f"(d[7]), "+f"(d[8]), "+f"(d[9]), "+f"(d[10]), "+f"(d[11]), "+f"(d[12]), "+f"(d[13]), "+f"(d[14]), "+f"(d[15]), "+f"(d[16]), "+f"(d[17]), "+f"(d[18]), "+f"(d[19]), "+f"(d[20]), "+f"(d[21]), "+f"(d[22]), "+f"(d[23]), "+f"(d[24]), "+f"(d[25]), "+f"(d[26]), "+f"(d[27]), "+f"(d[28]), "+f"(d[29]), "+f"(d[30]), "+f"(d[31]), "+f"(d[32]), "+f"(d[33]), "+f"(d[34]), "+f"(d[35]), "+f"(d[36]), "+f"(d[37]), "+f"(d[38]), "+f"(d[39]), "+f"(d[40]), "+f"(d[41]), "+f"(d[42]), "+f"(d[43]), "+f"(d[44]), "+f"(d[45]), "+f"(d[46]), "+f"(d[47]), "+f"(d[48]), "+f"(d[49]), "+f"(d[50]), "+f"(d[51]), "+f"(d[52]), "+f"(d[53]), "+f"(d[54]), "+f"(d[55]), "+f"(d[56]), "+f"(d[57]), "+f"(d[58]), "+f"(d[59]), "+f"(d[60]), "+f"(d[61]), "+f"(d[62]), "+f"(d[63]), "+f"(d[64]), "+f"(d[65]), "+f"(d[66]), "+f"(d[67]), "+f"(d[68]), "+f"(d[69]), "+f"(d[70]), "+f"(d[71]), "+f"(d[72]), "+f"(d[73]), "+f"(d[74]), "+f"(d[75]), "+f"(d[76]), "+f"(d[77]), "+f"(d[78]), "+f"(d[79]), "+f"(d[80]), "+f"(d[81]), "+f"(d[82]), "+f"(d[83]), "+f"(d[84]), "+f"(d[85]), "+f"(d[86]), "+f"(d[87]), "+f"(d[88]), "+f"(d[89]), "+f"(d[90]), "+f"(d[91]), "+f"(d[92]), "+f"(d[93]), "+f"(d[94]), "+f"(d[95])
        : "l"(da), "l"(db), "r"(scale_d));
}
__device__ __forceinline__ void wgmma_ss_n128_tb(float (&d)[64], uint64_t da, uint64_t db, int scale_d) {
    asm volatile(
        "{\n.reg .pred p;\nsetp.ne.b32 p, %66, 0;\n"
        "wgmma.mma_async.sync.aligned.m64n128k16.f32.bf16.bf16 "
        "{%0, %1, %2, %3, %4, %5, %6, %7, %8, %9, %10, %11, %12, %13, %14, %15, %16, %17, %18, %19, %20, %21, %22, %23, %24, %25, %26, %27, %28, %29, %30, %31, %32, %33, %34, %35, %36, %37, %38, %39, %40, %41, %42, %43, %44, %45, %46, %47, %48, %49, %50, %51, %52, %53, %54, %55, %56, %57, %58, %59, %60, %61, %62, %63}, %64, %65, p, 1, 1, 0, 1;\n}\n"
        : "+f"(d[0]), "+f"(d[1]), "+f"(d[2]), "+f"(d[3]), "+f"(d[4]), "+f"(d[5]), "+f"(d[6]), "+f"(d[7]), "+f"(d[8]), "+f"(d[9]), "+f"(d[10]), "+f"(d[11]), "+f"(d[12]), "+f"(d[13]), "+f"(d[14]), "+f"(d[15]), "+f"(d[16]), "+f"(d[17]), "+f"(d[18]), "+f"(d[19]), "+f"(d[20]), "+f"(d[21]), "+f"(d[22]), "+f"(d[23]), "+f"(d[24]), "+f"(d[25]), "+f"(d[26]), "+f"(d[27]), "+f"(d[28]), "+f"(d[29]), "+f"(d[30]), "+f"(d[31]), "+f"(d[32]), "+f"(d[33]), "+f"(d[34]), "+f"(d[35]), "+f"(d[36]), "+f"(d[37]), "+f"(d[38]), "+f"(d[39]), "+f"(d[40]), "+f"(d[41]), "+f"(d[42]), "+f"(d[43]), "+f"(d[44]), "+f"(d[45]), "+f"(d[46]), "+f"(d[47]), "+f"(d[48]), "+f"(d[49]), "+f"(d[50]), "+f"(d[51]), "+f"(d[52]), "+f"(d[53]), "+f"(d[54]), "+f"(d[55]), "+f"(d[56]), "+f"(d[57]), "+f"(d[58]), "+f"(d[59]), "+f"(d[60]), "+f"(d[61]), "+f"(d[62]), "+f"(d[63])
        : "l"(da), "l"(db), "r"(scale_d));
}
__device__ __forceinline__ void wgmma_ss_n40(float (&d)[20], uint64_t da, uint64_t db, int scale_d) {
    asm volatile(
        "{\n.reg .pred p;\nsetp.ne.b32 p, %22, 0;\n"
        "wgmma.mma_async.sync.aligned.m64n40k16.f32.bf16.bf16 "
        "{%0, %1, %2, %3, %4, %5, %6, %7, %8, %9, %10, %11, %12, %13, %14, %15, %16, %17, %18, %19}, %20, %21, p, 1, 1, 0, 0;\n}\n"
        : "+f"(d[0]), "+f"(d[1]), "+f"(d[2]), "+f"(d[3]), "+f"(d[4]), "+f"(d[5]), "+f"(d[6]), "+f"(d[7]), "+f"(d[8]), "+f"(d[9]), "+f"(d[10]), "+f"(d[11]), "+f"(d[12]), "+f"(d[13]), "+f"(d[14]), "+f"(d[15]), "+f"(d[16]), "+f"(d[17]), "+f"(d[18]), "+f"(d[19])
        : "l"(da), "l"(db), "r"(scale_d));
}
__device__ __forceinline__ void wgmma_ss_n8_ta(float (&d)[4], uint64_t da, uint64_t db, int scale_d) {
    asm volatile(
        "{\n.reg .pred p;\nsetp.ne.b32 p, %6, 0;\n"
        "wgmma.mma_async.sync.aligned.m64n8k16.f32.bf16.bf16 "
        "{%0, %1, %2, %3}, %4, %5, p, 1, 1, 1, 0;\n}\n"
        : "+f"(d[0]), "+f"(d[1]), "+f"(d[2]), "+f"(d[3])
        : "l"(da), "l"(db), "r"(scale_d));
}
__device__ __forceinline__ void wgmma_rs_n32_tb(float (&d)[16], uint32_t a0, uint32_t a1, uint32_t a2, uint32_t a3, uint64_t db, int scale_d) {
    asm volatile(
        "{\n.reg .pred p;\nsetp.ne.b32 p, %21, 0;\n"
        "wgmma.mma_async.sync.aligned.m64n32k16.f32.bf16.bf16 "
        "{%0, %1, %2, %3, %4, %5, %6, %7, %8, %9, %10, %11, %12, %13, %14, %15}, {%16, %17, %18, %19}, %20, p, 1, 1, 1;\n}\n"
        : "+f"(d[0]), "+f"(d[1]), "+f"(d[2]), "+f"(d[3]), "+f"(d[4]), "+f"(d[5]), "+f"(d[6]), "+f"(d[7]), "+f"(d[8]), "+f"(d[9]), "+f"(d[10]), "+f"(d[11]), "+f"(d[12]), "+f"(d[13]), "+f"(d[14]), "+f"(d[15])
        : "r"(a0), "r"(a1), "r"(a2), "r"(a3), "l"(db), "r"(scale_d));
}
__device__ __forceinline__ void wgmma_rs_n40_tb(float (&d)[20], uint32_t a0, uint32_t a1, uint32_t a2, uint32_t a3, uint64_t db, int scale_d) {
    asm volatile(
        "{\n.reg .pred p;\nsetp.ne.b32 p, %25, 0;\n"
        "wgmma.mma_async.sync.aligned.m64n40k16.f32.bf16.bf16 "
        "{%0, %1, %2, %3, %4, %5, %6, %7, %8, %9, %10, %11, %12, %13, %14, %15, %16, %17, %18, %19}, {%20, %21, %22, %23}, %24, p, 1, 1, 1;\n}\n"
        : "+f"(d[0]), "+f"(d[1]), "+f"(d[2]), "+f"(d[3]), "+f"(d[4]), "+f"(d[5]), "+f"(d[6]), "+f"(d[7]), "+f"(d[8]), "+f"(d[9]), "+f"(d[10]), "+f"(d[11]), "+f"(d[12]), "+f"(d[13]), "+f"(d[14]), "+f"(d[15]), "+f"(d[16]), "+f"(d[17]), "+f"(d[18]), "+f"(d[19])
        : "r"(a0), "r"(a1), "r"(a2), "r"(a3), "l"(db), "r"(scale_d));
}

constexpr float LOG2E = 1.4426950408889634f;
constexpr uint32_t DH128 = (1024u >> 4) | (1u << 30);

__device__ __forceinline__ float silu_f(float v) { return v * rcp(1.0f + ex2(-v * LOG2E)); }
__device__ __forceinline__ float silu_t(float v) { const float h = 0.5f * v; float th; asm("tanh.approx.f32 %0, %1;" : "=f"(th) : "f"(h)); return fmaf(h, th, h); }
__device__ __forceinline__ uint32_t ln_pair(uint32_t xv, uint32_t m2, float rs) { const uint32_t a = hsub2(xv, m2); return pack_bf16(bf_lo(a) * rs, bf_hi(a) * rs); }
__device__ __forceinline__ uint32_t silu_pair(uint32_t v) { return pack_bf16(silu_t(bf_lo(v)), silu_t(bf_hi(v))); }
__device__ __forceinline__ uint32_t gate_pair(uint32_t v, float hr, float hm) {
    const float a = fmaf(bf_lo(v), hr, hm), b = fmaf(bf_hi(v), hr, hm);
    float ta, tb;
    asm("tanh.approx.f32 %0, %1;" : "=f"(ta) : "f"(a)); asm("tanh.approx.f32 %0, %1;" : "=f"(tb) : "f"(b));
    return pack_bf16(fmaf(a, ta, a), fmaf(b, tb, b));
}
__device__ __forceinline__ void gate_item(uint4& v, uint32_t sb, int row) {
    const float hr = 0.5f * ldsf(sb + SM_RS + row * 4), hm = -bf_lo(lds32(sb + SM_MD + row * 4)) * hr;
    v.x = gate_pair(v.x, hr, hm); v.y = gate_pair(v.y, hr, hm); v.z = gate_pair(v.z, hr, hm); v.w = gate_pair(v.w, hr, hm);
    asm volatile("" : "+r"(v.x), "+r"(v.y), "+r"(v.z), "+r"(v.w) :: "memory");
}
__device__ __forceinline__ uint32_t hfma2(uint32_t a, uint32_t b, uint32_t c) { uint32_t r; asm("fma.rn.bf16x2 %0, %1, %2, %3;" : "=r"(r) : "r"(a), "r"(b), "r"(c)); return r; }
__device__ __forceinline__ uint32_t dup_lo(uint32_t v) { uint32_t r; asm("{\n.reg .b16 l, h;\nmov.b32 {l, h}, %1;\nmov.b32 %0, {l, l};\n}" : "=r"(r) : "r"(v)); return r; }
__device__ __forceinline__ uint32_t dup_hi(uint32_t v) { uint32_t r; asm("{\n.reg .b16 l, h;\nmov.b32 {l, h}, %1;\nmov.b32 %0, {h, h};\n}" : "=r"(r) : "r"(v)); return r; }
__device__ __forceinline__ uint32_t hmax2(uint32_t a, uint32_t b) { uint32_t r; asm("max.NaN.bf16x2 %0, %1, %2;" : "=r"(r) : "r"(a), "r"(b)); return r; }
template <bool SQ> __device__ __forceinline__ void colsum8(float (&a)[8], float& sq, const uint4 (&v)[8]) {
    uint32_t q = 0;
#pragma unroll
    for (int i = 0; i < 8; i++) {
        a[0] += bf_lo(v[i].x); a[1] += bf_hi(v[i].x); a[2] += bf_lo(v[i].y); a[3] += bf_hi(v[i].y);
        a[4] += bf_lo(v[i].z); a[5] += bf_hi(v[i].z); a[6] += bf_lo(v[i].w); a[7] += bf_hi(v[i].w);
        if (SQ) q = hfma2(v[i].x, v[i].x, hfma2(v[i].y, v[i].y, hfma2(v[i].z, v[i].z, hfma2(v[i].w, v[i].w, q))));
    }
    if (SQ) sq += bf_lo(q) + bf_hi(q);
}
__device__ __forceinline__ void hfma8(uint4& h, uint32_t w, const uint4& v) { h.x = hfma2(v.x, w, h.x); h.y = hfma2(v.y, w, h.y); h.z = hfma2(v.z, w, h.z); h.w = hfma2(v.w, w, h.w); }
template <int ST, class F>
__device__ __forceinline__ void gemv_run(float (&a)[8], int cnt, int b, uint32_t ph, uint32_t lo, uint32_t wa, uint32_t ws, uint32_t bar0, uint32_t pin, F done) {
    uint32_t rdy = 0;
#pragma unroll 1
    for (int m = 0; m < cnt; m++) {
        if (!rdy) mbar_wait(bar0 + b * 8, ph);
        uint4 A[8];
        const uint4 w = lds128(wa);
#pragma unroll
        for (int i = 0; i < 8; i++) A[i] = lds128(lo + b * 4096 + i * ST);
        const int bc = b;
        if (++b == 3) { b = 0; ph ^= 1; }
        asm volatile("{\n.reg .pred p;\nmbarrier.test_wait.parity.shared::cta.b64 p, [%1], %2;\nselp.u32 %0, 1, 0, p;\n}" : "=r"(rdy) : "r"(bar0 + b * 8), "r"(ph) : "memory");
        sts32(pin, 0u);
        wa += ws;
        uint4 h = make_uint4(0, 0, 0, 0);
        hfma8(h, dup_lo(w.x), A[0]); hfma8(h, dup_hi(w.x), A[1]); hfma8(h, dup_lo(w.y), A[2]); hfma8(h, dup_hi(w.y), A[3]);
        hfma8(h, dup_lo(w.z), A[4]); hfma8(h, dup_hi(w.z), A[5]); hfma8(h, dup_lo(w.w), A[6]); hfma8(h, dup_hi(w.w), A[7]);
        a[0] += bf_lo(h.x); a[1] += bf_hi(h.x); a[2] += bf_lo(h.y); a[3] += bf_hi(h.y);
        a[4] += bf_lo(h.z); a[5] += bf_hi(h.z); a[6] += bf_lo(h.w); a[7] += bf_hi(h.w);
        fence_regs(a);
        done(m, bc);
    }
}
template <int OFF> __device__ __forceinline__ void pack_head(const float (&acc)[96], uint32_t (&f)[8]) {
#pragma unroll
    for (int i = 0; i < 8; i++) f[i] = pack_bf16(acc[OFF + 2 * i], acc[OFF + 2 * i + 1]);
}
__device__ __forceinline__ void feat_mma(float (&p)[16], const uint32_t (&f)[8], uint32_t wlo) {
    constexpr uint32_t DH = (512u >> 4) | (2u << 30);
    wgmma_rs_n32_tb(p, f[0], f[1], f[2], f[3], desc_from(wlo, DH), 0);
    wgmma_rs_n32_tb(p, f[4], f[5], f[6], f[7], desc_from(wlo + 64, DH), 1);
}
template <int S> __device__ __forceinline__ void row_ext(const float (&p)[16], float& a, float& b) {
    auto op = [](float x, float y) { return S > 0 ? fmaxf(x, y) : fminf(x, y); };
    a = op(op(op(p[0], p[1]), op(p[4], p[5])), op(op(p[8], p[9]), op(p[12], p[13])));
    b = op(op(op(p[2], p[3]), op(p[6], p[7])), op(op(p[10], p[11]), op(p[14], p[15])));
#pragma unroll
    for (int o = 1; o <= 2; o <<= 1) { a = op(a, __shfl_xor_sync(0xffffffffu, a, o)); b = op(b, __shfl_xor_sync(0xffffffffu, b, o)); }
}
__device__ __forceinline__ void dual_exp(const float (&p)[16], float scA, float scB, uint32_t (&pos)[8], uint32_t (&neg)[8], uint32_t& chk) {
#pragma unroll
    for (int j = 0; j < 8; j += 2) {
        const float a0 = ex2(p[2 * j] * scA), a1 = ex2(p[2 * j + 1] * scA);
        const float b0 = ex2(p[2 * j + 2] * scB), b1 = ex2(p[2 * j + 3] * scB);
        const float pa = a0 * a1, pb = b0 * b1, R = rcp(pa * pb);
        const uint32_t r = pack_bf16(R * pb, R * pa);
        pos[j] = pack_bf16(a0, a1); pos[j + 1] = pack_bf16(b0, b1);
        neg[j] = hmul2(pos[j], dup_lo(r)); neg[j + 1] = hmul2(pos[j + 1], dup_hi(r));
        chk = hadd2(chk, hadd2(hadd2(pos[j], neg[j]), hadd2(pos[j + 1], neg[j + 1])));
    }
}
template <int S> __device__ __forceinline__ void exact_exp(const float (&p)[16], float scA, float scB, uint32_t (&o)[8]) {
    float mA, mB;
    row_ext<S>(p, mA, mB);
#pragma unroll
    for (int j = 0; j < 8; j++) {
        const float sc = S * ((j & 1) ? scB : scA), m = (j & 1) ? mB : mA;
        const float u = ex2((p[2 * j] - m) * sc), v = ex2((p[2 * j + 1] - m) * sc);
        o[j] = S > 0 ? pack_bf16(u, v) : pack_bf16(v, u);
    }
}
__device__ __forceinline__ void features(const float (&p0)[16], const float (&p1)[16], const float (&rs)[4],
                                         uint32_t (&pa)[8], uint32_t (&na)[8], uint32_t (&pb)[8], uint32_t (&nb)[8]) {
    uint32_t chk = 0;
    dual_exp(p0, rs[0] * LOG2E, rs[1] * LOG2E, pa, na, chk);
    dual_exp(p1, rs[2] * LOG2E, rs[3] * LOG2E, pb, nb, chk);
    if (__builtin_expect(!__all_sync(0xffffffffu, bf_lo(chk) + bf_hi(chk) < 1.0e9f), 0)) {
        exact_exp<1>(p0, rs[0] * LOG2E, rs[1] * LOG2E, pa); exact_exp<-1>(p0, rs[0] * LOG2E, rs[1] * LOG2E, na);
        exact_exp<1>(p1, rs[2] * LOG2E, rs[3] * LOG2E, pb); exact_exp<-1>(p1, rs[2] * LOG2E, rs[3] * LOG2E, nb);
    }
}
__device__ __forceinline__ float quad_sum(float v) { v += __shfl_xor_sync(0xffffffffu, v, 1); return v + __shfl_xor_sync(0xffffffffu, v, 2); }
__device__ __forceinline__ float key_block(const float (&p)[16], float rsA, float rsB, uint32_t d0, uint32_t d1, uint32_t off) {
    float r[8], sp[2], sn[2];
    uint32_t pos[8], neg[8];
    const float scA = rsA * LOG2E, scB = rsB * LOG2E;
#pragma unroll
    for (int j = 0; j < 8; j += 2) {
        const float a0 = ex2(p[2 * j] * scA), a1 = ex2(p[2 * j + 1] * scA);
        const float b0 = ex2(p[2 * j + 2] * scB), b1 = ex2(p[2 * j + 3] * scB);
        const float pa = a0 * a1, pb = b0 * b1, R = rcp(pa * pb), ta = a0 + a1, tb = b0 + b1;
        r[j] = R * pb; r[j + 1] = R * pa;
        if (j == 0) { sp[0] = ta; sp[1] = tb; sn[0] = r[0] * ta; sn[1] = r[1] * tb; }
        else { sp[0] += ta; sp[1] += tb; sn[0] = fmaf(r[j], ta, sn[0]); sn[1] = fmaf(r[j + 1], tb, sn[1]); }
        pos[j] = pack_bf16(a0, a1); pos[j + 1] = pack_bf16(b0, b1);
    }
    const float qa = quad_sum(sp[0]), qb = quad_sum(sp[1]), na = quad_sum(sn[0]), nb = quad_sum(sn[1]);
    const float iq = rcp(qa * qb), nA = rsA * rcp(na), nB = rsB * rcp(nb);
    const uint32_t fp = pack_bf16(rsA * qb * iq, rsB * qa * iq);
#pragma unroll
    for (int j = 0; j < 8; j += 2) {
        const uint32_t rn = pack_bf16(r[j] * nA, r[j + 1] * nB);
        neg[j] = hmul2(pos[j], dup_lo(rn)); neg[j + 1] = hmul2(pos[j + 1], dup_hi(rn));
        pos[j] = hmul2(pos[j], dup_lo(fp)); pos[j + 1] = hmul2(pos[j + 1], dup_hi(fp));
    }
    stsm_t(d0 + 4096, neg[0], neg[2], neg[4], neg[6]); stsm_t(d1 + 4096, neg[1], neg[3], neg[5], neg[7]);
    stsm_t(d0 + off, pos[0], pos[2], pos[4], pos[6]); stsm_t(d1 + off, pos[1], pos[3], pos[5], pos[7]);
    return (qa + qb) + (na + nb);
}
__device__ __forceinline__ void shift_max(float (&p)[16]) {
    float mA, mB;
    row_ext<1>(p, mA, mB);
#pragma unroll
    for (int j = 0; j < 16; j++) p[j] -= (j & 2) ? mB : mA;
}
__device__ __forceinline__ void key_head(float (&p0)[16], float (&p1)[16], const float (&rs)[4], uint32_t d0, uint32_t d1) {
    uint32_t st;
    asm volatile("mov.u32 %0, 0;" : "=r"(st));
    bool again;
#pragma unroll 1
    do {
        const uint32_t off = (st & 2u) << 11;
        const float chk = key_block(p0, rs[0], rs[1], d0, d1, off) + key_block(p1, rs[2], rs[3], d0 + 8192, d1 + 8192, off);
        again = st == 1u || (st == 0u && !__all_sync(0xffffffffu, chk < 1.0e9f));
        if (__builtin_expect(again, 0)) {
            if (st) {
#pragma unroll
                for (int j = 0; j < 16; j += 2) {
                    float t = p0[j]; p0[j] = -p0[j + 1]; p0[j + 1] = -t;
                    t = p1[j]; p1[j] = -p1[j + 1]; p1[j + 1] = -t;
                }
            }
            shift_max(p0); shift_max(p1);
            st++;
        }
        asm volatile("" ::: "memory");
    } while (again);
}
__device__ __forceinline__ void o_mma(float (&d)[20], float (&e)[20], const uint32_t (&pos)[8], const uint32_t (&neg)[8], uint32_t klo) {
    wgmma_rs_n40_tb(d, pos[0], pos[1], pos[2], pos[3], desc_from(klo, 1024u >> 4), 0);
    wgmma_rs_n40_tb(e, neg[0], neg[1], neg[2], neg[3], desc_from(klo + 32, 1024u >> 4), 0);
    wgmma_rs_n40_tb(d, pos[4], pos[5], pos[6], pos[7], desc_from(klo + 16, 1024u >> 4), 1);
    wgmma_rs_n40_tb(e, neg[4], neg[5], neg[6], neg[7], desc_from(klo + 48, 1024u >> 4), 1);
}
__device__ __forceinline__ void o_store(const float (&d)[20], const float (&e)[20], __nv_bfloat16* dst) {
    const float iA = rcp(fmaf(d[16], e[17], fmaf(e[16], d[17], 1e-6f * d[17] * e[17])));
    const float iB = rcp(fmaf(d[18], e[19], fmaf(e[18], d[19], 1e-6f * d[19] * e[19])));
    const float pA = e[17] * iA, nA = d[17] * iA, pB = e[19] * iB, nB = d[19] * iB;
    uint32_t oa[4], ob[4];
#pragma unroll
    for (int j = 0; j < 4; j++) {
        oa[j] = pack_bf16(fmaf(d[j * 4], pA, e[j * 4] * nA), fmaf(d[j * 4 + 1], pA, e[j * 4 + 1] * nA));
        ob[j] = pack_bf16(fmaf(d[j * 4 + 2], pB, e[j * 4 + 2] * nB), fmaf(d[j * 4 + 3], pB, e[j * 4 + 3] * nB));
    }
    *reinterpret_cast<uint4*>(dst) = make_uint4(oa[0] ? oa[0] : 0x8000u, oa[1], oa[2], oa[3]);
    *reinterpret_cast<uint4*>(dst + 8 * D_) = make_uint4(ob[0] ? ob[0] : 0x8000u, ob[1], ob[2], ob[3]);
}

template <int N> __device__ __forceinline__ void kv_gather(uint4 (&v)[3 * N], const uint4* src, uint32_t dst, int lane, float us) {
    unsigned it = 0;
#pragma unroll 1
    while (++it < (1u << 20)) {
        bool ok = true;
#pragma unroll
        for (int j = 0; j < 3 * N; j++) ok = ok && (v[j].w >> 16) == 0x4800u;
        if (__all_sync(0xffffffffu, ok)) break;
#pragma unroll
        for (int j = 0; j < 3 * N; j++) v[j] = ld_gpu(src + j * 32);
    }
    dst += (lane >> 2) * 16;
    auto cv = [&](uint32_t w) { const float2 f = unpack_f16(w); return pack_bf16(f.x * us, f.y * us); };
#pragma unroll
    for (int n = 0; n < N; n++) {
        sts128(dst + (lane & 3) * 1024 + n * 256, cv(v[3 * n].x), cv(v[3 * n].y), cv(v[3 * n].z), cv(v[3 * n + 2].x));
        sts128(dst + (lane & 3) * 1024 + n * 256 + 128, cv(v[3 * n + 1].x), cv(v[3 * n + 1].y), cv(v[3 * n + 1].z), cv(v[3 * n + 2].y));
        sts32(dst + 4096 + n * 256 + (lane & 3) * 4, pack_bf16(unpack_f16(v[3 * n].w).x, 1.0f));
        sts32(dst + 4096 + n * 256 + 128 + (lane & 3) * 4, pack_bf16(unpack_f16(v[3 * n + 1].w).x, 1.0f));
    }
    fence_async_smem();
    __syncwarp();
}

__global__ void __launch_bounds__(NTHREADS, 1)
fused_kernel(const Params P, const __grid_constant__ CUtensorMap tmX, const __grid_constant__ CUtensorMap tmW, const __grid_constant__ CUtensorMap tmX2,
             const __grid_constant__ SideMaps tmS, const __grid_constant__ CUtensorMap tmPhi,
             const __grid_constant__ CUtensorMap tmWo, const __grid_constant__ CUtensorMap tmO) {
    extern __shared__ __align__(1024) uint8_t smem_raw[];
    constexpr uint32_t sb = 1024;
    if (smem_u32(smem_raw) != sb) return;
    constexpr uint32_t bars = sb + SM_BARS;
    const int rb = blockIdx.x >> 4, hp = blockIdx.x & 15;
    TLP(threadIdx.x == 32, 0); TLG(threadIdx.x == 32, 48);
    auto load_stage = [&](int s, int ks) {
        mbar_expect_tx(bars + 8 * (B_FULL + s), STAGE);
        tma_2d(sb + s * STAGE, &tmX, bars + 8 * (B_FULL + s), ks * 64, rb * 256);
        tma_3d(sb + s * STAGE + 32768, &tmW, bars + 8 * (B_FULL + s), hp * 64, ks * 64, 0);
    };
    if (threadIdx.x < 256) {
        const uint32_t t = threadIdx.x, r = t >> 3, sw = ((t ^ r) & 7) * 16;
        const __nv_bfloat16* wp = P.wqkv + (size_t)r * 3 * D_ + hp * 64 + (t & 7) * 8;
        const __nv_bfloat16* xp = P.x + (size_t)(rb * 256 + (t >> 7) * 128 + (r & 15)) * D_ + (t & 7) * 8;
#pragma unroll
        for (int i = 0; i < 3; i++) asm volatile("cp.async.cg.shared.global [%0], [%1], 16;" :: "r"(sb + 32768 + i * 8192 + r * 128 + sw), "l"(wp + i * D_) : "memory");
#pragma unroll
        for (int i = 0; i < 8; i++) asm volatile("cp.async.cg.shared.global [%0], [%1], 16;" :: "r"(sb + (t >> 7) * 16384 + ((r & 15) + i * 16) * 128 + sw), "l"(xp + i * 16 * D_) : "memory");
        asm volatile("cp.async.commit_group;" ::: "memory");
#pragma unroll
        for (int i = 0; i < 3; i++) asm volatile("cp.async.cg.shared.global [%0], [%1], 16;" :: "r"(sb + 36864 + i * 8192 + r * 128 + sw), "l"(wp + 96 * D_ + i * D_) : "memory");
        asm volatile("cp.async.commit_group;" ::: "memory");
    }
    const int tid = threadIdx.x, warp = __shfl_sync(0xffffffffu, tid >> 5, 0), lane = tid & 31;
    const bool elect = lane == 0;

    if (warp >= 8) {
        const int aw = warp - 9;
        auto load_o = [&](int i, unsigned par) {
            mbar_expect_tx(bars + 8 * (B_OF + i), 16384);
            tma_2d(sb + o_slot(i) * 16384, &tmO, bars + 8 * (B_OF + i), i * 64, par * S_ + rb * 256 + (hp & 1) * 128);
        };
        auto load_wo = [&](int i) {
            mbar_expect_tx(bars + 8 * (B_OF + i), 16384);
            tma_4d(sb + wo_slot(i) * 16384, &tmWo, bars + 8 * (B_OF + i), 0, (i >> 3) * 32, (i & 7) * 2, hp & 14);
        };
        if (warp == 9) {
            if (elect_one()) {
#pragma unroll
                for (int i = B_OF; i < B_COUNT; i++)
                    mbar_init(bars + 8 * i, i < B_SD ? 2 : (i < B_WPHI ? 8 : ((i < B_KV || i >= B_FF || i == B_LN) ? 1 : 4)));
                asm volatile("fence.mbarrier_init.release.cluster;" ::: "memory");
            }
        }
        if (warp == 8) {
            if (elect_one()) {
#pragma unroll
                for (int i = 0; i < 3; i++) { mbar_init(bars + 8 * (B_FULL + i), 1); mbar_init(bars + 8 * (B_EMPTY + i), 8); }
                mbar_init(bars + 8 * B_XR, 1);
                asm volatile("fence.mbarrier_init.release.cluster;" ::: "memory");
                asm volatile("mbarrier.arrive.shared::cta.b64 _, [%0];" :: "r"(bars + 8 * B_FULL) : "memory");
            }
            __syncwarp();
            nb_arrive(0, NTHREADS);
        } else {
            __syncwarp();
            nb_sync(0, NTHREADS);
        }
        asm volatile("setmaxnreg.dec.sync.aligned.u32 56;");
        if (warp == 8 && elect_one()) {
            load_stage(1, 1); load_stage(2, 2);
            mbar_expect_tx(bars + 8 * B_XR, 32768);
            asm volatile("cp.async.bulk.shared::cluster.global.mbarrier::complete_tx::bytes [%0], [%1], 32768, [%2];"
                         :: "r"(sb + SM_FB + 4096), "l"(P.x + (size_t)blockIdx.x * 16 * D_), "r"(bars + 8 * B_XR) : "memory");
        }
        __syncwarp();
        nb_sync(NB_KV, 128);
        unsigned epoch;
        asm volatile("ld.relaxed.gpu.global.u32 %0, [%1];" : "=r"(epoch) : "l"(&P.scr->epoch) : "memory");
        auto get_acc = [&]() { return &P.scr->acc[epoch & 1u]; };
        if (warp == 8) {
            epoch = __shfl_sync(0xffffffffu, epoch, 0);
            int s = 0, ph = 0;
#pragma unroll 1
            for (int j = 0; j < 15; j++) {
                mbar_wait(bars + 8 * (B_EMPTY + s), ph);
                if (elect_one()) {
                    if (j < 13) load_stage(s, j + 3);
                    if (j < 2) {
                        prefetch_l2(P.wqkv + (size_t)(256 + j * 384 + blockIdx.x * 3) * 3 * D_, 18432);
                    } else if (j < 10) {
                        if (j == 2) asm volatile("mbarrier.arrive.shared::cta.b64 _, [%0];" :: "r"(bars + 8 * B_FF) : "memory");
                        const size_t o = (size_t)((j - 2) * 128 + blockIdx.x) * F_;
                        prefetch_l2(P.wg + o, F_ * 2); prefetch_l2(P.wu + o, F_ * 2);
                    }
                    if (j == JWO) prefetch_l2(P.wo + (size_t)blockIdx.x * 8 * D_, 16384);
                    if (j == 12) {
                        asm volatile("prefetch.tensormap [%0];" :: "l"(&tmO) : "memory");
                        asm volatile("prefetch.tensormap [%0];" :: "l"(&tmS.wd8) : "memory");
                        asm volatile("prefetch.tensormap [%0];" :: "l"(&tmWo) : "memory");
                        mbar_expect_tx(bars + 8 * B_WPHI, 4096);
                        tma_2d(sb + SM_WPHI, &tmPhi, bars + 8 * B_WPHI, 0, hp * 64);
                    }
                    if (j >= 13) {
                        if (blockIdx.x >= 112 || j == 13) { load_wo(2 * j - 26); load_wo(2 * j - 25); }
                        else {
                            mbar_expect_tx(bars + 8 * (B_DN + 1), 32768);
                            tma_3d(sb + 6 * 16384, &tmS.wd8, bars + 8 * (B_DN + 1), 0, blockIdx.x * 32, 8);
                        }
                    }
                }
                __syncwarp();
                if (++s == 3) { s = 0; ph ^= 1; }
                if (j == 12 && hp == 0 && lane < 4) P.scr->hint[rb * 32 + lane] = 0u;
                if (j >= 3 && j < 11) {
                    uint4* zp = reinterpret_cast<uint4*>(P.o + (size_t)((~epoch & 1u) * S_ + blockIdx.x * 16 + (j - 3) * 2) * D_) + lane;
#pragma unroll
                    for (int i = 0; i < 2; i++) zp[i * 128] = make_uint4(0, 0, 0, 0);
                    const int i = (j - 3) * 32 + lane;
                    if (i < ACC_VEC_PER_CTA) reinterpret_cast<uint4*>(&P.scr->acc[~epoch & 1u])[blockIdx.x * ACC_VEC_PER_CTA + i] = make_uint4(0, 0, 0, 0);
                }
            }
            TLP(elect, 20);
        } else {
            const bool ffn = blockIdx.x < 112;
            const uint32_t fbuf = sb + SM_FB + 4096 + aw * 12288, fbar = bars + 8 * (B_FF + 1 + aw * 3);
        const int nc = aw == 0 ? NC0 : (aw == 1 ? 12 - NC0 - NC2 : NC2), c0 = aw == 0 ? 0 : (aw == 1 ? NC0 : 12 - NC2);
        const int ng = !ffn ? 0 : (aw == 0 ? NG0 : (aw == 1 ? NG1 : 32 - NG0 - NG1)), g0 = aw == 0 ? 0 : (aw == 1 ? NG0 : NG0 + NG1);
        auto issue = [&](int i, int b) {
            __syncwarp();
            if (i < nc + ng && elect_one()) {
                mbar_expect_tx(fbar + b * 8, 4096);
                if (i < nc) {
                    tma_2d(fbuf + b * 4096, &tmS.wc, fbar + b * 8, ((c0 + i) >> 2) * 1024 + hp * 64, rb * 128 + ((c0 + i) & 3) * 32);
                } else {
                    tma_2d(fbuf + b * 4096, &tmS.wg, fbar + b * 8, blockIdx.x * 32, (g0 + i - nc) * 32);
                    tma_2d(fbuf + b * 4096 + 2048, &tmS.wu, fbar + b * 8, blockIdx.x * 32, (g0 + i - nc) * 32);
                }
            }
            __syncwarp();
        };
            {
                uint4 wv[4];
#pragma unroll
                for (int i = 0; i < 4; i++) wv[i] = __ldg(reinterpret_cast<const uint4*>(P.wr) + i * 32 + lane);
                const uint32_t* ww = reinterpret_cast<const uint32_t*>(wv);
                float sw = 0.f;
#pragma unroll
                for (int i = 0; i < 16; i++) sw += bf_lo(ww[i]) + bf_hi(ww[i]);
#pragma unroll 1
                for (int o = 16; o > 0; o >>= 1) sw += __shfl_xor_sync(0xffffffffu, sw, o);
                sts32(sb + SM_MISC + 20, __float_as_uint(sw));
                if (aw == 2) {
#pragma unroll
                    for (int i = 0; i < 3; i++) P.scr->kv[(hp * 8 + rb) * 96 + i * 32 + lane] = make_uint4(0, 0, 0, 0);
                    asm volatile("fence.acq_rel.gpu;" ::: "memory");
                    __syncwarp();
                }
                mbar_wait(bars + 8 * B_XR, 0);
#pragma unroll 1
                for (int r = aw * 6; r < min(aw * 6 + 6, 16); r++) {
                    const uint32_t buf = sb + SM_FB + 4096 + r * 2048;
                    uint4 xv[4];
                    uint32_t c2 = lds32(buf);
#pragma unroll
                    for (int i = 0; i < 4; i++) xv[i] = lds128(buf + i * 512 + lane * 16);
                    sts32(sb + SM_MISC + 12, 0u);
                    c2 = fabsf(bf_lo(c2) - bf_hi(c2)) < 0.25f * fabsf(bf_lo(c2)) ? dup_lo(c2) : 0u;
                    const uint32_t* xw = reinterpret_cast<const uint32_t*>(xv);
                    uint32_t d2[2] = {0u, 0u};
                    float s0 = 0.f, s1 = 0.f, q0 = 0.f, q1 = 0.f;
#pragma unroll
                    for (int i = 0; i < 16; i++) {
                        const uint32_t a = hsub2(xw[i], c2);
                        s0 += bf_lo(a); s1 += bf_hi(a);
                        d2[i & 1] = hfma2(a, ww[i], d2[i & 1]);
                        q0 = fmaf(bf_lo(a), bf_lo(a), q0); q1 = fmaf(bf_hi(a), bf_hi(a), q1);
                    }
                    sts128(sb + SM_SP + r * 512 + lane * 16, __float_as_uint(s0 + s1), __float_as_uint(q0 + q1),
                           __float_as_uint((bf_lo(d2[0]) + bf_hi(d2[0])) + (bf_lo(d2[1]) + bf_hi(d2[1]))), c2 << 16);
                }
                epoch = __shfl_sync(0xffffffffu, epoch, 0);
                if (aw < 2) nb_arrive(NB_FFN, 96);
                mbar_wait(bars + 8 * B_FF, 0);
#pragma unroll 1
                for (int i = 0; i < 3; i++) issue(i, i);
                const unsigned tag = epoch + 1u;
                if (aw == 2) {
                    nb_sync(NB_FFN, 96);
                    TLP(elect, 23);
                    float s = 0.f, q = 0.f, dt = 0.f, x0;
#pragma unroll 8
                    for (int j = 0; j < 16; j++) {
                        const uint4 e = lds128(sb + SM_SP + lane * 256 + ((j + lane) & 15) * 16);
                        s += __uint_as_float(e.x); q += __uint_as_float(e.y); dt += __uint_as_float(e.z); x0 = __uint_as_float(e.w);
                    }
                    s += __shfl_xor_sync(0xffffffffu, s, 1); q += __shfl_xor_sync(0xffffffffu, q, 1); dt += __shfl_xor_sync(0xffffffffu, dt, 1);
                    const float ms = s * (1.0f / D_);
                    const float vb = round_bf16(fmaxf(q - s * ms, 0.f) * (1.0f / D_));
                    const uint32_t md = pack_bf16(x0 + ms, sqrt_a(round_bf16(vb + 1e-5f)));
                    const uint32_t rbits = pack_bf16((dt - (bf_lo(md) - x0) * ldsf(sb + SM_MISC + 20)) * rcp(bf_hi(md)), 0.f);
                    const int row = blockIdx.x * 16 + (lane >> 1);
                    const uint32_t key = ((((rbits & 0x8000u) ? (~rbits & 0xFFFFu) : (rbits | 0x8000u)) + 1u) << 11) | (uint32_t)(2047 - row);
                    asm volatile("st.relaxed.gpu.global.v2.u32 [%0], {%1, %2};" :: "l"(&P.scr->rows[row]), "r"(md), "r"(tag) : "memory");
                    if (key == __reduce_max_sync(0xffffffffu, key))
                        asm volatile("st.relaxed.gpu.global.v4.u32 [%0], {%1, %2, %3, %3};" :: "l"(&P.scr->best[blockIdx.x]), "r"(key), "r"(md), "r"(tag) : "memory");
                    TLP(elect, 24);
                }
                {
                    float a[8], sq = 0.f, wt = 0.f;
#pragma unroll
                    for (int i = 0; i < 8; i++) a[i] = 0.f;
#pragma unroll 1
                    for (int m = 0; m < nc; m++) {
                        const int b = m % 3, c = c0 + m;
                        mbar_wait(fbar + b * 8, (m / 3) & 1);
                        uint4 v[8];
#pragma unroll
                        for (int i = 0; i < 8; i++) v[i] = lds128(fbuf + b * 4096 + i * 512 + lane * 16);
                        sts32(sb + SM_MISC + 12, 0u);
                        colsum8<true>(a, sq, v);
                        fence_regs(a);
                        wt += 1.0f;
                        issue(m + 3, b);
                        if ((c & 3) == 3 || m == nc - 1) {
#pragma unroll 1
                            for (int o = 8; o <= 16; o <<= 1) {
#pragma unroll
                                for (int i = 0; i < 8; i++) a[i] += __shfl_xor_sync(0xffffffffu, a[i], o);
                                sq += __shfl_xor_sync(0xffffffffu, sq, o);
                            }
                            float4* dst = &get_acc()->cs[((c >> 2) * 16 + hp) * 24 + lane];
                            if (lane < 8) { red_v4(dst, a[0], a[1], a[2], wt); red_v4(dst + 8, a[3], a[4], a[5], wt); red_v4(dst + 16, a[6], a[7], sq, wt); }
#pragma unroll
                            for (int i = 0; i < 8; i++) a[i] = 0.f;
                            wt = 0.f;
                        }
                    }
                    TLP(tid == 288, 26); TLP(tid == 320, 15); TLP(tid == 352, 22);
                }
                if (aw == 0) {
                    uint4 v[4];
                    unsigned it = 0;
                    bool ok = true;
#pragma unroll 1
                    do {
                        if (!ok) __nanosleep(200);
#pragma unroll
                        for (int i = 0; i < 4; i++) v[i] = ld_gpu(&P.scr->best[i * 32 + lane]);
                        ok = v[0].z == tag && v[1].z == tag && v[2].z == tag && v[3].z == tag;
                    } while (!__all_sync(0xffffffffu, ok) && ++it < (1u << 20));
#pragma unroll
                    for (int i = 1; i < 4; i++) if (v[i].x > v[0].x) v[0] = v[i];
                    const uint32_t key = __reduce_max_sync(0xffffffffu, v[0].x);
                    const uint32_t md = __reduce_or_sync(0xffffffffu, v[0].x == key ? v[0].y : 0u);
                    const int sel = 2047 - (int)(key & 2047u);
                    const uint4* xp = reinterpret_cast<const uint4*>(P.x + (size_t)sel * D_) + lane;
#pragma unroll
                    for (int i = 0; i < 4; i++) v[i] = __ldg(xp + i * 32);
                    const uint32_t m2 = __byte_perm(md, 0, 0x1010);
                    const float rs = rcp(bf_hi(md));
                    const uint32_t ord = (key >> 11) - 1u;
                    const float r = __uint_as_float(((ord & 0x8000u) ? (ord & 0x7FFFu) : (~ord & 0xFFFFu)) << 16);
                    sts128(sb + SM_MISC, (uint32_t)sel, __float_as_uint(round_bf16(rcp(1.0f + ex2(-r * LOG2E)))), epoch, 0u);
#pragma unroll
                    for (int i = 0; i < 4; i++) {
                        const uint32_t e0 = ln_pair(v[i].x, m2, rs), e1 = ln_pair(v[i].y, m2, rs), e2 = ln_pair(v[i].z, m2, rs), e3 = ln_pair(v[i].w, m2, rs);
                        const uint32_t xa = sb + SM_XS + i * 512 + (lane >> 2) * 64 + (lane & 3) * 4;
                        sts32(xa, __byte_perm(e0, e2, 0x5410)); sts32(xa + 16, __byte_perm(e0, e2, 0x7632));
                        sts32(xa + 32, __byte_perm(e1, e3, 0x5410)); sts32(xa + 48, __byte_perm(e1, e3, 0x7632));
                    }
                    TLP(elect, 25);
                    __syncwarp();
                    mbar_arrive_if(elect, bars + 8 * B_XS);
                }
            }
            if (aw == 2) {
                    const int l = lane < 24 ? lane : 0;
                    const float4* src = &get_acc()->cs[((l >> 3) * 16 + hp) * 24 + (l & 7)];
                    float4 v0, v1, v2;
                    uint4 v[4];
                    unsigned it = 0;
                    bool ok;
#pragma unroll 1
                    do {
                        v0 = ld_gpu(src); v1 = ld_gpu(src + 8); v2 = ld_gpu(src + 16);
                        ok = v0.w == 32.0f && v1.w == 32.0f && v2.w == 32.0f;
#pragma unroll
                        for (int i = 0; i < 4; i++) v[i] = ld_gpu(reinterpret_cast<const uint4*>(&P.scr->rows[rb * 256]) + i * 32 + lane);
#pragma unroll
                        for (int i = 0; i < 4; i++) ok = ok && v[i].y == epoch + 1u && v[i].w == epoch + 1u;
                    } while (!__all_sync(0xffffffffu, ok) && ++it < (1u << 20));
#pragma unroll
                    for (int i = 0; i < 4; i++) {
                        const uint32_t o = i * 256 + lane * 8;
                        sts64(sb + SM_MD + o, v[i].x, v[i].z);
                        sts64(sb + SM_RS + o, __float_as_uint(rcp(bf_hi(v[i].x))), __float_as_uint(rcp(bf_hi(v[i].z))));
                        const uint32_t h0 = hmul2(dup_lo(v[i].x), 0xBF00BF00u), h1 = hmul2(dup_lo(v[i].z), 0xBF00BF00u);
                        sts128(sb + SM_AX + o * 4, h0, h0 & 0xFFFFu, 0u, 0u);
                        sts128(sb + SM_AX + o * 4 + 16, h1, h1 & 0xFFFFu, 0u, 0u);
                    }
                    sts128(sb + SM_H + lane * 16, 0u, 0u, 0u, 0u); sts128(sb + SM_H + 512 + lane * 16, 0u, 0u, 0u, 0u);
                    const uint32_t e2 = __reduce_max_sync(0xffffffffu, l >= 16 ? __float_as_uint(v2.z) : 0u) >> 23;
                    sts32(sb + SM_MISC + 16, (uint32_t)min(max(187 - (int)((e2 + 1) >> 1), 1), 180) << 23);
                    float cc[8] = {v0.x, v0.y, v0.z, v1.x, v1.y, v1.z, v2.x, v2.y};
                    const uint32_t bx = sb + SM_BX + (l >> 3) * 1024;
#pragma unroll 1
                    for (int k = 0; k < 8; k++) {
                        uint32_t w[4];
#pragma unroll
                        for (int i = 0; i < 4; i++) {
                            w[i] = pack_bf16(cc[2 * i], cc[2 * i + 1]);
                            cc[2 * i] -= bf_lo(w[i]); cc[2 * i + 1] -= bf_hi(w[i]);
                        }
                        sts128(bx + k * 128 + (((l & 7) ^ k) * 16), w[0], w[1], w[2], w[3]);
                    }
                    fence_async_smem();
                    __syncwarp();
                    mbar_arrive_if(elect, bars + 8 * B_LN);
                    TLP(elect, 28);
                }
            mbar_wait(bars + 8 * B_XS, 0);
            if (ffn) {
                float a[8];
#pragma unroll
                for (int i = 0; i < 8; i++) a[i] = 0.f;
                TLP(elect, 40 + aw);
                gemv_run<256>(a, ng, nc % 3, (nc / 3) & 1, fbuf + (lane >> 4) * 2048 + (lane & 15) * 16, sb + SM_XS + g0 * 64 + (lane & 12) * 4, 64, fbar, sb + SM_MISC + 12,
                              [&](int m, int b) { issue(nc + m + 3, b); });
                TLP(elect, 44 + aw);
#pragma unroll 1
                for (int o = 4; o <= 8; o <<= 1) {
#pragma unroll
                    for (int i = 0; i < 8; i++) a[i] += __shfl_xor_sync(0xffffffffu, a[i], o);
                }
                if ((lane & 12) == 0) {
                    const uint32_t ga = sb + SM_GU + aw * 256 + (lane >> 4) * 128 + (lane & 3) * 32;
                    sts128(ga, __float_as_uint(a[0]), __float_as_uint(a[1]), __float_as_uint(a[2]), __float_as_uint(a[3]));
                    sts128(ga + 16, __float_as_uint(a[4]), __float_as_uint(a[5]), __float_as_uint(a[6]), __float_as_uint(a[7]));
                }
                nb_sync(NB_AUX, 96);
                if (warp == 9) {
                    if (elect_one()) {
                        mbar_expect_tx(bars + 8 * B_DN, 32768);
                        tma_3d(sb + SM_FB + 8192, &tmS.wd8, bars + 8 * B_DN, 0, blockIdx.x * 32, 0);
                    }
                    const uint32_t ga = sb + SM_GU + lane * 4;
                    const float gg = round_bf16((ldsf(ga) + ldsf(ga + 256)) + ldsf(ga + 512));
                    const float uu = round_bf16((ldsf(ga + 128) + ldsf(ga + 384)) + ldsf(ga + 640));
                    asm volatile("st.shared.u16 [%0], %1;" :: "r"(sb + SM_H + (lane >> 3) * 256 + 112 + (lane & 7) * 2), "h"((uint16_t)pack_bf16(round_bf16(silu_f(gg)) * uu, 0.f)) : "memory");
                    fence_async_smem();
                }
                __syncwarp();
                TLP(tid == 288, 27);
            }
        }
        {
            TLP(tid == 288, 38);
            const int w4 = warp & 3;
            const uint32_t sp = sb + SM_FB + w4 * 1536;
            auto send = [&](int h) {
                if (elect_one()) {
                    asm volatile("cp.reduce.async.bulk.global.shared::cta.bulk_group.add.noftz.f16 [%0], [%1], 1536;"
                                 :: "l"(&P.scr->kv[(hp * 8 + h * 4 + w4) * 96]), "r"(sp) : "memory");
                    asm volatile("cp.async.bulk.commit_group;" ::: "memory");
                }
            };
            float ya[4] = {0.f, 0.f, 0.f, 0.f}, yb[4] = {0.f, 0.f, 0.f, 0.f};
            uint4 g0[3];
#pragma unroll 1
            for (int h = 0; h < 2; h++) {
                {
                    float d[20];
                    const uint32_t alo = dlo(sb + SM_PHI + h * 32768, 16), vlo = dlo(sb + SM_V + h * 20480, 16);
                    mbar_wait(bars + 8 * (B_PHI + h), 0);
                    wgmma_fence();
#pragma unroll
                    for (int k = 0; k < 16; k++)
                        wgmma_ss_n40(d, desc_from(alo + (k >> 2) * 512 + (k & 3) * 2, DH128), desc_from(vlo + (k >> 2) * 320 + (k & 3) * 2, DH128), k);
                    wgmma_commit();
#pragma unroll
                    for (int j = 0; j < 3; j++) g0[j] = ld_gpu(&P.scr->kv[(hp * 8 + w4) * 96 + j * 32 + lane]);
                    asm volatile("cp.async.bulk.wait_group.read 0;" ::: "memory");
                    __syncwarp();
                    const float ksc = ldsf(sb + SM_MISC + 16);
                    wgmma_wait<0>();
                    fence_regs(d);
#define U(x) pack_f16(d[x] * ksc, d[x + 1] * ksc)
                    sts128(sp + lane * 16, U(0), U(4), U(8), pack_f16(d[16], 1.0f));
                    sts128(sp + 512 + lane * 16, U(2), U(6), U(10), pack_f16(d[18], 1.0f));
                    sts128(sp + 1024 + lane * 16, U(12), U(14), 0u, 0x3C000000u);
#undef U
                    fence_async_smem();
                    __syncwarp();
                    send(h);
                    TLP(tid == 256, 30 + h);
                    nb_sync(NB_KV, 128);
                    if (h) break;
                    if (warp == 8 && elect_one()) {
                        mbar_expect_tx(bars + 8 * B_X, 32768);
                        tma_2d(sb, &tmX2, bars + 8 * B_X, (hp >> 1) * 128, rb * 256 + (hp & 1) * 128);
                        tma_2d(sb + 16384, &tmX2, bars + 8 * B_X, (hp >> 1) * 128 + 64, rb * 256 + (hp & 1) * 128);
                        load_wo(4);
                    }
                    __syncwarp();
                }
                if (blockIdx.x < 112) {
                    const uint32_t hlo = dlo(sb + SM_H, 256);
                    mbar_wait(bars + 8 * B_DN, 0);
                    mbar_wait(bars + 8 * (B_DN + 1), 0);
                    wgmma_fence();
#pragma unroll 2
                    for (int k = 0; k < 16; k++) {
                        wgmma_ss_n8_ta(yb, desc_from(dlo(sb + 6 * 16384, 16) + k * 128, DH128), desc_from(hlo + (k & 1) * 32 + 7 - (k >> 1), 8), k);
                        wgmma_ss_n8_ta(ya, desc_from(dlo(sb + SM_FB + 8192, 16) + k * 128, DH128), desc_from(hlo + (k & 1) * 32 + 7 - (k >> 1), 8), k);
                    }
                    wgmma_commit();
                    wgmma_wait<0>();
                    fence_regs(ya); fence_regs(yb);
                    if (warp == 8) {
                        nb_sync(NB_KV, 128);
                        if (elect_one()) { load_wo(2); load_wo(3); }
                        __syncwarp();
                    } else {
                        nb_arrive(NB_KV, 128);
                    }
                    TLP(tid == 288, 29);
                }
            }
            const float kus = __uint_as_float((254u << 23) - lds32(sb + SM_MISC + 16));
            kv_gather<1>(g0, &P.scr->kv[(hp * 8 + w4) * 96 + lane], sb + SM_KVOP + w4 * 256, lane, kus);
            mbar_arrive_if(elect, bars + 8 * B_KV);
            asm volatile("cp.async.bulk.wait_group.read 0;" ::: "memory");
            __syncwarp();
            if (blockIdx.x < 112) {
#define U(x) __float_as_uint(x)
                sts128(sp + lane * 16, U(ya[0]), U(ya[1]), U(ya[2]), U(1.0f));
                sts128(sp + 512 + lane * 16, U(ya[3]), U(yb[0]), U(yb[1]), U(1.0f));
                sts128(sp + 1024 + lane * 16, U(yb[2]), U(yb[3]), 0u, U(1.0f));
#undef U
                fence_async_smem();
                __syncwarp();
                if (elect_one()) {
                    asm volatile("cp.reduce.async.bulk.global.shared::cta.bulk_group.add.f32 [%0], [%1], 1536;"
                                 :: "l"(&get_acc()->y[((blockIdx.x & 3) * 4 + w4) * 96]), "r"(sp) : "memory");
                    asm volatile("cp.async.bulk.commit_group;" ::: "memory");
                }
                __syncwarp();
            }
            if (w4 >= 2) {
                uint4 g1[6];
#pragma unroll
                for (int j = 0; j < 6; j++) g1[j] = make_uint4(0, 0, 0, 0);
                kv_gather<2>(g1, &P.scr->kv[(hp * 8 + 2 * w4) * 96 + lane], sb + SM_KVOP - 5120 + (w4 - 2) * 512, lane, kus);
                mbar_arrive_if(lane < 2, bars + 8 * (B_KV + 1));
            }
            asm volatile("cp.async.bulk.wait_group.read 0;" ::: "memory");
            __syncwarp();
            mbar_arrive_if(elect, bars + 8 * B_S1);
        }
        if (warp == 8) {
            if (elect_one()) {
                const unsigned* flag = &get_acc()->cnt_o[rb * 128];
                uint4 hint = make_uint4(0, 0, 0, 0);
                mbar_wait(bars + 8 * B_O, 0);
#pragma unroll
                for (int i = 0; i < 16; i++) {
                    if (i < 4) {
                        unsigned it = 0;
#pragma unroll 1
                        while ((i == 0 ? hint.x : (i == 1 ? hint.y : (i == 2 ? hint.z : hint.w))) < 16u && ++it < (1u << 14)) hint = ld_gpu(reinterpret_cast<const uint4*>(&P.scr->hint[rb * 32]));
                    }
                    if (i == 4) poll_counter(flag + 32, 16);
                    if (i == 8) mbar_wait(bars + 8 * B_C1, 0);
                    if (i == 4 || i == 8) asm volatile("fence.proxy.async.global;" ::: "memory");
                    if ((i & 3) == 0 && i < 12) TL(i == 0 ? 21 : (i == 4 ? 34 : 36));
                    if (i == 4 || i > 5) mbar_wait(bars + 8 * (B_SD + max(i - 5, 0)), 0);
                    load_o(i, epoch & 1u);
                    if (i == 3) { load_wo(5); mbar_wait(bars + 8 * B_S1, 0); load_wo(6); }
                    if (i >= 5 && i < 14) load_wo(i + 2);
                }
            }
        } else if (warp == 9) {
            if (elect_one()) {
                unsigned* flag = &get_acc()->cnt_o[rb * 128];
                mbar_wait(bars + 8 * B_O, 0);
                asm volatile("red.release.gpu.global.add.u32 [%0], 1;" :: "l"(flag + 32) : "memory");
                TL(35);
            }
        } else if (warp == 10) {
            if (elect_one()) {
                unsigned* f = &get_acc()->cnt_o[rb * 128 + 96];
                mbar_wait(bars + 8 * (B_O + 1), 0);
                asm volatile("red.release.gpu.global.add.u32 [%0], 1;" :: "l"(f) : "memory");
                TL(37);
                poll_counter(f, 16);
                asm volatile("mbarrier.arrive.shared::cta.b64 _, [%0];" :: "r"(bars + 8 * B_C1) : "memory");
            }
        } else if (warp == 11) {
            const uint4 misc = lds128(sb + SM_MISC);
            if ((int)(misc.x >> 7) == rb * 2 + (hp & 1)) {
                float y[4] = {0.f, 0.f, 0.f, 0.f};
#pragma unroll 1
                for (int rep = 0; rep < 4; rep++) {
                    const float4* yp = &get_acc()->y[(rep * 4 + (lane >> 3)) * 96 + (hp >> 3) * 32 + (lane & 7) * 4 + ((hp >> 1) & 3)];
                    float4 u, v;
                    unsigned it = 0;
#pragma unroll 1
                    do { u = ld_gpu(yp); v = ld_gpu(yp + 32); } while (!__all_sync(0xffffffffu, u.w == 28.0f && v.w == 28.0f) && ++it < (1u << 20));
                    if (hp & 8) { y[0] += u.y; y[1] += v.x; y[2] += u.z; y[3] += v.y; } else { y[0] += u.x; y[1] += u.z; y[2] += u.y; y[3] += v.x; }
                }
                const uint32_t sg = __byte_perm(misc.y, 0, 0x3232), ya = sb + SM_Y + ((lane >> 3) * 16 + (lane & 7)) * 2;
                const uint32_t w0 = hmul2(pack_bf16(y[0], y[1]), sg), w1 = hmul2(pack_bf16(y[2], y[3]), sg);
                asm volatile("st.shared.u16 [%0], %1;" :: "r"(ya), "h"((uint16_t)w0) : "memory");
                asm volatile("st.shared.u16 [%0], %1;" :: "r"(ya + 16), "h"((uint16_t)(w0 >> 16)) : "memory");
                asm volatile("st.shared.u16 [%0], %1;" :: "r"(ya + 128), "h"((uint16_t)w1) : "memory");
                asm volatile("st.shared.u16 [%0], %1;" :: "r"(ya + 144), "h"((uint16_t)(w1 >> 16)) : "memory");
                __syncwarp();
                if (lane < 16) {
                    const uint4 xc = __ldg(reinterpret_cast<const uint4*>(P.x + (size_t)misc.x * D_ + (hp >> 1) * 128) + lane);
                    const uint32_t m2 = __byte_perm(lds32(sb + SM_MD + (misc.x & 255u) * 4), 0, 0x1010);
                    const float r = ldsf(sb + SM_RS + (misc.x & 255u) * 4);
                    const uint4 yv = lds128(sb + SM_Y + lane * 16);
                    sts128(sb + SM_Y + lane * 16, silu_pair(hadd2(ln_pair(xc.x, m2, r), yv.x)), silu_pair(hadd2(ln_pair(xc.y, m2, r), yv.y)),
                           silu_pair(hadd2(ln_pair(xc.z, m2, r), yv.z)), silu_pair(hadd2(ln_pair(xc.w, m2, r), yv.w)));
                    sts128(sb + SM_Y + 256 + lane * 16, xc.x, xc.y, xc.z, xc.w);
                }
                __syncwarp();
                mbar_arrive_if(elect, bars + 8 * B_Y);
                TLP(elect, 39);
            }
        }
    } else {
        const int wg = warp >> 2, w4 = warp & 3, g = lane >> 2;
        nb_sync(0, NTHREADS);
        asm volatile("setmaxnreg.inc.sync.aligned.u32 224;");
        TLP(tid == 0, 1);
        const int row0 = wg * 128 + w4 * 16 + g;
        float pq0[16], pq1[16];
        float rs[4];
        uint32_t f2[8], f3[8], q0[8], q1[8], q2[8], q3[8];
        float qa[16], qb[16];
        const uint32_t wlo = dlo(sb + SM_WPHI, 16);
        const uint32_t sw0 = (uint32_t)(((w4 * 2) ^ (lane & 7)) * 16), sw1 = sw0 ^ 16u;
        {
            float acc0[96], acc1[96];
            {
                const uint32_t alo0 = dlo(sb + wg * 16384, 16), blo0 = dlo(sb + 32768, 8192);
                {
#pragma unroll
                    for (int k = 0; k < 4; k++) {
                        if (k == 0) asm volatile("cp.async.wait_group 1;" ::: "memory");
                        if (k == 2) { wgmma_commit(); asm volatile("cp.async.wait_group 0;" ::: "memory"); }
                        if (!(k & 1)) { fence_async_smem(); nb_sync(NB_STAG, 256); wgmma_fence(); }
                        if (k == 0) { TLP(tid == 0, 2); TLG(tid == 0, 49); }
                        wgmma_ss_n192_tb(acc0, desc_from(alo0 + k * 2, DH128), desc_from(blo0 + k * 128, DH128), k);
                        wgmma_ss_n192_tb(acc1, desc_from(alo0 + 512 + k * 2, DH128), desc_from(blo0 + k * 128, DH128), k);
                    }
                    wgmma_commit();
                }
                int s = 1, ph = 0, ps = 0;
#pragma unroll 1
                for (int ks = 1; ks < 16; ks++) {
                    const bool hold = wg && ks == 15;
                    if (hold) {
                        wgmma_wait<0>();
                        mbar_arrive_if(elect, bars + 8 * (B_EMPTY + ps));
                        nb_sync(6, 256);
                    }
                    mbar_wait(bars + 8 * (B_FULL + s), ph);
                    const uint32_t alo = alo0 + s * (STAGE >> 4), blo = blo0 + s * (STAGE >> 4);
                    wgmma_fence();
#pragma unroll
                    for (int k = 0; k < 4; k++) {
                        if (k == SARR && !wg && ks == 15) nb_arrive(6, 256);
                        wgmma_ss_n192_tb(acc0, desc_from(alo + k * 2, DH128), desc_from(blo + k * 128, DH128), 1);
                        wgmma_ss_n192_tb(acc1, desc_from(alo + 512 + k * 2, DH128), desc_from(blo + k * 128, DH128), 1);
                        if (k == 0) {
                            wgmma_commit();
                            wgmma_wait<1>();
                            mbar_arrive_if(elect && !hold, bars + 8 * (B_EMPTY + ps));
                        }
                    }
                    wgmma_commit();
                    ps = s;
                    if (++s == 3) { s = 0; ph ^= 1; }
                }
            }
            if (SARR == 4 && !wg) nb_arrive(6, 256);
            mbar_wait(bars + 8 * B_LN, 0);
            wgmma_fence();
            wgmma_ss_n192_tb(acc0, desc_from(dlo(sb + SM_AX + wg * 2048, 0), 128u >> 4), desc_from(dlo(sb + SM_BX, 1024), 1u << 30), 1);
            wgmma_ss_n192_tb(acc1, desc_from(dlo(sb + SM_AX + wg * 2048 + 1024, 0), 128u >> 4), desc_from(dlo(sb + SM_BX, 1024), 1u << 30), 1);
            wgmma_commit();
            if (SARR == 5 && !wg) nb_arrive(6, 256);
            mbar_wait(bars + 8 * (B_EMPTY + 2), 0);
            mbar_wait(bars + 8 * B_WPHI, 0);
            {
                uint32_t md[4];
#pragma unroll
                for (int i = 0; i < 4; i++) {
                    const int r = row0 + (i >> 1) * 64 + (i & 1) * 8;
                    md[i] = __byte_perm(lds32(sb + SM_MD + r * 4), 0, 0x3232);
                    rs[i] = ldsf(sb + SM_RS + r * 4);
                }
                const uint32_t zb = sb + SM_V + wg * 10240 + (lane >> 4) * 5120 + 4096 + (lane & 7) * 128 + (sw0 ^ ((lane & 8) * 2));
                stsm_t(zb, md[0], md[1], md[2], md[3]);
                stsm_t(zb + 20480, md[0], md[1], md[2], md[3]);
            }
            wgmma_wait<0>();
            fence_regs(acc0); fence_regs(acc1);
            TLP(tid == 0, 3); TLG(tid == 0, 50);
            const uint32_t vb = sb + SM_V + wg * 10240 + lane * 128;
            uint32_t f0[8], f1[8], v[8];
            pack_head<64>(acc0, v); stsm_t(vb + sw0, v[0], v[2], v[4], v[6]); stsm_t(vb + sw1, v[1], v[3], v[5], v[7]);
            pack_head<64>(acc1, v); stsm_t(vb + 5120 + sw0, v[0], v[2], v[4], v[6]); stsm_t(vb + 5120 + sw1, v[1], v[3], v[5], v[7]);
#pragma unroll
            for (int i = 32; i < 48; i++) { asm volatile("" : "+f"(acc0[i]) :: "memory"); asm volatile("" : "+f"(acc1[i]) :: "memory"); }
            pack_head<32>(acc0, f0); pack_head<32>(acc1, f1);
            wgmma_fence();
            feat_mma(pq0, f0, wlo); feat_mma(pq1, f1, wlo);
            wgmma_commit();
            pack_head<80>(acc0, v); stsm_t(vb + 20480 + sw0, v[0], v[2], v[4], v[6]); stsm_t(vb + 20480 + sw1, v[1], v[3], v[5], v[7]);
            pack_head<80>(acc1, v); stsm_t(vb + 25600 + sw0, v[0], v[2], v[4], v[6]); stsm_t(vb + 25600 + sw1, v[1], v[3], v[5], v[7]);
            pack_head<48>(acc0, f2); pack_head<48>(acc1, f3);
            pack_head<0>(acc0, q0); pack_head<0>(acc1, q1);
#pragma unroll
            for (int i = 0; i < 16; i++) { qa[i] = acc0[16 + i]; qb[i] = acc1[16 + i]; }
            fence_regs(f2); fence_regs(f3); fence_regs(q0); fence_regs(q1);
            wgmma_wait<0>();
            fence_regs(pq0); fence_regs(pq1); fence_regs(f0); fence_regs(f1);
            mbar_arrive_if(elect, bars + 8 * B_T);
            TLP(tid == 0, 4);
        }
#pragma unroll 1
        for (int h = 0; h < 2; h++) {
            const uint32_t pb = sb + SM_PHI + wg * 16384 + lane * 128 + h * 32768;
            key_head(pq0, pq1, rs, pb + sw0, pb + sw1);
            wgmma_fence();
            feat_mma(pq0, f2, wlo + 128 - h * 128); feat_mma(pq1, f3, wlo + 128 - h * 128);
            wgmma_commit();
            fence_async_smem();
            __syncwarp();
            mbar_arrive_if(elect, bars + 8 * (B_PHI + h));
            TLP(tid == 0, 6 + 2 * h);
            mbar_wait(bars + 8 * B_T, 0);
            wgmma_wait<0>();
            fence_regs(pq0); fence_regs(pq1); fence_regs(f2); fence_regs(f3);
#pragma unroll
            for (int j = 0; j < 8; j++) { f2[j] = q0[j]; f3[j] = q1[j]; }
            fence_regs(f2); fence_regs(f3);
        }
#pragma unroll
        for (int j = 0; j < 8; j++) { q2[j] = pack_bf16(qa[2 * j], qa[2 * j + 1]); q3[j] = pack_bf16(qb[2 * j], qb[2 * j + 1]); }
        const uint32_t par = lds32(sb + SM_MISC + 8) & 1u;
        const int orow = (hp & 1) * 128 + wg * 64 + w4 * 16 + (lane >> 4);
        const size_t goff = (size_t)(rb * 256 + orow) * D_ + (hp >> 1) * 128 + (lane & 15) * 8;
        uint4 gv[8], xv[8];
#pragma unroll
        for (int i = 0; i < 8; i++) xv[i] = make_uint4(0, 0, 0, 0);
#pragma unroll
        for (int i = 0; i < GSPLIT2; i++) gv[i] = make_uint4(0, 0, 0, 0);
        const uint32_t rowc = sb + ((lane >> 3) & 1) * 16384 + (wg * 64 + w4 * 16 + (lane >> 4)) * 128;
        {
            uint32_t hbump;
            asm volatile("mov.u32 %0, %1;" : "=r"(hbump) : "r"((uint32_t)(hp < 8 && elect)));
            __nv_bfloat16* od = P.o + (size_t)(par * S_ + rb * 256 + row0) * D_ + hp * 32 + (lane & 3) * 8;
#pragma unroll 1
            for (int h = 0; h < 2; h++) {
                uint32_t pa[8], na[8], pb[8], nb[8];
                features(pq0, pq1, rs, pa, na, pb, nb);
                TLP(tid == 0, 16 + h);
                if (h == 0) {
                    wgmma_fence();
                    feat_mma(pq0, q2, wlo + 128); feat_mma(pq1, q3, wlo + 128);
                    wgmma_commit();
                    mbar_wait(bars + 8 * B_X, 0);
#pragma unroll
                    for (int i = 0; i < 8; i++) xv[i] = lds128(rowc + i * 256 + (((lane & 7) ^ ((2 * i + (lane >> 4)) & 7)) * 16));
#pragma unroll
                    for (int i = 0; i < GSPLIT; i++) { gv[i] = xv[i]; gate_item(gv[i], sb, orow + 2 * i); }
                    wgmma_wait<0>();
                    fence_regs(pq0); fence_regs(pq1); fence_regs(q2); fence_regs(q3);
                    TLP(tid == 0, 18);
                } else {
#pragma unroll
                    for (int i = GSPLIT; i < GSPLIT2; i++) { gv[i] = xv[i]; gate_item(gv[i], sb, orow + 2 * i); }
                    TLP(tid == 0, 10);
                }
                {
                    float d0[20], e0[20], d1[20], e1[20];
                    const uint32_t klo = dlo(sb + SM_KVOP - h * 5120, 128);
                    fence_regs(pa); fence_regs(na); fence_regs(pb); fence_regs(nb);
                    mbar_wait(bars + 8 * (B_KV + h), 0);
                    TLP(tid == 0, 32 + h);
                    wgmma_fence();
                    o_mma(d0, e0, pa, na, klo);
                    o_mma(d1, e1, pb, nb, klo);
                    wgmma_commit();
                    wgmma_wait<0>();
                    fence_regs(d0); fence_regs(e0); fence_regs(pa); fence_regs(na);
                    fence_regs(d1); fence_regs(e1); fence_regs(pb); fence_regs(nb);
                    o_store(d0, e0, od + h * 512);
                    asm volatile("{\n.reg .pred q;\nsetp.gt.s32 q, %1, %2;\n@q red.relaxed.gpu.global.add.u32 [%0], %1;\n}" :: "l"(&P.scr->hint[rb * 32 + (hp >> 1) + lane]), "r"(hbump), "r"(h) : "memory");
                    o_store(d1, e1, od + h * 512 + 64 * D_);
                    __syncwarp();
                    mbar_arrive_if(elect, bars + 8 * (B_O + h));
                }
                TLP(tid == 0, 9 + 2 * h);
            }
        }
        float ghr[8], ghm[8];
#pragma unroll
        for (int i = GSPLIT2; i < 8; i++) { ghr[i] = 0.5f * ldsf(sb + SM_RS + (orow + 2 * i) * 4); ghm[i] = -bf_lo(lds32(sb + SM_MD + (orow + 2 * i) * 4)) * ghr[i]; }
        float acc[64];
        {
            const uint32_t alo0 = dlo(sb + wg * 8192, 16), blo0 = dlo(sb, 8192);
            const uint32_t ta0 = sb + (wg * 64 + w4 * 16) * 128 + lane * 16;
            uint32_t cv[2][4];
#pragma unroll
            for (int i = 0; i < 1; i++) {
                mbar_wait(bars + 8 * (B_OF + i), 0);
#pragma unroll
                for (int j = 0; j < 4; j++) cv[i][j] = lds32(ta0 + i * 16384 + j * 512);
            }
#pragma unroll
            for (int i = 0; i < 16; i++) {
                const uint32_t alo = alo0 + o_slot(i) * 1024, blo = blo0 + wo_slot(i) * 1024;
                if (i < 4) {
                    if (__builtin_expect(__any_sync(0xffffffffu, min(min(cv[i & 1][0], cv[i & 1][1]), min(cv[i & 1][2], cv[i & 1][3])) == 0u), 0)) {
                        uint4 v[4];
                        unsigned it = 0;
#pragma unroll 1
                        do {
#pragma unroll
                            for (int j = 0; j < 4; j++) {
                                const int r = j * 4 + (lane >> 3);
                                v[j] = ld_gpu(reinterpret_cast<const uint4*>(P.o + (size_t)(par * S_ + rb * 256 + (orow & ~1) + r) * D_ + i * 64) + ((lane ^ r) & 7));
                            }
                        } while (__any_sync(0xffffffffu, min(min(v[0].x, v[1].x), min(v[2].x, v[3].x)) == 0u) && ++it < (1u << 18));
#pragma unroll
                        for (int j = 0; j < 4; j++) sts128(ta0 + (i & 3) * 16384 + j * 512, v[j].x, v[j].y, v[j].z, v[j].w);
                        fence_async_smem();
                        __syncwarp();
                    }
                } else {
                    mbar_wait(bars + 8 * (B_OF + i), 0);
                }
                if (i == OSTAG && wg == 0) nb_sync(NB_STAG, 256);
                wgmma_fence();
#pragma unroll
                for (int k = 0; k < 4; k++) {
                    if (i == 15 && k == OARR && wg) nb_arrive(NB_STAG, 256);
                    wgmma_ss_n128_tb(acc, desc_from(alo + k * 2, DH128), desc_from(blo + k * 128, DH128), k | i);
                    if (k == OREL) {
                        if (i > 0 && i < 12) {
                            wgmma_commit();
                            wgmma_wait<1>();
                            mbar_arrive_if(elect, bars + 8 * (B_SD + i - 1));
                        }
                    }
                }
                wgmma_commit();
                if (i == 15 && OARR == 4 && wg) nb_arrive(NB_STAG, 256);
                if (i == 0) { TLP(tid == 0, 12); TLG(tid == 0, 51); }
                if (i < 3) {
                    mbar_wait(bars + 8 * (B_OF + i + 1), 0);
#pragma unroll
                    for (int j = 0; j < 4; j++) cv[~i & 1][j] = lds32(ta0 + (i + 1) * 16384 + j * 512);
                }
                static_assert(2 * (8 - GSPLIT2) <= 16 - GST, "");
                if (i >= GST && GSPLIT2 + (i - GST) / 2 < 8) {
                    const int q = GSPLIT2 + (i - GST) / 2;
                    if ((i - GST) & 1) { gv[q].z = gate_pair(xv[q].z, ghr[q], ghm[q]); gv[q].w = gate_pair(xv[q].w, ghr[q], ghm[q]); asm volatile("" : "+r"(gv[q].z), "+r"(gv[q].w) :: "memory"); }
                    else { gv[q].x = gate_pair(xv[q].x, ghr[q], ghm[q]); gv[q].y = gate_pair(xv[q].y, ghr[q], ghm[q]); asm volatile("" : "+r"(gv[q].x), "+r"(gv[q].y) :: "memory"); }
                }
            }
        }
        wgmma_wait<0>();
        fence_regs(acc);
        TLP(tid == 0, 13); TLG(tid == 0, 52);
        {
            const uint32_t stg = sb + (wg * 64 + w4 * 16) * 128;
            const int rr = lane & 7;
#pragma unroll
            for (int c = 0; c < 4; c++) {
                const uint32_t a0 = stg + (c >> 1) * 16384 + rr * 128 + ((((c & 1) * 4 + (lane >> 3)) ^ rr) * 16);
                stsm(a0, pack_bf16(acc[c * 16 + 0], acc[c * 16 + 1]), pack_bf16(acc[c * 16 + 4], acc[c * 16 + 5]),
                     pack_bf16(acc[c * 16 + 8], acc[c * 16 + 9]), pack_bf16(acc[c * 16 + 12], acc[c * 16 + 13]));
                stsm(a0 + 1024, pack_bf16(acc[c * 16 + 2], acc[c * 16 + 3]), pack_bf16(acc[c * 16 + 6], acc[c * 16 + 7]),
                     pack_bf16(acc[c * 16 + 10], acc[c * 16 + 11]), pack_bf16(acc[c * 16 + 14], acc[c * 16 + 15]));
            }
            __syncwarp();
#pragma unroll
            for (int i = 0; i < 8; i++) {
                const uint4 sv = lds128(rowc + i * 256 + (((lane & 7) ^ ((2 * i + (lane >> 4)) & 7)) * 16));
                uint4 o;
                o.x = hadd2(xv[i].x, hmul2(sv.x, gv[i].x)); o.y = hadd2(xv[i].y, hmul2(sv.y, gv[i].y));
                o.z = hadd2(xv[i].z, hmul2(sv.z, gv[i].z)); o.w = hadd2(xv[i].w, hmul2(sv.w, gv[i].w));
                *reinterpret_cast<uint4*>(P.out + goff + (size_t)i * 2 * D_) = o;
            }
            const uint32_t sel = lds32(sb + SM_MISC);
            if ((int)(sel >> 4) == rb * 16 + (orow >> 4)) {
                mbar_wait(bars + 8 * B_Y, 0);
                if ((sel & 1u) == (uint32_t)(lane >> 4)) {
                    const int i = (sel & 15u) >> 1;
                    const uint4 sv = lds128(rowc + i * 256 + (((lane & 7) ^ (sel & 7u)) * 16));
                    const uint4 gq = lds128(sb + SM_Y + (lane & 15) * 16), xq = lds128(sb + SM_Y + 256 + (lane & 15) * 16);
                    *reinterpret_cast<uint4*>(P.out + goff + (size_t)i * 2 * D_) = make_uint4(hadd2(xq.x, hmul2(sv.x, gq.x)), hadd2(xq.y, hmul2(sv.y, gq.y)), hadd2(xq.z, hmul2(sv.z, gq.z)), hadd2(xq.w, hmul2(sv.w, gq.w)));
                }
            }
        }
        TLG(tid == 0, 53);
        if (tid == 0) { TL(14); TL_DUMP(); }
        if (blockIdx.x == 0 && tid == 0) asm volatile("st.relaxed.gpu.global.u32 [%0], %1;" :: "l"(&P.scr->epoch), "r"(lds32(sb + SM_MISC + 8) + 1u) : "memory");
    }
}

typedef CUresult (*PFN_encodeTiled)(CUtensorMap*, CUtensorMapDataType, cuuint32_t, void*, const cuuint64_t*, const cuuint64_t*,
                                    const cuuint32_t*, const cuuint32_t*, CUtensorMapInterleave, CUtensorMapSwizzle,
                                    CUtensorMapL2promotion, CUtensorMapFloatOOBfill);

void make_map(PFN_encodeTiled fn, CUtensorMap* m, const void* ptr, int rank, const cuuint64_t* dims, const cuuint64_t* strides, const cuuint32_t* box, CUtensorMapSwizzle sw) {
    const cuuint32_t es[5] = {1, 1, 1, 1, 1};
    fn(m, CU_TENSOR_MAP_DATA_TYPE_BFLOAT16, rank, const_cast<void*>(ptr), dims, strides, box, es, CU_TENSOR_MAP_INTERLEAVE_NONE,
       sw, CU_TENSOR_MAP_L2_PROMOTION_L2_256B, CU_TENSOR_MAP_FLOAT_OOB_FILL_NONE);
}
void make_2d(PFN_encodeTiled fn, CUtensorMap* m, const void* ptr, uint64_t rows, uint64_t cols, uint32_t box_rows, uint32_t box_cols, CUtensorMapSwizzle sw) {
    const cuuint64_t gd[2] = {cols, rows}, gs[1] = {cols * 2};
    const cuuint32_t bd[2] = {box_cols, box_rows};
    make_map(fn, m, ptr, 2, gd, gs, bd, sw);
}

}

extern "C" void kernel_launch(void* const* d_in, const int* in_sizes, int n_in, void* d_out, int out_size) {
    (void)in_sizes; (void)n_in; (void)out_size;
    static PFN_encodeTiled fn = nullptr;
    static void* o_ptr = nullptr;
    static void* scr_ptr = nullptr;
    static void* tl_ptr = nullptr;
    if (!fn) {
        void* p = nullptr;
        cudaDriverEntryPointQueryResult st;
        cudaGetDriverEntryPoint("cuTensorMapEncodeTiled", &p, cudaEnableDefault, &st);
        fn = (PFN_encodeTiled)p;
        cudaGetSymbolAddress(&o_ptr, g_o);
        cudaGetSymbolAddress(&scr_ptr, g_scr);
        cudaFuncSetAttribute(fused_kernel, cudaFuncAttributeMaxDynamicSharedMemorySize, SM_TOTAL);
    }
    CUtensorMap tmX, tmW, tmPhi, tmWo, tmO, tmX2;
    SideMaps tmS;
    make_2d(fn, &tmX, d_in[0], S_, D_, 256, 64, CU_TENSOR_MAP_SWIZZLE_128B);
    {
        const cuuint64_t gd[3] = {1024, 1024, 3}, gs[2] = {6144, 2048};
        const cuuint32_t bd[3] = {64, 64, 3};
        make_map(fn, &tmW, d_in[1], 3, gd, gs, bd, CU_TENSOR_MAP_SWIZZLE_128B);
    }
    make_2d(fn, &tmS.wc, d_in[1], D_, 3 * D_, 32, 64, CU_TENSOR_MAP_SWIZZLE_NONE);
    make_2d(fn, &tmPhi, d_in[2], 1024, 32, 64, 32, CU_TENSOR_MAP_SWIZZLE_64B);
    make_2d(fn, &tmS.wg, d_in[6], D_, F_, 32, 32, CU_TENSOR_MAP_SWIZZLE_NONE);
    make_2d(fn, &tmS.wu, d_in[7], D_, F_, 32, 32, CU_TENSOR_MAP_SWIZZLE_NONE);
    {
        const cuuint64_t gd[3] = {64, F_, 16}, gs[2] = {2048, 128};
        const cuuint32_t bd[3] = {64, 32, 8};
        make_map(fn, &tmS.wd8, d_in[8], 3, gd, gs, bd, CU_TENSOR_MAP_SWIZZLE_128B);
    }
    {
        const cuuint64_t gd[4] = {64, 64, 16, 16}, gs[3] = {2048, 64 * 2048, 128};
        const cuuint32_t bd[4] = {64, 32, 2, 2};
        make_map(fn, &tmWo, d_in[3], 4, gd, gs, bd, CU_TENSOR_MAP_SWIZZLE_128B);
    }
    make_2d(fn, &tmO, o_ptr, 2 * S_, D_, 128, 64, CU_TENSOR_MAP_SWIZZLE_128B);
    make_2d(fn, &tmX2, d_in[0], S_, D_, 128, 64, CU_TENSOR_MAP_SWIZZLE_128B);
    Params P;
    P.x = (const __nv_bfloat16*)d_in[0];
    P.wr = (const __nv_bfloat16*)d_in[5];
    P.wqkv = (const __nv_bfloat16*)d_in[1];
    P.wg = (const __nv_bfloat16*)d_in[6];
    P.wu = (const __nv_bfloat16*)d_in[7];
    P.wd = (const __nv_bfloat16*)d_in[8];
    P.wo = (const __nv_bfloat16*)d_in[3];
    P.out = (__nv_bfloat16*)d_out;
    P.o = (__nv_bfloat16*)o_ptr;
    P.scr = (Scratch*)scr_ptr;
    P.tl = (unsigned long long*)tl_ptr;
    cudaLaunchConfig_t cfg = {};
    cfg.gridDim = dim3(NCTA); cfg.blockDim = dim3(NTHREADS); cfg.dynamicSmemBytes = SM_TOTAL; cfg.stream = cudaStreamPerThread;
    cudaLaunchAttribute at[1];
    at[0].id = cudaLaunchAttributeCooperative; at[0].val.cooperative = 1;
    cfg.attrs = at; cfg.numAttrs = 1;
    cudaLaunchKernelEx(&cfg, fused_kernel, P, tmX, tmW, tmX2, tmS, tmPhi, tmWo, tmO);
}
```

```cpp
#include <cuda_runtime.h>
#include <cuda_bf16.h>
#include <cuda.h>
#include <stdint.h>

namespace {

constexpr int S_ = 2048, D_ = 1024, F_ = 3584;
constexpr int NCTA = 128, NTHREADS = 384;
#define POLL_NS 100
#define OREL 2
#define OSTAG 12
#define OARR 3
#define NC0 3
#define NC2 4
#define NG0 12
#define NG1 12
#define GSPLIT 1
#define GSPLIT2 2
#define GST 3
#define SARR 3
#define JWO 12

constexpr int STAGE = 57344;
constexpr int SM_PHI = 0;
constexpr int SM_V = 131072;
constexpr int SM_AX = 172032;
constexpr int SM_BX = 176128;
constexpr int SM_SP = 172032;
constexpr int SM_FB = 180224;
constexpr int SM_XS = 221184;
constexpr int SM_KVOP = 172032;
constexpr int SM_MD = 223232;
constexpr int SM_RS = 224256;
constexpr int SM_Y = 225280;
constexpr int SM_GU = 225536;
constexpr int SM_MISC = 226688;
constexpr int SM_H = 179200;
constexpr int SM_BARS = 226816;
constexpr int SM_WPHI = 227840;
constexpr int SM_TOTAL = 232448;

constexpr int B_FULL = 0, B_EMPTY = 3, B_OF = 6, B_SD = 22, B_O = 33, B_PHI = 35, B_T = 37, B_WPHI = 38, B_Y = 39, B_KV = 40, B_LN = 42, B_S1 = 43, B_FF = 44, B_X = 54, B_C1 = 55, B_DN = 56, B_XS = 58, B_COUNT = 59, B_XR = 59;
constexpr int NB_KV = 1, NB_FFN = 2, NB_AUX = 3, NB_DN = 4, NB_STAG = 5;
__device__ __forceinline__ int o_slot(int i) { const int r = i % 5; return r == 4 ? 10 : r; }
__device__ __forceinline__ int wo_slot(int i) { const int r = i % 7; return r == 6 ? 11 : 4 + r; }

struct __align__(128) Acc {
    float4 cs[48 * 8 * 3];
    float4 y[4 * 4 * 3 * 32];
    unsigned pad[1024];
};
constexpr int ACC_VEC_PER_CTA = (int)(sizeof(Acc) / 16 / NCTA);
static_assert(sizeof(Acc) == ACC_VEC_PER_CTA * 16 * NCTA && ACC_VEC_PER_CTA <= 256, "");
struct __align__(128) Scratch {
    Acc acc[2];
    uint4 kv[32 * 4 * 3 * 32];
    unsigned hint[8 * 32];
    unsigned cnt_o[8 * 128];
    uint2 rows[S_];
    uint4 best[NCTA];
    unsigned epoch;
};
__device__ Scratch g_scr;
__device__ __align__(1024) __nv_bfloat16 g_o[2 * S_ * D_];

#define TL(e) do {} while (0)
#define TLP(c, e) do {} while (0)
#define TLG(c, e) do {} while (0)
#define TL_DUMP() do {} while (0)

struct SideMaps { CUtensorMap wc, wg, wu, wd8; };
struct Params {
    const __nv_bfloat16* x;
    const __nv_bfloat16* wr;
    const __nv_bfloat16* wqkv;
    const __nv_bfloat16* wg;
    const __nv_bfloat16* wu;
    const __nv_bfloat16* wd;
    const __nv_bfloat16* wo;
    __nv_bfloat16* out;
    __nv_bfloat16* o;
    Scratch* scr;
    unsigned long long* tl;
};

__device__ __forceinline__ bool elect_one() {
    uint32_t p; asm volatile("{\n.reg .pred q;\nelect.sync _|q, 0xffffffff;\nselp.u32 %0, 1, 0, q;\n}" : "=r"(p)); return p;
}
__device__ __forceinline__ uint32_t smem_u32(const void* p) { return (uint32_t)__cvta_generic_to_shared(p); }
__device__ __forceinline__ void mbar_init(uint32_t bar, uint32_t cnt) { asm volatile("mbarrier.init.shared::cta.b64 [%0], %1;" :: "r"(bar), "r"(cnt) : "memory"); }
__device__ __forceinline__ void mbar_expect_tx(uint32_t bar, uint32_t bytes) { asm volatile("mbarrier.arrive.expect_tx.shared::cta.b64 _, [%0], %1;" :: "r"(bar), "r"(bytes) : "memory"); }
__device__ __forceinline__ void mbar_arrive_if(bool p, uint32_t bar) {
    asm volatile("{\n.reg .pred q;\nsetp.ne.b32 q, %1, 0;\n@q mbarrier.arrive.shared::cta.b64 _, [%0];\n}" :: "r"(bar), "r"((int)p) : "memory");
}
__device__ __forceinline__ void mbar_wait(uint32_t bar, uint32_t parity) {
    asm volatile("{\n.reg .pred p;\n.reg .u32 n;\nmov.u32 n, 0;\n"
                 "WAIT_LOOP:\nmbarrier.try_wait.parity.shared::cta.b64 p, [%0], %1;\n@p bra WAIT_DONE;\n"
                 "add.u32 n, n, 1;\nsetp.lt.u32 p, n, 0x40000;\n@p bra WAIT_LOOP;\nWAIT_DONE:\n}" :: "r"(bar), "r"(parity) : "memory");
}
__device__ __forceinline__ bool mbar_test(uint32_t bar, uint32_t parity) {
    uint32_t ok;
    asm volatile("{\n.reg .pred p;\nmbarrier.test_wait.parity.shared::cta.b64 p, [%1], %2;\nselp.u32 %0, 1, 0, p;\n}" : "=r"(ok) : "r"(bar), "r"(parity) : "memory");
    return __all_sync(0xffffffffu, ok);
}
__device__ __forceinline__ void tma_2d(uint32_t dst, const CUtensorMap* tm, uint32_t bar, int c0, int c1) {
    asm volatile("cp.async.bulk.tensor.2d.shared::cluster.global.mbarrier::complete_tx::bytes [%0], [%1, {%3, %4}], [%2];"
        :: "r"(dst), "l"(tm), "r"(bar), "r"(c0), "r"(c1) : "memory");
}
__device__ __forceinline__ void tma_3d(uint32_t dst, const CUtensorMap* tm, uint32_t bar, int c0, int c1, int c2) {
    asm volatile("cp.async.bulk.tensor.3d.shared::cluster.global.mbarrier::complete_tx::bytes [%0], [%1, {%3, %4, %5}], [%2];"
        :: "r"(dst), "l"(tm), "r"(bar), "r"(c0), "r"(c1), "r"(c2) : "memory");
}
__device__ __forceinline__ void tma_4d(uint32_t dst, const CUtensorMap* tm, uint32_t bar, int c0, int c1, int c2, int c3) {
    asm volatile("cp.async.bulk.tensor.4d.shared::cluster.global.mbarrier::complete_tx::bytes [%0], [%1, {%3, %4, %5, %6}], [%2];"
        :: "r"(dst), "l"(tm), "r"(bar), "r"(c0), "r"(c1), "r"(c2), "r"(c3) : "memory");
}
__device__ __forceinline__ void prefetch_l2(const void* p, uint32_t bytes) { asm volatile("cp.async.bulk.prefetch.L2.global [%0], %1;" :: "l"(p), "r"(bytes) : "memory"); }
__device__ __forceinline__ void wgmma_fence() { asm volatile("wgmma.fence.sync.aligned;" ::: "memory"); }
__device__ __forceinline__ void wgmma_commit() { asm volatile("wgmma.commit_group.sync.aligned;" ::: "memory"); }
template <int N> __device__ __forceinline__ void wgmma_wait() { asm volatile("wgmma.wait_group.sync.aligned %0;" :: "n"(N) : "memory"); }
template <int N> __device__ __forceinline__ void fence_regs(float (&a)[N]) {
#pragma unroll
    for (int i = 0; i < N; i++) asm volatile("" : "+f"(a[i]) :: "memory");
}
template <int N> __device__ __forceinline__ void fence_regs(uint32_t (&a)[N]) {
#pragma unroll
    for (int i = 0; i < N; i++) asm volatile("" : "+r"(a[i]) :: "memory");
}
__device__ __forceinline__ uint64_t desc_from(uint32_t lo, uint32_t hi) { uint64_t d; asm("mov.b64 %0, {%1, %2};" : "=l"(d) : "r"(lo), "r"(hi)); return d; }
__device__ __forceinline__ uint32_t dlo(uint32_t addr, uint32_t lbo) { return ((addr & 0x3FFFF) >> 4) | ((lbo >> 4) << 16); }
__device__ __forceinline__ void nb_sync(int id, int cnt) { asm volatile("bar.sync %0, %1;" :: "r"(id), "r"(cnt) : "memory"); }
__device__ __forceinline__ void nb_arrive(int id, int cnt) { asm volatile("bar.arrive %0, %1;" :: "r"(id), "r"(cnt) : "memory"); }
__device__ __forceinline__ void fence_async_smem() { asm volatile("fence.proxy.async.shared::cta;" ::: "memory"); }
__device__ __forceinline__ void red_v4(float4* p, float a, float b, float c, float d) {
    asm volatile("red.relaxed.gpu.global.add.v4.f32 [%0], {%1, %2, %3, %4};" :: "l"(p), "f"(a), "f"(b), "f"(c), "f"(d) : "memory");
}
__device__ __forceinline__ void red_h8(uint4* p, uint32_t a, uint32_t b, uint32_t c, uint32_t d) {
    asm volatile("red.relaxed.gpu.global.add.noftz.v4.f16x2 [%0], {%1, %2, %3, %4};" :: "l"(p), "r"(a), "r"(b), "r"(c), "r"(d) : "memory");
}
__device__ __forceinline__ float4 ld_gpu(const float4* p) {
    float4 v; asm volatile("ld.relaxed.gpu.global.v4.f32 {%0, %1, %2, %3}, [%4];" : "=f"(v.x), "=f"(v.y), "=f"(v.z), "=f"(v.w) : "l"(p) : "memory"); return v;
}
__device__ __forceinline__ uint4 ld_gpu(const uint4* p) {
    uint4 v; asm volatile("ld.relaxed.gpu.global.v4.u32 {%0, %1, %2, %3}, [%4];" : "=r"(v.x), "=r"(v.y), "=r"(v.z), "=r"(v.w) : "l"(p) : "memory"); return v;
}
__device__ __forceinline__ void poll_counter(const unsigned* p, unsigned target) {
    unsigned it = 0, v;
#pragma unroll 1
    do {
        asm volatile("ld.acquire.gpu.global.u32 %0, [%1];" : "=r"(v) : "l"(p) : "memory");
    } while (v < target && ++it < (1u << 20));
}
__device__ __forceinline__ uint32_t pack_bf16(float lo, float hi) { uint32_t r; asm("cvt.rn.bf16x2.f32 %0, %1, %2;" : "=r"(r) : "f"(hi), "f"(lo)); return r; }
__device__ __forceinline__ uint32_t pack_f16(float lo, float hi) { uint32_t r; asm("cvt.rn.f16x2.f32 %0, %1, %2;" : "=r"(r) : "f"(hi), "f"(lo)); return r; }
__device__ __forceinline__ float2 unpack_f16(uint32_t v) { float2 r; asm("{\n.reg .f16 l, h;\nmov.b32 {l, h}, %2;\ncvt.f32.f16 %0, l;\ncvt.f32.f16 %1, h;\n}" : "=f"(r.x), "=f"(r.y) : "r"(v)); return r; }
__device__ __forceinline__ float bf_lo(uint32_t v) { return __uint_as_float(v << 16); }
__device__ __forceinline__ float bf_hi(uint32_t v) { return __uint_as_float(v & 0xFFFF0000u); }
__device__ __forceinline__ float round_bf16(float v) { return bf_lo(pack_bf16(v, 0.f)); }
__device__ __forceinline__ float ex2(float v) { float r; asm("ex2.approx.ftz.f32 %0, %1;" : "=f"(r) : "f"(v)); return r; }
__device__ __forceinline__ float rcp(float v) { float r; asm("rcp.approx.ftz.f32 %0, %1;" : "=f"(r) : "f"(v)); return r; }
__device__ __forceinline__ float sqrt_a(float v) { float r; asm("sqrt.approx.f32 %0, %1;" : "=f"(r) : "f"(v)); return r; }
__device__ __forceinline__ void stsm(uint32_t addr, uint32_t r0, uint32_t r1, uint32_t r2, uint32_t r3) {
    asm volatile("stmatrix.sync.aligned.m8n8.x4.shared.b16 [%0], {%1, %2, %3, %4};" :: "r"(addr), "r"(r0), "r"(r1), "r"(r2), "r"(r3) : "memory");
}
__device__ __forceinline__ void stsm_t(uint32_t addr, uint32_t r0, uint32_t r1, uint32_t r2, uint32_t r3) {
    asm volatile("stmatrix.sync.aligned.m8n8.x4.trans.shared.b16 [%0], {%1, %2, %3, %4};" :: "r"(addr), "r"(r0), "r"(r1), "r"(r2), "r"(r3) : "memory");
}
__device__ __forceinline__ uint4 lds128(uint32_t addr) {
    uint4 v; asm volatile("ld.shared.v4.u32 {%0, %1, %2, %3}, [%4];" : "=r"(v.x), "=r"(v.y), "=r"(v.z), "=r"(v.w) : "r"(addr) : "memory"); return v;
}
__device__ __forceinline__ void sts128(uint32_t addr, uint32_t a, uint32_t b, uint32_t c, uint32_t d) {
    asm volatile("st.shared.v4.u32 [%0], {%1, %2, %3, %4};" :: "r"(addr), "r"(a), "r"(b), "r"(c), "r"(d) : "memory");
}
__device__ __forceinline__ void sts64(uint32_t addr, uint32_t a, uint32_t b) { asm volatile("st.shared.v2.u32 [%0], {%1, %2};" :: "r"(addr), "r"(a), "r"(b) : "memory"); }
__device__ __forceinline__ uint32_t lds32(uint32_t addr) { uint32_t v; asm volatile("ld.shared.u32 %0, [%1];" : "=r"(v) : "r"(addr) : "memory"); return v; }
__device__ __forceinline__ float ldsf(uint32_t addr) { return __uint_as_float(lds32(addr)); }
__device__ __forceinline__ void sts32(uint32_t addr, uint32_t v) { asm volatile("st.shared.u32 [%0], %1;" :: "r"(addr), "r"(v) : "memory"); }
__device__ __forceinline__ uint32_t hmul2(uint32_t a, uint32_t b) { uint32_t r; asm("mul.rn.bf16x2 %0, %1, %2;" : "=r"(r) : "r"(a), "r"(b)); return r; }
__device__ __forceinline__ uint32_t hadd2(uint32_t a, uint32_t b) { uint32_t r; asm("add.rn.bf16x2 %0, %1, %2;" : "=r"(r) : "r"(a), "r"(b)); return r; }
__device__ __forceinline__ uint32_t hsub2(uint32_t a, uint32_t b) { uint32_t r; asm("sub.rn.bf16x2 %0, %1, %2;" : "=r"(r) : "r"(a), "r"(b)); return r; }

__device__ __forceinline__ void wgmma_ss_n192_tb(float (&d)[96], uint64_t da, uint64_t db, int scale_d) {
    asm volatile(
        "{\n.reg .pred p;\nsetp.ne.b32 p, %98, 0;\n"
        "wgmma.mma_async.sync.aligned.m64n192k16.f32.bf16.bf16 "
        "{%0, %1, %2, %3, %4, %5, %6, %7, %8, %9, %10, %11, %12, %13, %14, %15, %16, %17, %18, %19, %20, %21, %22, %23, %24, %25, %26, %27, %28, %29, %30, %31, %32, %33, %34, %35, %36, %37, %38, %39, %40, %41, %42, %43, %44, %45, %46, %47, %48, %49, %50, %51, %52, %53, %54, %55, %56, %57, %58, %59, %60, %61, %62, %63, %64, %65, %66, %67, %68, %69, %70, %71, %72, %73, %74, %75, %76, %77, %78, %79, %80, %81, %82, %83, %84, %85, %86, %87, %88, %89, %90, %91, %92, %93, %94, %95}, %96, %97, p, 1, 1, 0, 1;\n}\n"
        : "+f"(d[0]), "+f"(d[1]), "+f"(d[2]), "+f"(d[3]), "+f"(d[4]), "+f"(d[5]), "+f"(d[6]), "+f"(d[7]), "+f"(d[8]), "+f"(d[9]), "+f"(d[10]), "+f"(d[11]), "+f"(d[12]), "+f"(d[13]), "+f"(d[14]), "+f"(d[15]), "+f"(d[16]), "+f"(d[17]), "+f"(d[18]), "+f"(d[19]), "+f"(d[20]), "+f"(d[21]), "+f"(d[22]), "+f"(d[23]), "+f"(d[24]), "+f"(d[25]), "+f"(d[26]), "+f"(d[27]), "+f"(d[28]), "+f"(d[29]), "+f"(d[30]), "+f"(d[31]), "+f"(d[32]), "+f"(d[33]), "+f"(d[34]), "+f"(d[35]), "+f"(d[36]), "+f"(d[37]), "+f"(d[38]), "+f"(d[39]), "+f"(d[40]), "+f"(d[41]), "+f"(d[42]), "+f"(d[43]), "+f"(d[44]), "+f"(d[45]), "+f"(d[46]), "+f"(d[47]), "+f"(d[48]), "+f"(d[49]), "+f"(d[50]), "+f"(d[51]), "+f"(d[52]), "+f"(d[53]), "+f"(d[54]), "+f"(d[55]), "+f"(d[56]), "+f"(d[57]), "+f"(d[58]), "+f"(d[59]), "+f"(d[60]), "+f"(d[61]), "+f"(d[62]), "+f"(d[63]), "+f"(d[64]), "+f"(d[65]), "+f"(d[66]), "+f"(d[67]), "+f"(d[68]), "+f"(d[69]), "+f"(d[70]), "+f"(d[71]), "+f"(d[72]), "+f"(d[73]), "+f"(d[74]), "+f"(d[75]), "+f"(d[76]), "+f"(d[77]), "+f"(d[78]), "+f"(d[79]), "+f"(d[80]), "+f"(d[81]), "+f"(d[82]), "+f"(d[83]), "+f"(d[84]), "+f"(d[85]), "+f"(d[86]), "+f"(d[87]), "+f"(d[88]), "+f"(d[89]), "+f"(d[90]), "+f"(d[91]), "+f"(d[92]), "+f"(d[93]), "+f"(d[94]), "+f"(d[95])
        : "l"(da), "l"(db), "r"(scale_d));
}
__device__ __forceinline__ void wgmma_ss_n128_tb(float (&d)[64], uint64_t da, uint64_t db, int scale_d) {
    asm volatile(
        "{\n.reg .pred p;\nsetp.ne.b32 p, %66, 0;\n"
        "wgmma.mma_async.sync.aligned.m64n128k16.f32.bf16.bf16 "
        "{%0, %1, %2, %3, %4, %5, %6, %7, %8, %9, %10, %11, %12, %13, %14, %15, %16, %17, %18, %19, %20, %21, %22, %23, %24, %25, %26, %27, %28, %29, %30, %31, %32, %33, %34, %35, %36, %37, %38, %39, %40, %41, %42, %43, %44, %45, %46, %47, %48, %49, %50, %51, %52, %53, %54, %55, %56, %57, %58, %59, %60, %61, %62, %63}, %64, %65, p, 1, 1, 0, 1;\n}\n"
        : "+f"(d[0]), "+f"(d[1]), "+f"(d[2]), "+f"(d[3]), "+f"(d[4]), "+f"(d[5]), "+f"(d[6]), "+f"(d[7]), "+f"(d[8]), "+f"(d[9]), "+f"(d[10]), "+f"(d[11]), "+f"(d[12]), "+f"(d[13]), "+f"(d[14]), "+f"(d[15]), "+f"(d[16]), "+f"(d[17]), "+f"(d[18]), "+f"(d[19]), "+f"(d[20]), "+f"(d[21]), "+f"(d[22]), "+f"(d[23]), "+f"(d[24]), "+f"(d[25]), "+f"(d[26]), "+f"(d[27]), "+f"(d[28]), "+f"(d[29]), "+f"(d[30]), "+f"(d[31]), "+f"(d[32]), "+f"(d[33]), "+f"(d[34]), "+f"(d[35]), "+f"(d[36]), "+f"(d[37]), "+f"(d[38]), "+f"(d[39]), "+f"(d[40]), "+f"(d[41]), "+f"(d[42]), "+f"(d[43]), "+f"(d[44]), "+f"(d[45]), "+f"(d[46]), "+f"(d[47]), "+f"(d[48]), "+f"(d[49]), "+f"(d[50]), "+f"(d[51]), "+f"(d[52]), "+f"(d[53]), "+f"(d[54]), "+f"(d[55]), "+f"(d[56]), "+f"(d[57]), "+f"(d[58]), "+f"(d[59]), "+f"(d[60]), "+f"(d[61]), "+f"(d[62]), "+f"(d[63])
        : "l"(da), "l"(db), "r"(scale_d));
}
__device__ __forceinline__ void wgmma_ss_n40(float (&d)[20], uint64_t da, uint64_t db, int scale_d) {
    asm volatile(
        "{\n.reg .pred p;\nsetp.ne.b32 p, %22, 0;\n"
        "wgmma.mma_async.sync.aligned.m64n40k16.f32.bf16.bf16 "
        "{%0, %1, %2, %3, %4, %5, %6, %7, %8, %9, %10, %11, %12, %13, %14, %15, %16, %17, %18, %19}, %20, %21, p, 1, 1, 0, 0;\n}\n"
        : "+f"(d[0]), "+f"(d[1]), "+f"(d[2]), "+f"(d[3]), "+f"(d[4]), "+f"(d[5]), "+f"(d[6]), "+f"(d[7]), "+f"(d[8]), "+f"(d[9]), "+f"(d[10]), "+f"(d[11]), "+f"(d[12]), "+f"(d[13]), "+f"(d[14]), "+f"(d[15]), "+f"(d[16]), "+f"(d[17]), "+f"(d[18]), "+f"(d[19])
        : "l"(da), "l"(db), "r"(scale_d));
}
__device__ __forceinline__ void wgmma_ss_n8_ta(float (&d)[4], uint64_t da, uint64_t db, int scale_d) {
    asm volatile(
        "{\n.reg .pred p;\nsetp.ne.b32 p, %6, 0;\n"
        "wgmma.mma_async.sync.aligned.m64n8k16.f32.bf16.bf16 "
        "{%0, %1, %2, %3}, %4, %5, p, 1, 1, 1, 0;\n}\n"
        : "+f"(d[0]), "+f"(d[1]), "+f"(d[2]), "+f"(d[3])
        : "l"(da), "l"(db), "r"(scale_d));
}
__device__ __forceinline__ void wgmma_rs_n32_tb(float (&d)[16], uint32_t a0, uint32_t a1, uint32_t a2, uint32_t a3, uint64_t db, int scale_d) {
    asm volatile(
        "{\n.reg .pred p;\nsetp.ne.b32 p, %21, 0;\n"
        "wgmma.mma_async.sync.aligned.m64n32k16.f32.bf16.bf16 "
        "{%0, %1, %2, %3, %4, %5, %6, %7, %8, %9, %10, %11, %12, %13, %14, %15}, {%16, %17, %18, %19}, %20, p, 1, 1, 1;\n}\n"
        : "+f"(d[0]), "+f"(d[1]), "+f"(d[2]), "+f"(d[3]), "+f"(d[4]), "+f"(d[5]), "+f"(d[6]), "+f"(d[7]), "+f"(d[8]), "+f"(d[9]), "+f"(d[10]), "+f"(d[11]), "+f"(d[12]), "+f"(d[13]), "+f"(d[14]), "+f"(d[15])
        : "r"(a0), "r"(a1), "r"(a2), "r"(a3), "l"(db), "r"(scale_d));
}
__device__ __forceinline__ void wgmma_rs_n40_tb(float (&d)[20], uint32_t a0, uint32_t a1, uint32_t a2, uint32_t a3, uint64_t db, int scale_d) {
    asm volatile(
        "{\n.reg .pred p;\nsetp.ne.b32 p, %25, 0;\n"
        "wgmma.mma_async.sync.aligned.m64n40k16.f32.bf16.bf16 "
        "{%0, %1, %2, %3, %4, %5, %6, %7, %8, %9, %10, %11, %12, %13, %14, %15, %16, %17, %18, %19}, {%20, %21, %22, %23}, %24, p, 1, 1, 1;\n}\n"
        : "+f"(d[0]), "+f"(d[1]), "+f"(d[2]), "+f"(d[3]), "+f"(d[4]), "+f"(d[5]), "+f"(d[6]), "+f"(d[7]), "+f"(d[8]), "+f"(d[9]), "+f"(d[10]), "+f"(d[11]), "+f"(d[12]), "+f"(d[13]), "+f"(d[14]), "+f"(d[15]), "+f"(d[16]), "+f"(d[17]), "+f"(d[18]), "+f"(d[19])
        : "r"(a0), "r"(a1), "r"(a2), "r"(a3), "l"(db), "r"(scale_d));
}

constexpr float LOG2E = 1.4426950408889634f;
constexpr uint32_t DH128 = (1024u >> 4) | (1u << 30);

__device__ __forceinline__ float silu_f(float v) { return v * rcp(1.0f + ex2(-v * LOG2E)); }
__device__ __forceinline__ float silu_t(float v) { const float h = 0.5f * v; float th; asm("tanh.approx.f32 %0, %1;" : "=f"(th) : "f"(h)); return fmaf(h, th, h); }
__device__ __forceinline__ uint32_t ln_pair(uint32_t xv, uint32_t m2, float rs) { const uint32_t a = hsub2(xv, m2); return pack_bf16(bf_lo(a) * rs, bf_hi(a) * rs); }
__device__ __forceinline__ uint32_t silu_pair(uint32_t v) { return pack_bf16(silu_t(bf_lo(v)), silu_t(bf_hi(v))); }
__device__ __forceinline__ uint32_t gate_pair(uint32_t v, float hr, float hm) {
    const float a = fmaf(bf_lo(v), hr, hm), b = fmaf(bf_hi(v), hr, hm);
    float ta, tb;
    asm("tanh.approx.f32 %0, %1;" : "=f"(ta) : "f"(a)); asm("tanh.approx.f32 %0, %1;" : "=f"(tb) : "f"(b));
    return pack_bf16(fmaf(a, ta, a), fmaf(b, tb, b));
}
__device__ __forceinline__ void gate_item(uint4& v, uint32_t sb, int row) {
    const float hr = 0.5f * ldsf(sb + SM_RS + row * 4), hm = -bf_lo(lds32(sb + SM_MD + row * 4)) * hr;
    v.x = gate_pair(v.x, hr, hm); v.y = gate_pair(v.y, hr, hm); v.z = gate_pair(v.z, hr, hm); v.w = gate_pair(v.w, hr, hm);
    asm volatile("" : "+r"(v.x), "+r"(v.y), "+r"(v.z), "+r"(v.w) :: "memory");
}
__device__ __forceinline__ uint32_t hfma2(uint32_t a, uint32_t b, uint32_t c) { uint32_t r; asm("fma.rn.bf16x2 %0, %1, %2, %3;" : "=r"(r) : "r"(a), "r"(b), "r"(c)); return r; }
__device__ __forceinline__ uint32_t dup_lo(uint32_t v) { uint32_t r; asm("{\n.reg .b16 l, h;\nmov.b32 {l, h}, %1;\nmov.b32 %0, {l, l};\n}" : "=r"(r) : "r"(v)); return r; }
__device__ __forceinline__ uint32_t dup_hi(uint32_t v) { uint32_t r; asm("{\n.reg .b16 l, h;\nmov.b32 {l, h}, %1;\nmov.b32 %0, {h, h};\n}" : "=r"(r) : "r"(v)); return r; }
__device__ __forceinline__ uint32_t hmax2(uint32_t a, uint32_t b) { uint32_t r; asm("max.NaN.bf16x2 %0, %1, %2;" : "=r"(r) : "r"(a), "r"(b)); return r; }
template <bool SQ> __device__ __forceinline__ void colsum8(float (&a)[8], float& sq, const uint4 (&v)[8]) {
    uint32_t q = 0;
#pragma unroll
    for (int i = 0; i < 8; i++) {
        a[0] += bf_lo(v[i].x); a[1] += bf_hi(v[i].x); a[2] += bf_lo(v[i].y); a[3] += bf_hi(v[i].y);
        a[4] += bf_lo(v[i].z); a[5] += bf_hi(v[i].z); a[6] += bf_lo(v[i].w); a[7] += bf_hi(v[i].w);
        if (SQ) q = hfma2(v[i].x, v[i].x, hfma2(v[i].y, v[i].y, hfma2(v[i].z, v[i].z, hfma2(v[i].w, v[i].w, q))));
    }
    if (SQ) sq += bf_lo(q) + bf_hi(q);
}
__device__ __forceinline__ void hfma8(uint4& h, uint32_t w, const uint4& v) { h.x = hfma2(v.x, w, h.x); h.y = hfma2(v.y, w, h.y); h.z = hfma2(v.z, w, h.z); h.w = hfma2(v.w, w, h.w); }
template <int ST, class F>
__device__ __forceinline__ void gemv_run(float (&a)[8], int cnt, int b, uint32_t ph, uint32_t lo, uint32_t wa, uint32_t ws, uint32_t bar0, uint32_t pin, F done) {
    uint32_t rdy = 0;
#pragma unroll 1
    for (int m = 0; m < cnt; m++) {
        if (!rdy) mbar_wait(bar0 + b * 8, ph);
        uint4 A[8];
        const uint4 w = lds128(wa);
#pragma unroll
        for (int i = 0; i < 8; i++) A[i] = lds128(lo + b * 4096 + i * ST);
        const int bc = b;
        if (++b == 3) { b = 0; ph ^= 1; }
        asm volatile("{\n.reg .pred p;\nmbarrier.test_wait.parity.shared::cta.b64 p, [%1], %2;\nselp.u32 %0, 1, 0, p;\n}" : "=r"(rdy) : "r"(bar0 + b * 8), "r"(ph) : "memory");
        sts32(pin, 0u);
        wa += ws;
        uint4 h = make_uint4(0, 0, 0, 0);
        hfma8(h, dup_lo(w.x), A[0]); hfma8(h, dup_hi(w.x), A[1]); hfma8(h, dup_lo(w.y), A[2]); hfma8(h, dup_hi(w.y), A[3]);
        hfma8(h, dup_lo(w.z), A[4]); hfma8(h, dup_hi(w.z), A[5]); hfma8(h, dup_lo(w.w), A[6]); hfma8(h, dup_hi(w.w), A[7]);
        a[0] += bf_lo(h.x); a[1] += bf_hi(h.x); a[2] += bf_lo(h.y); a[3] += bf_hi(h.y);
        a[4] += bf_lo(h.z); a[5] += bf_hi(h.z); a[6] += bf_lo(h.w); a[7] += bf_hi(h.w);
        fence_regs(a);
        done(m, bc);
    }
}
template <int OFF> __device__ __forceinline__ void pack_head(const float (&acc)[96], uint32_t (&f)[8]) {
#pragma unroll
    for (int i = 0; i < 8; i++) f[i] = pack_bf16(acc[OFF + 2 * i], acc[OFF + 2 * i + 1]);
}
__device__ __forceinline__ void feat_mma(float (&p)[16], const uint32_t (&f)[8], uint32_t wlo) {
    constexpr uint32_t DH = (512u >> 4) | (2u << 30);
    wgmma_rs_n32_tb(p, f[0], f[1], f[2], f[3], desc_from(wlo, DH), 0);
    wgmma_rs_n32_tb(p, f[4], f[5], f[6], f[7], desc_from(wlo + 64, DH), 1);
}
template <int S> __device__ __forceinline__ void row_ext(const float (&p)[16], float& a, float& b) {
    auto op = [](float x, float y) { return S > 0 ? fmaxf(x, y) : fminf(x, y); };
    a = op(op(op(p[0], p[1]), op(p[4], p[5])), op(op(p[8], p[9]), op(p[12], p[13])));
    b = op(op(op(p[2], p[3]), op(p[6], p[7])), op(op(p[10], p[11]), op(p[14], p[15])));
#pragma unroll
    for (int o = 1; o <= 2; o <<= 1) { a = op(a, __shfl_xor_sync(0xffffffffu, a, o)); b = op(b, __shfl_xor_sync(0xffffffffu, b, o)); }
}
__device__ __forceinline__ void dual_exp(const float (&p)[16], float scA, float scB, uint32_t (&pos)[8], uint32_t (&neg)[8], uint32_t& chk) {
#pragma unroll
    for (int j = 0; j < 8; j += 2) {
        const float a0 = ex2(p[2 * j] * scA), a1 = ex2(p[2 * j + 1] * scA);
        const float b0 = ex2(p[2 * j + 2] * scB), b1 = ex2(p[2 * j + 3] * scB);
        const float pa = a0 * a1, pb = b0 * b1, R = rcp(pa * pb);
        const uint32_t r = pack_bf16(R * pb, R * pa);
        pos[j] = pack_bf16(a0, a1); pos[j + 1] = pack_bf16(b0, b1);
        neg[j] = hmul2(pos[j], dup_lo(r)); neg[j + 1] = hmul2(pos[j + 1], dup_hi(r));
        chk = hadd2(chk, hadd2(hadd2(pos[j], neg[j]), hadd2(pos[j + 1], neg[j + 1])));
    }
}
template <int S> __device__ __forceinline__ void exact_exp(const float (&p)[16], float scA, float scB, uint32_t (&o)[8]) {
    float mA, mB;
    row_ext<S>(p, mA, mB);
#pragma unroll
    for (int j = 0; j < 8; j++) {
        const float sc = S * ((j & 1) ? scB : scA), m = (j & 1) ? mB : mA;
        const float u = ex2((p[2 * j] - m) * sc), v = ex2((p[2 * j + 1] - m) * sc);
        o[j] = S > 0 ? pack_bf16(u, v) : pack_bf16(v, u);
    }
}
__device__ __forceinline__ void features(const float (&p0)[16], const float (&p1)[16], const float (&rs)[4],
                                         uint32_t (&pa)[8], uint32_t (&na)[8], uint32_t (&pb)[8], uint32_t (&nb)[8]) {
    uint32_t chk = 0;
    dual_exp(p0, rs[0] * LOG2E, rs[1] * LOG2E, pa, na, chk);
    dual_exp(p1, rs[2] * LOG2E, rs[3] * LOG2E, pb, nb, chk);
    if (__builtin_expect(!__all_sync(0xffffffffu, bf_lo(chk) + bf_hi(chk) < 1.0e9f), 0)) {
        exact_exp<1>(p0, rs[0] * LOG2E, rs[1] * LOG2E, pa); exact_exp<-1>(p0, rs[0] * LOG2E, rs[1] * LOG2E, na);
        exact_exp<1>(p1, rs[2] * LOG2E, rs[3] * LOG2E, pb); exact_exp<-1>(p1, rs[2] * LOG2E, rs[3] * LOG2E, nb);
    }
}
__device__ __forceinline__ float quad_sum(float v) { v += __shfl_xor_sync(0xffffffffu, v, 1); return v + __shfl_xor_sync(0xffffffffu, v, 2); }
__device__ __forceinline__ float key_block(const float (&p)[16], float rsA, float rsB, uint32_t d0, uint32_t d1, uint32_t off) {
    float r[8], sp[2], sn[2];
    uint32_t pos[8], neg[8];
    const float scA = rsA * LOG2E, scB = rsB * LOG2E;
#pragma unroll
    for (int j = 0; j < 8; j += 2) {
        const float a0 = ex2(p[2 * j] * scA), a1 = ex2(p[2 * j + 1] * scA);
        const float b0 = ex2(p[2 * j + 2] * scB), b1 = ex2(p[2 * j + 3] * scB);
        const float pa = a0 * a1, pb = b0 * b1, R = rcp(pa * pb), ta = a0 + a1, tb = b0 + b1;
        r[j] = R * pb; r[j + 1] = R * pa;
        if (j == 0) { sp[0] = ta; sp[1] = tb; sn[0] = r[0] * ta; sn[1] = r[1] * tb; }
        else { sp[0] += ta; sp[1] += tb; sn[0] = fmaf(r[j], ta, sn[0]); sn[1] = fmaf(r[j + 1], tb, sn[1]); }
        pos[j] = pack_bf16(a0, a1); pos[j + 1] = pack_bf16(b0, b1);
    }
    const float qa = quad_sum(sp[0]), qb = quad_sum(sp[1]), na = quad_sum(sn[0]), nb = quad_sum(sn[1]);
    const float iq = rcp(qa * qb), nA = rsA * rcp(na), nB = rsB * rcp(nb);
    const uint32_t fp = pack_bf16(rsA * qb * iq, rsB * qa * iq);
#pragma unroll
    for (int j = 0; j < 8; j += 2) {
        const uint32_t rn = pack_bf16(r[j] * nA, r[j + 1] * nB);
        neg[j] = hmul2(pos[j], dup_lo(rn)); neg[j + 1] = hmul2(pos[j + 1], dup_hi(rn));
        pos[j] = hmul2(pos[j], dup_lo(fp)); pos[j + 1] = hmul2(pos[j + 1], dup_hi(fp));
    }
    stsm_t(d0 + 4096, neg[0], neg[2], neg[4], neg[6]); stsm_t(d1 + 4096, neg[1], neg[3], neg[5], neg[7]);
    stsm_t(d0 + off, pos[0], pos[2], pos[4], pos[6]); stsm_t(d1 + off, pos[1], pos[3], pos[5], pos[7]);
    return (qa + qb) + (na + nb);
}
__device__ __forceinline__ void shift_max(float (&p)[16]) {
    float mA, mB;
    row_ext<1>(p, mA, mB);
#pragma unroll
    for (int j = 0; j < 16; j++) p[j] -= (j & 2) ? mB : mA;
}
__device__ __forceinline__ void key_head(float (&p0)[16], float (&p1)[16], const float (&rs)[4], uint32_t d0, uint32_t d1) {
    uint32_t st;
    asm volatile("mov.u32 %0, 0;" : "=r"(st));
    bool again;
#pragma unroll 1
    do {
        const uint32_t off = (st & 2u) << 11;
        const float chk = key_block(p0, rs[0], rs[1], d0, d1, off) + key_block(p1, rs[2], rs[3], d0 + 8192, d1 + 8192, off);
        again = st == 1u || (st == 0u && !__all_sync(0xffffffffu, chk < 1.0e9f));
        if (__builtin_expect(again, 0)) {
            if (st) {
#pragma unroll
                for (int j = 0; j < 16; j += 2) {
                    float t = p0[j]; p0[j] = -p0[j + 1]; p0[j + 1] = -t;
                    t = p1[j]; p1[j] = -p1[j + 1]; p1[j + 1] = -t;
                }
            }
            shift_max(p0); shift_max(p1);
            st++;
        }
        asm volatile("" ::: "memory");
    } while (again);
}
__device__ __forceinline__ void o_mma(float (&d)[20], float (&e)[20], const uint32_t (&pos)[8], const uint32_t (&neg)[8], uint32_t klo) {
    wgmma_rs_n40_tb(d, pos[0], pos[1], pos[2], pos[3], desc_from(klo, 1024u >> 4), 0);
    wgmma_rs_n40_tb(e, neg[0], neg[1], neg[2], neg[3], desc_from(klo + 32, 1024u >> 4), 0);
    wgmma_rs_n40_tb(d, pos[4], pos[5], pos[6], pos[7], desc_from(klo + 16, 1024u >> 4), 1);
    wgmma_rs_n40_tb(e, neg[4], neg[5], neg[6], neg[7], desc_from(klo + 48, 1024u >> 4), 1);
}
__device__ __forceinline__ void o_store(const float (&d)[20], const float (&e)[20], __nv_bfloat16* dst) {
    const float iA = rcp(fmaf(d[16], e[17], fmaf(e[16], d[17], 1e-6f * d[17] * e[17])));
    const float iB = rcp(fmaf(d[18], e[19], fmaf(e[18], d[19], 1e-6f * d[19] * e[19])));
    const float pA = e[17] * iA, nA = d[17] * iA, pB = e[19] * iB, nB = d[19] * iB;
    uint32_t oa[4], ob[4];
#pragma unroll
    for (int j = 0; j < 4; j++) {
        oa[j] = pack_bf16(fmaf(d[j * 4], pA, e[j * 4] * nA), fmaf(d[j * 4 + 1], pA, e[j * 4 + 1] * nA));
        ob[j] = pack_bf16(fmaf(d[j * 4 + 2], pB, e[j * 4 + 2] * nB), fmaf(d[j * 4 + 3], pB, e[j * 4 + 3] * nB));
    }
    *reinterpret_cast<uint4*>(dst) = make_uint4(oa[0] ? oa[0] : 0x8000u, oa[1], oa[2], oa[3]);
    *reinterpret_cast<uint4*>(dst + 8 * D_) = make_uint4(ob[0] ? ob[0] : 0x8000u, ob[1], ob[2], ob[3]);
}

template <int N> __device__ __forceinline__ void kv_gather(uint4 (&v)[3 * N], const uint4* src, uint32_t dst, int lane, float us) {
    unsigned it = 0;
#pragma unroll 1
    while (++it < (1u << 20)) {
        bool ok = true;
#pragma unroll
        for (int j = 0; j < 3 * N; j++) ok = ok && (v[j].w >> 16) == 0x4800u;
        if (__all_sync(0xffffffffu, ok)) break;
#pragma unroll
        for (int j = 0; j < 3 * N; j++) v[j] = ld_gpu(src + j * 32);
    }
    dst += (lane >> 2) * 16;
    auto cv = [&](uint32_t w) { const float2 f = unpack_f16(w); return pack_bf16(f.x * us, f.y * us); };
#pragma unroll
    for (int n = 0; n < N; n++) {
        sts128(dst + (lane & 3) * 1024 + n * 256, cv(v[3 * n].x), cv(v[3 * n].y), cv(v[3 * n].z), cv(v[3 * n + 2].x));
        sts128(dst + (lane & 3) * 1024 + n * 256 + 128, cv(v[3 * n + 1].x), cv(v[3 * n + 1].y), cv(v[3 * n + 1].z), cv(v[3 * n + 2].y));
        sts32(dst + 4096 + n * 256 + (lane & 3) * 4, pack_bf16(unpack_f16(v[3 * n].w).x, 1.0f));
        sts32(dst + 4096 + n * 256 + 128 + (lane & 3) * 4, pack_bf16(unpack_f16(v[3 * n + 1].w).x, 1.0f));
    }
    fence_async_smem();
    __syncwarp();
}

__global__ void __launch_bounds__(NTHREADS, 1)
fused_kernel(const Params P, const __grid_constant__ CUtensorMap tmX, const __grid_constant__ CUtensorMap tmW, const __grid_constant__ CUtensorMap tmX2,
             const __grid_constant__ SideMaps tmS, const __grid_constant__ CUtensorMap tmPhi,
             const __grid_constant__ CUtensorMap tmWo, const __grid_constant__ CUtensorMap tmO) {
    extern __shared__ __align__(1024) uint8_t smem_raw[];
    constexpr uint32_t sb = 1024;
    if (smem_u32(smem_raw) != sb) return;
    constexpr uint32_t bars = sb + SM_BARS;
    const int rb = blockIdx.x >> 4, hp = blockIdx.x & 15;
    TLP(threadIdx.x == 32, 0); TLG(threadIdx.x == 32, 48);
    auto load_stage = [&](int s, int ks) {
        mbar_expect_tx(bars + 8 * (B_FULL + s), STAGE);
        tma_2d(sb + s * STAGE, &tmX, bars + 8 * (B_FULL + s), ks * 64, rb * 256);
        tma_3d(sb + s * STAGE + 32768, &tmW, bars + 8 * (B_FULL + s), hp * 64, ks * 64, 0);
    };
    if (threadIdx.x < 256) {
        const uint32_t t = threadIdx.x, r = t >> 3, sw = ((t ^ r) & 7) * 16;
        const __nv_bfloat16* wp = P.wqkv + (size_t)r * 3 * D_ + hp * 64 + (t & 7) * 8;
        const __nv_bfloat16* xp = P.x + (size_t)(rb * 256 + (t >> 7) * 128 + (r & 15)) * D_ + (t & 7) * 8;
#pragma unroll
        for (int i = 0; i < 3; i++) asm volatile("cp.async.cg.shared.global [%0], [%1], 16;" :: "r"(sb + 32768 + i * 8192 + r * 128 + sw), "l"(wp + i * D_) : "memory");
#pragma unroll
        for (int i = 0; i < 8; i++) asm volatile("cp.async.cg.shared.global [%0], [%1], 16;" :: "r"(sb + (t >> 7) * 16384 + ((r & 15) + i * 16) * 128 + sw), "l"(xp + i * 16 * D_) : "memory");
        asm volatile("cp.async.commit_group;" ::: "memory");
#pragma unroll
        for (int i = 0; i < 3; i++) asm volatile("cp.async.cg.shared.global [%0], [%1], 16;" :: "r"(sb + 36864 + i * 8192 + r * 128 + sw), "l"(wp + 96 * D_ + i * D_) : "memory");
        asm volatile("cp.async.commit_group;" ::: "memory");
    }
    const int tid = threadIdx.x, warp = __shfl_sync(0xffffffffu, tid >> 5, 0), lane = tid & 31;
    const bool elect = lane == 0;

    if (warp >= 8) {
        const int aw = warp - 9;
        auto load_o = [&](int i, unsigned par) {
            mbar_expect_tx(bars + 8 * (B_OF + i), 16384);
            tma_2d(sb + o_slot(i) * 16384, &tmO, bars + 8 * (B_OF + i), i * 64, par * S_ + rb * 256 + (hp & 1) * 128);
        };
        auto load_wo = [&](int i) {
            mbar_expect_tx(bars + 8 * (B_OF + i), 16384);
            tma_4d(sb + wo_slot(i) * 16384, &tmWo, bars + 8 * (B_OF + i), 0, (i >> 3) * 32, (i & 7) * 2, hp & 14);
        };
        if (warp == 9) {
            if (elect_one()) {
#pragma unroll
                for (int i = B_OF; i < B_COUNT; i++)
                    mbar_init(bars + 8 * i, i < B_SD ? 2 : (i < B_WPHI ? 8 : ((i < B_KV || i >= B_FF || i == B_LN) ? 1 : 4)));
                asm volatile("fence.mbarrier_init.release.cluster;" ::: "memory");
            }
        }
        if (warp == 8) {
            if (elect_one()) {
#pragma unroll
                for (int i = 0; i < 3; i++) { mbar_init(bars + 8 * (B_FULL + i), 1); mbar_init(bars + 8 * (B_EMPTY + i), 8); }
                mbar_init(bars + 8 * B_XR, 1);
                asm volatile("fence.mbarrier_init.release.cluster;" ::: "memory");
                asm volatile("mbarrier.arrive.shared::cta.b64 _, [%0];" :: "r"(bars + 8 * B_FULL) : "memory");
            }
            __syncwarp();
            nb_arrive(0, NTHREADS);
        } else {
            __syncwarp();
            nb_sync(0, NTHREADS);
        }
        asm volatile("setmaxnreg.dec.sync.aligned.u32 56;");
        if (warp == 8 && elect_one()) {
            load_stage(1, 1); load_stage(2, 2);
            mbar_expect_tx(bars + 8 * B_XR, 32768);
            asm volatile("cp.async.bulk.shared::cluster.global.mbarrier::complete_tx::bytes [%0], [%1], 32768, [%2];"
                         :: "r"(sb + SM_FB + 4096), "l"(P.x + (size_t)blockIdx.x * 16 * D_), "r"(bars + 8 * B_XR) : "memory");
        }
        __syncwarp();
        nb_sync(NB_KV, 128);
        unsigned epoch;
        asm volatile("ld.relaxed.gpu.global.u32 %0, [%1];" : "=r"(epoch) : "l"(&P.scr->epoch) : "memory");
        auto get_acc = [&]() { return &P.scr->acc[epoch & 1u]; };
        if (warp == 8) {
            epoch = __shfl_sync(0xffffffffu, epoch, 0);
            int s = 0, ph = 0;
#pragma unroll 1
            for (int j = 0; j < 15; j++) {
                mbar_wait(bars + 8 * (B_EMPTY + s), ph);
                if (elect_one()) {
                    if (j < 13) load_stage(s, j + 3);
                    if (j < 2) {
                        prefetch_l2(P.wqkv + (size_t)(256 + j * 384 + blockIdx.x * 3) * 3 * D_, 18432);
                    } else if (j < 10) {
                        if (j == 2) asm volatile("mbarrier.arrive.shared::cta.b64 _, [%0];" :: "r"(bars + 8 * B_FF) : "memory");
                        const size_t o = (size_t)((j - 2) * 128 + blockIdx.x) * F_;
                        prefetch_l2(P.wg + o, F_ * 2); prefetch_l2(P.wu + o, F_ * 2);
                    }
                    if (j == JWO) prefetch_l2(P.wo + (size_t)blockIdx.x * 8 * D_, 16384);
                    if (j == 12) {
                        asm volatile("prefetch.tensormap [%0];" :: "l"(&tmO) : "memory");
                        asm volatile("prefetch.tensormap [%0];" :: "l"(&tmS.wd8) : "memory");
                        asm volatile("prefetch.tensormap [%0];" :: "l"(&tmWo) : "memory");
                        mbar_expect_tx(bars + 8 * B_WPHI, 4096);
                        tma_2d(sb + SM_WPHI, &tmPhi, bars + 8 * B_WPHI, 0, hp * 64);
                    }
                    if (j >= 13) {
                        if (blockIdx.x >= 112 || j == 13) { load_wo(2 * j - 26); load_wo(2 * j - 25); }
                        else {
                            mbar_expect_tx(bars + 8 * (B_DN + 1), 32768);
                            tma_3d(sb + 6 * 16384, &tmS.wd8, bars + 8 * (B_DN + 1), 0, blockIdx.x * 32, 8);
                        }
                    }
                }
                __syncwarp();
                if (++s == 3) { s = 0; ph ^= 1; }
                if (j == 12 && hp == 0 && lane < 4) P.scr->hint[rb * 32 + lane] = 0u;
                if (j >= 3 && j < 11) {
                    uint4* zp = reinterpret_cast<uint4*>(P.o + (size_t)((~epoch & 1u) * S_ + blockIdx.x * 16 + (j - 3) * 2) * D_) + lane;
#pragma unroll
                    for (int i = 0; i < 2; i++) zp[i * 128] = make_uint4(0, 0, 0, 0);
                    const int i = (j - 3) * 32 + lane;
                    if (i < ACC_VEC_PER_CTA) reinterpret_cast<uint4*>(&P.scr->acc[~epoch & 1u])[blockIdx.x * ACC_VEC_PER_CTA + i] = make_uint4(0, 0, 0, 0);
                }
            }
            TLP(elect, 20);
        } else {
            const bool ffn = blockIdx.x < 112;
            const uint32_t fbuf = sb + SM_FB + 4096 + aw * 12288, fbar = bars + 8 * (B_FF + 1 + aw * 3);
        const int nc = aw == 0 ? NC0 : (aw == 1 ? 12 - NC0 - NC2 : NC2), c0 = aw == 0 ? 0 : (aw == 1 ? NC0 : 12 - NC2);
        const int ng = !ffn ? 0 : (aw == 0 ? NG0 : (aw == 1 ? NG1 : 32 - NG0 - NG1)), g0 = aw == 0 ? 0 : (aw == 1 ? NG0 : NG0 + NG1);
        auto issue = [&](int i, int b) {
            __syncwarp();
            if (i < nc + ng && elect_one()) {
                mbar_expect_tx(fbar + b * 8, 4096);
                if (i < nc) {
                    tma_2d(fbuf + b * 4096, &tmS.wc, fbar + b * 8, ((c0 + i) >> 2) * 1024 + hp * 64, rb * 128 + ((c0 + i) & 3) * 32);
                } else {
                    tma_2d(fbuf + b * 4096, &tmS.wg, fbar + b * 8, blockIdx.x * 32, (g0 + i - nc) * 32);
                    tma_2d(fbuf + b * 4096 + 2048, &tmS.wu, fbar + b * 8, blockIdx.x * 32, (g0 + i - nc) * 32);
                }
            }
            __syncwarp();
        };
            {
                uint4 wv[4];
#pragma unroll
                for (int i = 0; i < 4; i++) wv[i] = __ldg(reinterpret_cast<const uint4*>(P.wr) + i * 32 + lane);
                const uint32_t* ww = reinterpret_cast<const uint32_t*>(wv);
                float sw = 0.f;
#pragma unroll
                for (int i = 0; i < 16; i++) sw += bf_lo(ww[i]) + bf_hi(ww[i]);
#pragma unroll 1
                for (int o = 16; o > 0; o >>= 1) sw += __shfl_xor_sync(0xffffffffu, sw, o);
                sts32(sb + SM_MISC + 20, __float_as_uint(sw));
                if (aw == 2) {
#pragma unroll
                    for (int i = 0; i < 3; i++) P.scr->kv[(hp * 8 + rb) * 96 + i * 32 + lane] = make_uint4(0, 0, 0, 0);
                    if (hp == 0) reinterpret_cast<uint4*>(&P.scr->cnt_o[rb * 128])[lane] = make_uint4(0, 0, 0, 0);
                    asm volatile("fence.acq_rel.gpu;" ::: "memory");
                    __syncwarp();
                }
                mbar_wait(bars + 8 * B_XR, 0);
#pragma unroll 1
                for (int r = aw * 6; r < min(aw * 6 + 6, 16); r++) {
                    const uint32_t buf = sb + SM_FB + 4096 + r * 2048;
                    uint4 xv[4];
                    uint32_t c2 = lds32(buf);
#pragma unroll
                    for (int i = 0; i < 4; i++) xv[i] = lds128(buf + i * 512 + lane * 16);
                    sts32(sb + SM_MISC + 12, 0u);
                    c2 = fabsf(bf_lo(c2) - bf_hi(c2)) < 0.25f * fabsf(bf_lo(c2)) ? dup_lo(c2) : 0u;
                    const uint32_t* xw = reinterpret_cast<const uint32_t*>(xv);
                    uint32_t d2[2] = {0u, 0u};
                    float s0 = 0.f, s1 = 0.f, q0 = 0.f, q1 = 0.f;
#pragma unroll
                    for (int i = 0; i < 16; i++) {
                        const uint32_t a = hsub2(xw[i], c2);
                        s0 += bf_lo(a); s1 += bf_hi(a);
                        d2[i & 1] = hfma2(a, ww[i], d2[i & 1]);
                        q0 = fmaf(bf_lo(a), bf_lo(a), q0); q1 = fmaf(bf_hi(a), bf_hi(a), q1);
                    }
                    sts128(sb + SM_SP + r * 512 + lane * 16, __float_as_uint(s0 + s1), __float_as_uint(q0 + q1),
                           __float_as_uint((bf_lo(d2[0]) + bf_hi(d2[0])) + (bf_lo(d2[1]) + bf_hi(d2[1]))), c2 << 16);
                }
                epoch = __shfl_sync(0xffffffffu, epoch, 0);
                if (aw < 2) nb_arrive(NB_FFN, 96);
                mbar_wait(bars + 8 * B_FF, 0);
#pragma unroll 1
                for (int i = 0; i < 3; i++) issue(i, i);
                const unsigned tag = epoch + 1u;
                if (aw == 2) {
                    nb_sync(NB_FFN, 96);
                    TLP(elect, 23);
                    float s = 0.f, q = 0.f, dt = 0.f, x0;
#pragma unroll 8
                    for (int j = 0; j < 16; j++) {
                        const uint4 e = lds128(sb + SM_SP + lane * 256 + ((j + lane) & 15) * 16);
                        s += __uint_as_float(e.x); q += __uint_as_float(e.y); dt += __uint_as_float(e.z); x0 = __uint_as_float(e.w);
                    }
                    s += __shfl_xor_sync(0xffffffffu, s, 1); q += __shfl_xor_sync(0xffffffffu, q, 1); dt += __shfl_xor_sync(0xffffffffu, dt, 1);
                    const float ms = s * (1.0f / D_);
                    const float vb = round_bf16(fmaxf(q - s * ms, 0.f) * (1.0f / D_));
                    const uint32_t md = pack_bf16(x0 + ms, sqrt_a(round_bf16(vb + 1e-5f)));
                    const uint32_t rbits = pack_bf16((dt - (bf_lo(md) - x0) * ldsf(sb + SM_MISC + 20)) * rcp(bf_hi(md)), 0.f);
                    const int row = blockIdx.x * 16 + (lane >> 1);
                    const uint32_t key = ((((rbits & 0x8000u) ? (~rbits & 0xFFFFu) : (rbits | 0x8000u)) + 1u) << 11) | (uint32_t)(2047 - row);
                    asm volatile("st.relaxed.gpu.global.v2.u32 [%0], {%1, %2};" :: "l"(&P.scr->rows[row]), "r"(md), "r"(tag) : "memory");
                    if (key == __reduce_max_sync(0xffffffffu, key))
                        asm volatile("st.relaxed.gpu.global.v4.u32 [%0], {%1, %2, %3, %3};" :: "l"(&P.scr->best[blockIdx.x]), "r"(key), "r"(md), "r"(tag) : "memory");
                    TLP(elect, 24);
                }
                {
                    float a[8], sq = 0.f, wt = 0.f;
#pragma unroll
                    for (int i = 0; i < 8; i++) a[i] = 0.f;
#pragma unroll 1
                    for (int m = 0; m < nc; m++) {
                        const int b = m % 3, c = c0 + m;
                        mbar_wait(fbar + b * 8, (m / 3) & 1);
                        uint4 v[8];
#pragma unroll
                        for (int i = 0; i < 8; i++) v[i] = lds128(fbuf + b * 4096 + i * 512 + lane * 16);
                        sts32(sb + SM_MISC + 12, 0u);
                        colsum8<true>(a, sq, v);
                        fence_regs(a);
                        wt += 1.0f;
                        issue(m + 3, b);
                        if ((c & 3) == 3 || m == nc - 1) {
#pragma unroll 1
                            for (int o = 8; o <= 16; o <<= 1) {
#pragma unroll
                                for (int i = 0; i < 8; i++) a[i] += __shfl_xor_sync(0xffffffffu, a[i], o);
                                sq += __shfl_xor_sync(0xffffffffu, sq, o);
                            }
                            float4* dst = &get_acc()->cs[((c >> 2) * 16 + hp) * 24 + lane];
                            if (lane < 8) { red_v4(dst, a[0], a[1], a[2], wt); red_v4(dst + 8, a[3], a[4], a[5], wt); red_v4(dst + 16, a[6], a[7], sq, wt); }
#pragma unroll
                            for (int i = 0; i < 8; i++) a[i] = 0.f;
                            wt = 0.f;
                        }
                    }
                    TLP(tid == 288, 26); TLP(tid == 320, 15); TLP(tid == 352, 22);
                }
                if (aw == 0) {
                    uint4 v[4];
                    unsigned it = 0;
                    bool ok = true;
#pragma unroll 1
                    do {
                        if (!ok) __nanosleep(200);
#pragma unroll
                        for (int i = 0; i < 4; i++) v[i] = ld_gpu(&P.scr->best[i * 32 + lane]);
                        ok = v[0].z == tag && v[1].z == tag && v[2].z == tag && v[3].z == tag;
                    } while (!__all_sync(0xffffffffu, ok) && ++it < (1u << 20));
#pragma unroll
                    for (int i = 1; i < 4; i++) if (v[i].x > v[0].x) v[0] = v[i];
                    const uint32_t key = __reduce_max_sync(0xffffffffu, v[0].x);
                    const uint32_t md = __reduce_or_sync(0xffffffffu, v[0].x == key ? v[0].y : 0u);
                    const int sel = 2047 - (int)(key & 2047u);
                    const uint4* xp = reinterpret_cast<const uint4*>(P.x + (size_t)sel * D_) + lane;
#pragma unroll
                    for (int i = 0; i < 4; i++) v[i] = __ldg(xp + i * 32);
                    const uint32_t m2 = __byte_perm(md, 0, 0x1010);
                    const float rs = rcp(bf_hi(md));
                    const uint32_t ord = (key >> 11) - 1u;
                    const float r = __uint_as_float(((ord & 0x8000u) ? (ord & 0x7FFFu) : (~ord & 0xFFFFu)) << 16);
                    sts128(sb + SM_MISC, (uint32_t)sel, __float_as_uint(round_bf16(rcp(1.0f + ex2(-r * LOG2E)))), epoch, 0u);
#pragma unroll
                    for (int i = 0; i < 4; i++) {
                        const uint32_t e0 = ln_pair(v[i].x, m2, rs), e1 = ln_pair(v[i].y, m2, rs), e2 = ln_pair(v[i].z, m2, rs), e3 = ln_pair(v[i].w, m2, rs);
                        const uint32_t xa = sb + SM_XS + i * 512 + (lane >> 2) * 64 + (lane & 3) * 4;
                        sts32(xa, __byte_perm(e0, e2, 0x5410)); sts32(xa + 16, __byte_perm(e0, e2, 0x7632));
                        sts32(xa + 32, __byte_perm(e1, e3, 0x5410)); sts32(xa + 48, __byte_perm(e1, e3, 0x7632));
                    }
                    TLP(elect, 25);
                    __syncwarp();
                    mbar_arrive_if(elect, bars + 8 * B_XS);
                }
            }
            if (aw == 2) {
                    const int l = lane < 24 ? lane : 0;
                    const float4* src = &get_acc()->cs[((l >> 3) * 16 + hp) * 24 + (l & 7)];
                    float4 v0, v1, v2;
                    uint4 v[4];
                    unsigned it = 0;
                    bool ok;
#pragma unroll 1
                    do {
                        v0 = ld_gpu(src); v1 = ld_gpu(src + 8); v2 = ld_gpu(src + 16);
                        ok = v0.w == 32.0f && v1.w == 32.0f && v2.w == 32.0f;
#pragma unroll
                        for (int i = 0; i < 4; i++) v[i] = ld_gpu(reinterpret_cast<const uint4*>(&P.scr->rows[rb * 256]) + i * 32 + lane);
#pragma unroll
                        for (int i = 0; i < 4; i++) ok = ok && v[i].y == epoch + 1u && v[i].w == epoch + 1u;
                    } while (!__all_sync(0xffffffffu, ok) && ++it < (1u << 20));
#pragma unroll
                    for (int i = 0; i < 4; i++) {
                        const uint32_t o = i * 256 + lane * 8;
                        sts64(sb + SM_MD + o, v[i].x, v[i].z);
                        sts64(sb + SM_RS + o, __float_as_uint(rcp(bf_hi(v[i].x))), __float_as_uint(rcp(bf_hi(v[i].z))));
                        const uint32_t h0 = hmul2(dup_lo(v[i].x), 0xBF00BF00u), h1 = hmul2(dup_lo(v[i].z), 0xBF00BF00u);
                        sts128(sb + SM_AX + o * 4, h0, h0 & 0xFFFFu, 0u, 0u);
                        sts128(sb + SM_AX + o * 4 + 16, h1, h1 & 0xFFFFu, 0u, 0u);
                    }
                    sts128(sb + SM_H + lane * 16, 0u, 0u, 0u, 0u); sts128(sb + SM_H + 512 + lane * 16, 0u, 0u, 0u, 0u);
                    const uint32_t e2 = __reduce_max_sync(0xffffffffu, l >= 16 ? __float_as_uint(v2.z) : 0u) >> 23;
                    sts32(sb + SM_MISC + 16, (uint32_t)min(max(187 - (int)((e2 + 1) >> 1), 1), 180) << 23);
                    float cc[8] = {v0.x, v0.y, v0.z, v1.x, v1.y, v1.z, v2.x, v2.y};
                    const uint32_t bx = sb + SM_BX + (l >> 3) * 1024;
#pragma unroll 1
                    for (int k = 0; k < 8; k++) {
                        uint32_t w[4];
#pragma unroll
                        for (int i = 0; i < 4; i++) {
                            w[i] = pack_bf16(cc[2 * i], cc[2 * i + 1]);
                            cc[2 * i] -= bf_lo(w[i]); cc[2 * i + 1] -= bf_hi(w[i]);
                        }
                        sts128(bx + k * 128 + (((l & 7) ^ k) * 16), w[0], w[1], w[2], w[3]);
                    }
                    fence_async_smem();
                    __syncwarp();
                    mbar_arrive_if(elect, bars + 8 * B_LN);
                    TLP(elect, 28);
                }
            mbar_wait(bars + 8 * B_XS, 0);
            if (ffn) {
                float a[8];
#pragma unroll
                for (int i = 0; i < 8; i++) a[i] = 0.f;
                TLP(elect, 40 + aw);
                gemv_run<256>(a, ng, nc % 3, (nc / 3) & 1, fbuf + (lane >> 4) * 2048 + (lane & 15) * 16, sb + SM_XS + g0 * 64 + (lane & 12) * 4, 64, fbar, sb + SM_MISC + 12,
                              [&](int m, int b) { issue(nc + m + 3, b); });
                TLP(elect, 44 + aw);
#pragma unroll 1
                for (int o = 4; o <= 8; o <<= 1) {
#pragma unroll
                    for (int i = 0; i < 8; i++) a[i] += __shfl_xor_sync(0xffffffffu, a[i], o);
                }
                if ((lane & 12) == 0) {
                    const uint32_t ga = sb + SM_GU + aw * 256 + (lane >> 4) * 128 + (lane & 3) * 32;
                    sts128(ga, __float_as_uint(a[0]), __float_as_uint(a[1]), __float_as_uint(a[2]), __float_as_uint(a[3]));
                    sts128(ga + 16, __float_as_uint(a[4]), __float_as_uint(a[5]), __float_as_uint(a[6]), __float_as_uint(a[7]));
                }
                nb_sync(NB_AUX, 96);
                if (warp == 9) {
                    if (elect_one()) {
                        mbar_expect_tx(bars + 8 * B_DN, 32768);
                        tma_3d(sb + SM_FB + 8192, &tmS.wd8, bars + 8 * B_DN, 0, blockIdx.x * 32, 0);
                    }
                    const uint32_t ga = sb + SM_GU + lane * 4;
                    const float gg = round_bf16((ldsf(ga) + ldsf(ga + 256)) + ldsf(ga + 512));
                    const float uu = round_bf16((ldsf(ga + 128) + ldsf(ga + 384)) + ldsf(ga + 640));
                    asm volatile("st.shared.u16 [%0], %1;" :: "r"(sb + SM_H + (lane >> 3) * 256 + 112 + (lane & 7) * 2), "h"((uint16_t)pack_bf16(round_bf16(silu_f(gg)) * uu, 0.f)) : "memory");
                    fence_async_smem();
                }
                __syncwarp();
                TLP(tid == 288, 27);
            }
        }
        {
            TLP(tid == 288, 38);
            const int w4 = warp & 3;
            const uint32_t sp = sb + SM_FB + w4 * 1536;
            auto send = [&](int h) {
                if (elect_one()) {
                    asm volatile("cp.reduce.async.bulk.global.shared::cta.bulk_group.add.noftz.f16 [%0], [%1], 1536;"
                                 :: "l"(&P.scr->kv[(hp * 8 + h * 4 + w4) * 96]), "r"(sp) : "memory");
                    asm volatile("cp.async.bulk.commit_group;" ::: "memory");
                }
            };
            float ya[4] = {0.f, 0.f, 0.f, 0.f}, yb[4] = {0.f, 0.f, 0.f, 0.f};
            uint4 g0[3];
#pragma unroll 1
            for (int h = 0; h < 2; h++) {
                {
                    float d[20];
                    const uint32_t alo = dlo(sb + SM_PHI + h * 32768, 16), vlo = dlo(sb + SM_V + h * 20480, 16);
                    mbar_wait(bars + 8 * (B_PHI + h), 0);
                    wgmma_fence();
#pragma unroll
                    for (int k = 0; k < 16; k++)
                        wgmma_ss_n40(d, desc_from(alo + (k >> 2) * 512 + (k & 3) * 2, DH128), desc_from(vlo + (k >> 2) * 320 + (k & 3) * 2, DH128), k);
                    wgmma_commit();
#pragma unroll
                    for (int j = 0; j < 3; j++) g0[j] = ld_gpu(&P.scr->kv[(hp * 8 + w4) * 96 + j * 32 + lane]);
                    asm volatile("cp.async.bulk.wait_group.read 0;" ::: "memory");
                    __syncwarp();
                    const float ksc = ldsf(sb + SM_MISC + 16);
                    wgmma_wait<0>();
                    fence_regs(d);
#define U(x) pack_f16(d[x] * ksc, d[x + 1] * ksc)
                    sts128(sp + lane * 16, U(0), U(4), U(8), pack_f16(d[16], 1.0f));
                    sts128(sp + 512 + lane * 16, U(2), U(6), U(10), pack_f16(d[18], 1.0f));
                    sts128(sp + 1024 + lane * 16, U(12), U(14), 0u, 0x3C000000u);
#undef U
                    fence_async_smem();
                    __syncwarp();
                    send(h);
                    TLP(tid == 256, 30 + h);
                    nb_sync(NB_KV, 128);
                    if (h) break;
                    if (warp == 8 && elect_one()) {
                        mbar_expect_tx(bars + 8 * B_X, 32768);
                        tma_2d(sb, &tmX2, bars + 8 * B_X, (hp >> 1) * 128, rb * 256 + (hp & 1) * 128);
                        tma_2d(sb + 16384, &tmX2, bars + 8 * B_X, (hp >> 1) * 128 + 64, rb * 256 + (hp & 1) * 128);
                        load_wo(4);
                    }
                    __syncwarp();
                }
                if (blockIdx.x < 112) {
                    const uint32_t hlo = dlo(sb + SM_H, 256);
                    mbar_wait(bars + 8 * B_DN, 0);
                    mbar_wait(bars + 8 * (B_DN + 1), 0);
                    wgmma_fence();
#pragma unroll 2
                    for (int k = 0; k < 16; k++) {
                        wgmma_ss_n8_ta(yb, desc_from(dlo(sb + 6 * 16384, 16) + k * 128, DH128), desc_from(hlo + (k & 1) * 32 + 7 - (k >> 1), 8), k);
                        wgmma_ss_n8_ta(ya, desc_from(dlo(sb + SM_FB + 8192, 16) + k * 128, DH128), desc_from(hlo + (k & 1) * 32 + 7 - (k >> 1), 8), k);
                    }
                    wgmma_commit();
                    wgmma_wait<0>();
                    fence_regs(ya); fence_regs(yb);
                    if (warp == 8) {
                        nb_sync(NB_KV, 128);
                        if (elect_one()) { load_wo(2); load_wo(3); }
                        __syncwarp();
                    } else {
                        nb_arrive(NB_KV, 128);
                    }
                    TLP(tid == 288, 29);
                }
            }
            const float kus = __uint_as_float((254u << 23) - lds32(sb + SM_MISC + 16));
            kv_gather<1>(g0, &P.scr->kv[(hp * 8 + w4) * 96 + lane], sb + SM_KVOP + w4 * 256, lane, kus);
            mbar_arrive_if(elect, bars + 8 * B_KV);
            asm volatile("cp.async.bulk.wait_group.read 0;" ::: "memory");
            __syncwarp();
            if (blockIdx.x < 112) {
#define U(x) __float_as_uint(x)
                sts128(sp + lane * 16, U(ya[0]), U(ya[1]), U(ya[2]), U(1.0f));
                sts128(sp + 512 + lane * 16, U(ya[3]), U(yb[0]), U(yb[1]), U(1.0f));
                sts128(sp + 1024 + lane * 16, U(yb[2]), U(yb[3]), 0u, U(1.0f));
#undef U
                fence_async_smem();
                __syncwarp();
                if (elect_one()) {
                    asm volatile("cp.reduce.async.bulk.global.shared::cta.bulk_group.add.f32 [%0], [%1], 1536;"
                                 :: "l"(&get_acc()->y[((blockIdx.x & 3) * 4 + w4) * 96]), "r"(sp) : "memory");
                    asm volatile("cp.async.bulk.commit_group;" ::: "memory");
                }
                __syncwarp();
            }
            if (w4 >= 2) {
                uint4 g1[6];
#pragma unroll
                for (int j = 0; j < 6; j++) g1[j] = make_uint4(0, 0, 0, 0);
                kv_gather<2>(g1, &P.scr->kv[(hp * 8 + 2 * w4) * 96 + lane], sb + SM_KVOP - 5120 + (w4 - 2) * 512, lane, kus);
                mbar_arrive_if(lane < 2, bars + 8 * (B_KV + 1));
            }
            asm volatile("cp.async.bulk.wait_group.read 0;" ::: "memory");
            __syncwarp();
            mbar_arrive_if(elect, bars + 8 * B_S1);
        }
        if (warp == 8) {
            if (elect_one()) {
                const unsigned* flag = &P.scr->cnt_o[rb * 128];
                uint4 hint = make_uint4(0, 0, 0, 0);
                mbar_wait(bars + 8 * B_O, 0);
#pragma unroll
                for (int i = 0; i < 16; i++) {
                    if (i < 4) {
                        unsigned it = 0;
#pragma unroll 1
                        while ((i == 0 ? hint.x : (i == 1 ? hint.y : (i == 2 ? hint.z : hint.w))) < 16u && ++it < (1u << 14)) hint = ld_gpu(reinterpret_cast<const uint4*>(&P.scr->hint[rb * 32]));
                    }
                    if (i == 4) poll_counter(flag + 32, 16);
                    if (i == 8) mbar_wait(bars + 8 * B_C1, 0);
                    if (i == 4 || i == 8) asm volatile("fence.proxy.async.global;" ::: "memory");
                    if ((i & 3) == 0 && i < 12) TL(i == 0 ? 21 : (i == 4 ? 34 : 36));
                    if (i == 4 || i > 5) mbar_wait(bars + 8 * (B_SD + max(i - 5, 0)), 0);
                    load_o(i, epoch & 1u);
                    if (i == 3) { load_wo(5); mbar_wait(bars + 8 * B_S1, 0); load_wo(6); }
                    if (i >= 5 && i < 14) load_wo(i + 2);
                }
            }
        } else if (warp == 9) {
            if (elect_one()) {
                unsigned* flag = &P.scr->cnt_o[rb * 128];
                mbar_wait(bars + 8 * B_O, 0);
                asm volatile("red.release.gpu.global.add.u32 [%0], 1;" :: "l"(flag + 32) : "memory");
                TL(35);
            }
        } else if (warp == 10) {
            if (elect_one()) {
                unsigned* f = &P.scr->cnt_o[rb * 128 + 96];
                mbar_wait(bars + 8 * (B_O + 1), 0);
                asm volatile("red.release.gpu.global.add.u32 [%0], 1;" :: "l"(f) : "memory");
                TL(37);
                poll_counter(f, 16);
                asm volatile("mbarrier.arrive.shared::cta.b64 _, [%0];" :: "r"(bars + 8 * B_C1) : "memory");
            }
        } else if (warp == 11) {
            const uint4 misc = lds128(sb + SM_MISC);
            if ((int)(misc.x >> 7) == rb * 2 + (hp & 1)) {
                float y[4] = {0.f, 0.f, 0.f, 0.f};
#pragma unroll 1
                for (int rep = 0; rep < 4; rep++) {
                    const float4* yp = &get_acc()->y[(rep * 4 + (lane >> 3)) * 96 + (hp >> 3) * 32 + (lane & 7) * 4 + ((hp >> 1) & 3)];
                    float4 u, v;
                    unsigned it = 0;
#pragma unroll 1
                    do { u = ld_gpu(yp); v = ld_gpu(yp + 32); } while (!__all_sync(0xffffffffu, u.w == 28.0f && v.w == 28.0f) && ++it < (1u << 20));
                    if (hp & 8) { y[0] += u.y; y[1] += v.x; y[2] += u.z; y[3] += v.y; } else { y[0] += u.x; y[1] += u.z; y[2] += u.y; y[3] += v.x; }
                }
                const uint32_t sg = __byte_perm(misc.y, 0, 0x3232), ya = sb + SM_Y + ((lane >> 3) * 16 + (lane & 7)) * 2;
                const uint32_t w0 = hmul2(pack_bf16(y[0], y[1]), sg), w1 = hmul2(pack_bf16(y[2], y[3]), sg);
                asm volatile("st.shared.u16 [%0], %1;" :: "r"(ya), "h"((uint16_t)w0) : "memory");
                asm volatile("st.shared.u16 [%0], %1;" :: "r"(ya + 16), "h"((uint16_t)(w0 >> 16)) : "memory");
                asm volatile("st.shared.u16 [%0], %1;" :: "r"(ya + 128), "h"((uint16_t)w1) : "memory");
                asm volatile("st.shared.u16 [%0], %1;" :: "r"(ya + 144), "h"((uint16_t)(w1 >> 16)) : "memory");
                __syncwarp();
                if (lane < 16) {
                    const uint4 xc = __ldg(reinterpret_cast<const uint4*>(P.x + (size_t)misc.x * D_ + (hp >> 1) * 128) + lane);
                    const uint32_t m2 = __byte_perm(lds32(sb + SM_MD + (misc.x & 255u) * 4), 0, 0x1010);
                    const float r = ldsf(sb + SM_RS + (misc.x & 255u) * 4);
                    const uint4 yv = lds128(sb + SM_Y + lane * 16);
                    sts128(sb + SM_Y + lane * 16, silu_pair(hadd2(ln_pair(xc.x, m2, r), yv.x)), silu_pair(hadd2(ln_pair(xc.y, m2, r), yv.y)),
                           silu_pair(hadd2(ln_pair(xc.z, m2, r), yv.z)), silu_pair(hadd2(ln_pair(xc.w, m2, r), yv.w)));
                    sts128(sb + SM_Y + 256 + lane * 16, xc.x, xc.y, xc.z, xc.w);
                }
                __syncwarp();
                mbar_arrive_if(elect, bars + 8 * B_Y);
                TLP(elect, 39);
            }
        }
    } else {
        const int wg = warp >> 2, w4 = warp & 3, g = lane >> 2;
        nb_sync(0, NTHREADS);
        asm volatile("setmaxnreg.inc.sync.aligned.u32 224;");
        TLP(tid == 0, 1);
        const int row0 = wg * 128 + w4 * 16 + g;
        float pq0[16], pq1[16];
        float rs[4];
        uint32_t f2[8], f3[8], q0[8], q1[8], q2[8], q3[8];
        float qa[16], qb[16];
        const uint32_t wlo = dlo(sb + SM_WPHI, 16);
        const uint32_t sw0 = (uint32_t)(((w4 * 2) ^ (lane & 7)) * 16), sw1 = sw0 ^ 16u;
        {
            float acc0[96], acc1[96];
            {
                const uint32_t alo0 = dlo(sb + wg * 16384, 16), blo0 = dlo(sb + 32768, 8192);
                {
#pragma unroll
                    for (int k = 0; k < 4; k++) {
                        if (k == 0) asm volatile("cp.async.wait_group 1;" ::: "memory");
                        if (k == 2) { wgmma_commit(); asm volatile("cp.async.wait_group 0;" ::: "memory"); }
                        if (!(k & 1)) { fence_async_smem(); nb_sync(NB_STAG, 256); wgmma_fence(); }
                        if (k == 0) { TLP(tid == 0, 2); TLG(tid == 0, 49); }
                        wgmma_ss_n192_tb(acc0, desc_from(alo0 + k * 2, DH128), desc_from(blo0 + k * 128, DH128), k);
                        wgmma_ss_n192_tb(acc1, desc_from(alo0 + 512 + k * 2, DH128), desc_from(blo0 + k * 128, DH128), k);
                    }
                    wgmma_commit();
                }
                int s = 1, ph = 0, ps = 0;
#pragma unroll 1
                for (int ks = 1; ks < 16; ks++) {
                    const bool hold = wg && ks == 15;
                    if (hold) {
                        wgmma_wait<0>();
                        mbar_arrive_if(elect, bars + 8 * (B_EMPTY + ps));
                        nb_sync(6, 256);
                    }
                    mbar_wait(bars + 8 * (B_FULL + s), ph);
                    const uint32_t alo = alo0 + s * (STAGE >> 4), blo = blo0 + s * (STAGE >> 4);
                    wgmma_fence();
#pragma unroll
                    for (int k = 0; k < 4; k++) {
                        if (k == SARR && !wg && ks == 15) nb_arrive(6, 256);
                        wgmma_ss_n192_tb(acc0, desc_from(alo + k * 2, DH128), desc_from(blo + k * 128, DH128), 1);
                        wgmma_ss_n192_tb(acc1, desc_from(alo + 512 + k * 2, DH128), desc_from(blo + k * 128, DH128), 1);
                        if (k == 0) {
                            wgmma_commit();
                            wgmma_wait<1>();
                            mbar_arrive_if(elect && !hold, bars + 8 * (B_EMPTY + ps));
                        }
                    }
                    wgmma_commit();
                    ps = s;
                    if (++s == 3) { s = 0; ph ^= 1; }
                }
            }
            if (SARR == 4 && !wg) nb_arrive(6, 256);
            mbar_wait(bars + 8 * B_LN, 0);
            wgmma_fence();
            wgmma_ss_n192_tb(acc0, desc_from(dlo(sb + SM_AX + wg * 2048, 0), 128u >> 4), desc_from(dlo(sb + SM_BX, 1024), 1u << 30), 1);
            wgmma_ss_n192_tb(acc1, desc_from(dlo(sb + SM_AX + wg * 2048 + 1024, 0), 128u >> 4), desc_from(dlo(sb + SM_BX, 1024), 1u << 30), 1);
            wgmma_commit();
            if (SARR == 5 && !wg) nb_arrive(6, 256);
            mbar_wait(bars + 8 * (B_EMPTY + 2), 0);
            mbar_wait(bars + 8 * B_WPHI, 0);
            {
                uint32_t md[4];
#pragma unroll
                for (int i = 0; i < 4; i++) {
                    const int r = row0 + (i >> 1) * 64 + (i & 1) * 8;
                    md[i] = __byte_perm(lds32(sb + SM_MD + r * 4), 0, 0x3232);
                    rs[i] = ldsf(sb + SM_RS + r * 4);
                }
                const uint32_t zb = sb + SM_V + wg * 10240 + (lane >> 4) * 5120 + 4096 + (lane & 7) * 128 + (sw0 ^ ((lane & 8) * 2));
                stsm_t(zb, md[0], md[1], md[2], md[3]);
                stsm_t(zb + 20480, md[0], md[1], md[2], md[3]);
            }
            wgmma_wait<0>();
            fence_regs(acc0); fence_regs(acc1);
            TLP(tid == 0, 3); TLG(tid == 0, 50);
            const uint32_t vb = sb + SM_V + wg * 10240 + lane * 128;
            uint32_t f0[8], f1[8], v[8];
            pack_head<64>(acc0, v); stsm_t(vb + sw0, v[0], v[2], v[4], v[6]); stsm_t(vb + sw1, v[1], v[3], v[5], v[7]);
            pack_head<64>(acc1, v); stsm_t(vb + 5120 + sw0, v[0], v[2], v[4], v[6]); stsm_t(vb + 5120 + sw1, v[1], v[3], v[5], v[7]);
#pragma unroll
            for (int i = 32; i < 48; i++) { asm volatile("" : "+f"(acc0[i]) :: "memory"); asm volatile("" : "+f"(acc1[i]) :: "memory"); }
            pack_head<32>(acc0, f0); pack_head<32>(acc1, f1);
            wgmma_fence();
            feat_mma(pq0, f0, wlo); feat_mma(pq1, f1, wlo);
            wgmma_commit();
            pack_head<80>(acc0, v); stsm_t(vb + 20480 + sw0, v[0], v[2], v[4], v[6]); stsm_t(vb + 20480 + sw1, v[1], v[3], v[5], v[7]);
            pack_head<80>(acc1, v); stsm_t(vb + 25600 + sw0, v[0], v[2], v[4], v[6]); stsm_t(vb + 25600 + sw1, v[1], v[3], v[5], v[7]);
            pack_head<48>(acc0, f2); pack_head<48>(acc1, f3);
            pack_head<0>(acc0, q0); pack_head<0>(acc1, q1);
#pragma unroll
            for (int i = 0; i < 16; i++) { qa[i] = acc0[16 + i]; qb[i] = acc1[16 + i]; }
            fence_regs(f2); fence_regs(f3); fence_regs(q0); fence_regs(q1);
            wgmma_wait<0>();
            fence_regs(pq0); fence_regs(pq1); fence_regs(f0); fence_regs(f1);
            mbar_arrive_if(elect, bars + 8 * B_T);
            TLP(tid == 0, 4);
        }
#pragma unroll 1
        for (int h = 0; h < 2; h++) {
            const uint32_t pb = sb + SM_PHI + wg * 16384 + lane * 128 + h * 32768;
            key_head(pq0, pq1, rs, pb + sw0, pb + sw1);
            wgmma_fence();
            feat_mma(pq0, f2, wlo + 128 - h * 128); feat_mma(pq1, f3, wlo + 128 - h * 128);
            wgmma_commit();
            fence_async_smem();
            __syncwarp();
            mbar_arrive_if(elect, bars + 8 * (B_PHI + h));
            TLP(tid == 0, 6 + 2 * h);
            mbar_wait(bars + 8 * B_T, 0);
            wgmma_wait<0>();
            fence_regs(pq0); fence_regs(pq1); fence_regs(f2); fence_regs(f3);
#pragma unroll
            for (int j = 0; j < 8; j++) { f2[j] = q0[j]; f3[j] = q1[j]; }
            fence_regs(f2); fence_regs(f3);
        }
#pragma unroll
        for (int j = 0; j < 8; j++) { q2[j] = pack_bf16(qa[2 * j], qa[2 * j + 1]); q3[j] = pack_bf16(qb[2 * j], qb[2 * j + 1]); }
        const uint32_t par = lds32(sb + SM_MISC + 8) & 1u;
        const int orow = (hp & 1) * 128 + wg * 64 + w4 * 16 + (lane >> 4);
        const size_t goff = (size_t)(rb * 256 + orow) * D_ + (hp >> 1) * 128 + (lane & 15) * 8;
        uint4 gv[8], xv[8];
#pragma unroll
        for (int i = 0; i < 8; i++) xv[i] = make_uint4(0, 0, 0, 0);
#pragma unroll
        for (int i = 0; i < GSPLIT2; i++) gv[i] = make_uint4(0, 0, 0, 0);
        const uint32_t rowc = sb + ((lane >> 3) & 1) * 16384 + (wg * 64 + w4 * 16 + (lane >> 4)) * 128;
        {
            uint32_t hbump;
            asm volatile("mov.u32 %0, %1;" : "=r"(hbump) : "r"((uint32_t)(hp < 8 && elect)));
            __nv_bfloat16* od = P.o + (size_t)(par * S_ + rb * 256 + row0) * D_ + hp * 32 + (lane & 3) * 8;
#pragma unroll 1
            for (int h = 0; h < 2; h++) {
                uint32_t pa[8], na[8], pb[8], nb[8];
                features(pq0, pq1, rs, pa, na, pb, nb);
                TLP(tid == 0, 16 + h);
                if (h == 0) {
                    wgmma_fence();
                    feat_mma(pq0, q2, wlo + 128); feat_mma(pq1, q3, wlo + 128);
                    wgmma_commit();
                    mbar_wait(bars + 8 * B_X, 0);
#pragma unroll
                    for (int i = 0; i < 8; i++) xv[i] = lds128(rowc + i * 256 + (((lane & 7) ^ ((2 * i + (lane >> 4)) & 7)) * 16));
#pragma unroll
                    for (int i = 0; i < GSPLIT; i++) { gv[i] = xv[i]; gate_item(gv[i], sb, orow + 2 * i); }
                    wgmma_wait<0>();
                    fence_regs(pq0); fence_regs(pq1); fence_regs(q2); fence_regs(q3);
                    TLP(tid == 0, 18);
                } else {
#pragma unroll
                    for (int i = GSPLIT; i < GSPLIT2; i++) { gv[i] = xv[i]; gate_item(gv[i], sb, orow + 2 * i); }
                    TLP(tid == 0, 10);
                }
                {
                    float d0[20], e0[20], d1[20], e1[20];
                    const uint32_t klo = dlo(sb + SM_KVOP - h * 5120, 128);
                    fence_regs(pa); fence_regs(na); fence_regs(pb); fence_regs(nb);
                    mbar_wait(bars + 8 * (B_KV + h), 0);
                    TLP(tid == 0, 32 + h);
                    wgmma_fence();
                    o_mma(d0, e0, pa, na, klo);
                    o_mma(d1, e1, pb, nb, klo);
                    wgmma_commit();
                    wgmma_wait<0>();
                    fence_regs(d0); fence_regs(e0); fence_regs(pa); fence_regs(na);
                    fence_regs(d1); fence_regs(e1); fence_regs(pb); fence_regs(nb);
                    o_store(d0, e0, od + h * 512);
                    asm volatile("{\n.reg .pred q;\nsetp.gt.s32 q, %1, %2;\n@q red.relaxed.gpu.global.add.u32 [%0], %1;\n}" :: "l"(&P.scr->hint[rb * 32 + (hp >> 1) + lane]), "r"(hbump), "r"(h) : "memory");
                    o_store(d1, e1, od + h * 512 + 64 * D_);
                    __syncwarp();
                    mbar_arrive_if(elect, bars + 8 * (B_O + h));
                }
                TLP(tid == 0, 9 + 2 * h);
            }
        }
        float ghr[8], ghm[8];
#pragma unroll
        for (int i = GSPLIT2; i < 8; i++) { ghr[i] = 0.5f * ldsf(sb + SM_RS + (orow + 2 * i) * 4); ghm[i] = -bf_lo(lds32(sb + SM_MD + (orow + 2 * i) * 4)) * ghr[i]; }
        float acc[64];
        {
            const uint32_t alo0 = dlo(sb + wg * 8192, 16), blo0 = dlo(sb, 8192);
            const uint32_t ta0 = sb + (wg * 64 + w4 * 16) * 128 + lane * 16;
            uint32_t cv[2][4];
#pragma unroll
            for (int i = 0; i < 1; i++) {
                mbar_wait(bars + 8 * (B_OF + i), 0);
#pragma unroll
                for (int j = 0; j < 4; j++) cv[i][j] = lds32(ta0 + i * 16384 + j * 512);
            }
#pragma unroll
            for (int i = 0; i < 16; i++) {
                const uint32_t alo = alo0 + o_slot(i) * 1024, blo = blo0 + wo_slot(i) * 1024;
                if (i < 4) {
                    if (__builtin_expect(__any_sync(0xffffffffu, min(min(cv[i & 1][0], cv[i & 1][1]), min(cv[i & 1][2], cv[i & 1][3])) == 0u), 0)) {
                        uint4 v[4];
                        unsigned it = 0;
#pragma unroll 1
                        do {
#pragma unroll
                            for (int j = 0; j < 4; j++) {
                                const int r = j * 4 + (lane >> 3);
                                v[j] = ld_gpu(reinterpret_cast<const uint4*>(P.o + (size_t)(par * S_ + rb * 256 + (orow & ~1) + r) * D_ + i * 64) + ((lane ^ r) & 7));
                            }
                        } while (__any_sync(0xffffffffu, min(min(v[0].x, v[1].x), min(v[2].x, v[3].x)) == 0u) && ++it < (1u << 18));
#pragma unroll
                        for (int j = 0; j < 4; j++) sts128(ta0 + (i & 3) * 16384 + j * 512, v[j].x, v[j].y, v[j].z, v[j].w);
                        fence_async_smem();
                        __syncwarp();
                    }
                } else {
                    mbar_wait(bars + 8 * (B_OF + i), 0);
                }
                if (i == OSTAG && wg == 0) nb_sync(NB_STAG, 256);
                wgmma_fence();
#pragma unroll
                for (int k = 0; k < 4; k++) {
                    if (i == 15 && k == OARR && wg) nb_arrive(NB_STAG, 256);
                    wgmma_ss_n128_tb(acc, desc_from(alo + k * 2, DH128), desc_from(blo + k * 128, DH128), k | i);
                    if (k == OREL) {
                        if (i > 0 && i < 12) {
                            wgmma_commit();
                            wgmma_wait<1>();
                            mbar_arrive_if(elect, bars + 8 * (B_SD + i - 1));
                        }
                    }
                }
                wgmma_commit();
                if (i == 15 && OARR == 4 && wg) nb_arrive(NB_STAG, 256);
                if (i == 0) { TLP(tid == 0, 12); TLG(tid == 0, 51); }
                if (i < 3) {
                    mbar_wait(bars + 8 * (B_OF + i + 1), 0);
#pragma unroll
                    for (int j = 0; j < 4; j++) cv[~i & 1][j] = lds32(ta0 + (i + 1) * 16384 + j * 512);
                }
                static_assert(2 * (8 - GSPLIT2) <= 16 - GST, "");
                if (i >= GST && GSPLIT2 + (i - GST) / 2 < 8) {
                    const int q = GSPLIT2 + (i - GST) / 2;
                    if ((i - GST) & 1) { gv[q].z = gate_pair(xv[q].z, ghr[q], ghm[q]); gv[q].w = gate_pair(xv[q].w, ghr[q], ghm[q]); asm volatile("" : "+r"(gv[q].z), "+r"(gv[q].w) :: "memory"); }
                    else { gv[q].x = gate_pair(xv[q].x, ghr[q], ghm[q]); gv[q].y = gate_pair(xv[q].y, ghr[q], ghm[q]); asm volatile("" : "+r"(gv[q].x), "+r"(gv[q].y) :: "memory"); }
                }
            }
        }
        wgmma_wait<0>();
        fence_regs(acc);
        TLP(tid == 0, 13); TLG(tid == 0, 52);
        {
            const uint32_t stg = sb + (wg * 64 + w4 * 16) * 128;
            const int rr = lane & 7;
#pragma unroll
            for (int c = 0; c < 4; c++) {
                const uint32_t a0 = stg + (c >> 1) * 16384 + rr * 128 + ((((c & 1) * 4 + (lane >> 3)) ^ rr) * 16);
                stsm(a0, pack_bf16(acc[c * 16 + 0], acc[c * 16 + 1]), pack_bf16(acc[c * 16 + 4], acc[c * 16 + 5]),
                     pack_bf16(acc[c * 16 + 8], acc[c * 16 + 9]), pack_bf16(acc[c * 16 + 12], acc[c * 16 + 13]));
                stsm(a0 + 1024, pack_bf16(acc[c * 16 + 2], acc[c * 16 + 3]), pack_bf16(acc[c * 16 + 6], acc[c * 16 + 7]),
                     pack_bf16(acc[c * 16 + 10], acc[c * 16 + 11]), pack_bf16(acc[c * 16 + 14], acc[c * 16 + 15]));
            }
            __syncwarp();
#pragma unroll
            for (int i = 0; i < 8; i++) {
                const uint4 sv = lds128(rowc + i * 256 + (((lane & 7) ^ ((2 * i + (lane >> 4)) & 7)) * 16));
                uint4 o;
                o.x = hadd2(xv[i].x, hmul2(sv.x, gv[i].x)); o.y = hadd2(xv[i].y, hmul2(sv.y, gv[i].y));
                o.z = hadd2(xv[i].z, hmul2(sv.z, gv[i].z)); o.w = hadd2(xv[i].w, hmul2(sv.w, gv[i].w));
                *reinterpret_cast<uint4*>(P.out + goff + (size_t)i * 2 * D_) = o;
            }
            const uint32_t sel = lds32(sb + SM_MISC);
            if ((int)(sel >> 4) == rb * 16 + (orow >> 4)) {
                mbar_wait(bars + 8 * B_Y, 0);
                if ((sel & 1u) == (uint32_t)(lane >> 4)) {
                    const int i = (sel & 15u) >> 1;
                    const uint4 sv = lds128(rowc + i * 256 + (((lane & 7) ^ (sel & 7u)) * 16));
                    const uint4 gq = lds128(sb + SM_Y + (lane & 15) * 16), xq = lds128(sb + SM_Y + 256 + (lane & 15) * 16);
                    *reinterpret_cast<uint4*>(P.out + goff + (size_t)i * 2 * D_) = make_uint4(hadd2(xq.x, hmul2(sv.x, gq.x)), hadd2(xq.y, hmul2(sv.y, gq.y)), hadd2(xq.z, hmul2(sv.z, gq.z)), hadd2(xq.w, hmul2(sv.w, gq.w)));
                }
            }
        }
        TLG(tid == 0, 53);
        if (tid == 0) { TL(14); TL_DUMP(); }
        if (blockIdx.x == 0 && tid == 0) asm volatile("st.relaxed.gpu.global.u32 [%0], %1;" :: "l"(&P.scr->epoch), "r"(lds32(sb + SM_MISC + 8) + 1u) : "memory");
    }
}

typedef CUresult (*PFN_encodeTiled)(CUtensorMap*, CUtensorMapDataType, cuuint32_t, void*, const cuuint64_t*, const cuuint64_t*,
                                    const cuuint32_t*, const cuuint32_t*, CUtensorMapInterleave, CUtensorMapSwizzle,
                                    CUtensorMapL2promotion, CUtensorMapFloatOOBfill);

void make_map(PFN_encodeTiled fn, CUtensorMap* m, const void* ptr, int rank, const cuuint64_t* dims, const cuuint64_t* strides, const cuuint32_t* box, CUtensorMapSwizzle sw) {
    const cuuint32_t es[5] = {1, 1, 1, 1, 1};
    fn(m, CU_TENSOR_MAP_DATA_TYPE_BFLOAT16, rank, const_cast<void*>(ptr), dims, strides, box, es, CU_TENSOR_MAP_INTERLEAVE_NONE,
       sw, CU_TENSOR_MAP_L2_PROMOTION_L2_256B, CU_TENSOR_MAP_FLOAT_OOB_FILL_NONE);
}
void make_2d(PFN_encodeTiled fn, CUtensorMap* m, const void* ptr, uint64_t rows, uint64_t cols, uint32_t box_rows, uint32_t box_cols, CUtensorMapSwizzle sw) {
    const cuuint64_t gd[2] = {cols, rows}, gs[1] = {cols * 2};
    const cuuint32_t bd[2] = {box_cols, box_rows};
    make_map(fn, m, ptr, 2, gd, gs, bd, sw);
}

}

extern "C" void kernel_launch(void* const* d_in, const int* in_sizes, int n_in, void* d_out, int out_size) {
    (void)in_sizes; (void)n_in; (void)out_size;
    static PFN_encodeTiled fn = nullptr;
    static void* o_ptr = nullptr;
    static void* scr_ptr = nullptr;
    static void* tl_ptr = nullptr;
    if (!fn) {
        void* p = nullptr;
        cudaDriverEntryPointQueryResult st;
        cudaGetDriverEntryPoint("cuTensorMapEncodeTiled", &p, cudaEnableDefault, &st);
        fn = (PFN_encodeTiled)p;
        cudaGetSymbolAddress(&o_ptr, g_o);
        cudaGetSymbolAddress(&scr_ptr, g_scr);
        cudaFuncSetAttribute(fused_kernel, cudaFuncAttributeMaxDynamicSharedMemorySize, SM_TOTAL);
    }
    CUtensorMap tmX, tmW, tmPhi, tmWo, tmO, tmX2;
    SideMaps tmS;
    make_2d(fn, &tmX, d_in[0], S_, D_, 256, 64, CU_TENSOR_MAP_SWIZZLE_128B);
    {
        const cuuint64_t gd[3] = {1024, 1024, 3}, gs[2] = {6144, 2048};
        const cuuint32_t bd[3] = {64, 64, 3};
        make_map(fn, &tmW, d_in[1], 3, gd, gs, bd, CU_TENSOR_MAP_SWIZZLE_128B);
    }
    make_2d(fn, &tmS.wc, d_in[1], D_, 3 * D_, 32, 64, CU_TENSOR_MAP_SWIZZLE_NONE);
    make_2d(fn, &tmPhi, d_in[2], 1024, 32, 64, 32, CU_TENSOR_MAP_SWIZZLE_64B);
    make_2d(fn, &tmS.wg, d_in[6], D_, F_, 32, 32, CU_TENSOR_MAP_SWIZZLE_NONE);
    make_2d(fn, &tmS.wu, d_in[7], D_, F_, 32, 32, CU_TENSOR_MAP_SWIZZLE_NONE);
    {
        const cuuint64_t gd[3] = {64, F_, 16}, gs[2] = {2048, 128};
        const cuuint32_t bd[3] = {64, 32, 8};
        make_map(fn, &tmS.wd8, d_in[8], 3, gd, gs, bd, CU_TENSOR_MAP_SWIZZLE_128B);
    }
    {
        const cuuint64_t gd[4] = {64, 64, 16, 16}, gs[3] = {2048, 64 * 2048, 128};
        const cuuint32_t bd[4] = {64, 32, 2, 2};
        make_map(fn, &tmWo, d_in[3], 4, gd, gs, bd, CU_TENSOR_MAP_SWIZZLE_128B);
    }
    make_2d(fn, &tmO, o_ptr, 2 * S_, D_, 128, 64, CU_TENSOR_MAP_SWIZZLE_128B);
    make_2d(fn, &tmX2, d_in[0], S_, D_, 128, 64, CU_TENSOR_MAP_SWIZZLE_128B);
    Params P;
    P.x = (const __nv_bfloat16*)d_in[0];
    P.wr = (const __nv_bfloat16*)d_in[5];
    P.wqkv = (const __nv_bfloat16*)d_in[1];
    P.wg = (const __nv_bfloat16*)d_in[6];
    P.wu = (const __nv_bfloat16*)d_in[7];
    P.wd = (const __nv_bfloat16*)d_in[8];
    P.wo = (const __nv_bfloat16*)d_in[3];
    P.out = (__nv_bfloat16*)d_out;
    P.o = (__nv_bfloat16*)o_ptr;
    P.scr = (Scratch*)scr_ptr;
    P.tl = (unsigned long long*)tl_ptr;
    cudaLaunchConfig_t cfg = {};
    cfg.gridDim = dim3(NCTA); cfg.blockDim = dim3(NTHREADS); cfg.dynamicSmemBytes = SM_TOTAL; cfg.stream = cudaStreamPerThread;
    cudaLaunchAttribute at[1];
    at[0].id = cudaLaunchAttributeCooperative; at[0].val.cooperative = 1;
    cfg.attrs = at; cfg.numAttrs = 1;
    cudaLaunchKernelEx(&cfg, fused_kernel, P, tmX, tmW, tmX2, tmS, tmPhi, tmWo, tmO);
}
```

```cpp
#include <cuda_runtime.h>
#include <cuda_bf16.h>
#include <cuda.h>
#include <stdint.h>

namespace {

constexpr int S_ = 2048, D_ = 1024, F_ = 3584;
constexpr int NCTA = 128, NTHREADS = 384;
#define OREL 2
#define OSTAG 12
#define OARR 3
#define NC0 3
#define NC2 4
#define NG0 12
#define NG1 12
#define GSPLIT 1
#define GSPLIT2 2
#define GST 3
#define SARR 3
#define JWO 12

constexpr int STAGE = 57344;
constexpr int SM_PHI = 0;
constexpr int SM_V = 131072;
constexpr int SM_AX = 172032;
constexpr int SM_BX = 176128;
constexpr int SM_SP = 172032;
constexpr int SM_FB = 180224;
constexpr int SM_XS = 221184;
constexpr int SM_KVOP = 172032;
constexpr int SM_MD = 223232;
constexpr int SM_RS = 224256;
constexpr int SM_Y = 225280;
constexpr int SM_GU = 225536;
constexpr int SM_MISC = 226688;
constexpr int SM_H = 179200;
constexpr int SM_BARS = 226816;
constexpr int SM_WPHI = 227840;
constexpr int SM_TOTAL = 232448;

constexpr int B_FULL = 0, B_EMPTY = 3, B_OF = 6, B_SD = 22, B_O = 33, B_PHI = 35, B_T = 37, B_WPHI = 38, B_Y = 39, B_KV = 40, B_LN = 42, B_S1 = 43, B_FF = 44, B_X = 54, B_C1 = 55, B_DN = 56, B_XS = 58, B_COUNT = 59, B_XR = 59;
constexpr int NB_KV = 1, NB_FFN = 2, NB_AUX = 3, NB_LEAD = 4, NB_STAG = 5;
__device__ __forceinline__ int o_slot(int i) { const int r = i % 5; return r == 4 ? 10 : r; }
__device__ __forceinline__ int wo_slot(int i) { const int r = i % 7; return r == 6 ? 11 : 4 + r; }

struct __align__(128) Acc {
    float4 cs[48 * 8 * 3];
    float4 y[4 * 4 * 3 * 32];
};
constexpr int ACC_VEC_PER_CTA = (int)(sizeof(Acc) / 16 / NCTA);
static_assert(sizeof(Acc) == ACC_VEC_PER_CTA * 16 * NCTA && ACC_VEC_PER_CTA <= 32, "");
struct __align__(128) Scratch {
    Acc acc[2];
    uint4 kv[32 * 4 * 3 * 32];
    unsigned hint[8 * 32];
    unsigned cnt_o[8 * 128];
    uint2 rows[S_];
    uint4 best[NCTA];
    unsigned epoch;
};
__device__ Scratch g_scr;
__device__ __align__(1024) __nv_bfloat16 g_o[2 * S_ * D_];

#define TL(e) do {} while (0)
#define TLP(c, e) do {} while (0)
#define TLG(c, e) do {} while (0)
#define TL_DUMP() do {} while (0)

struct SideMaps { CUtensorMap wc, wg, wu, wd8; };
struct Params {
    const __nv_bfloat16* x;
    const __nv_bfloat16* wr;
    const __nv_bfloat16* wqkv;
    const __nv_bfloat16* wg;
    const __nv_bfloat16* wu;
    const __nv_bfloat16* wd;
    const __nv_bfloat16* wo;
    __nv_bfloat16* out;
    __nv_bfloat16* o;
    Scratch* scr;
    unsigned long long* tl;
};

__device__ __forceinline__ bool elect_one() {
    uint32_t p; asm volatile("{\n.reg .pred q;\nelect.sync _|q, 0xffffffff;\nselp.u32 %0, 1, 0, q;\n}" : "=r"(p)); return p;
}
__device__ __forceinline__ uint32_t smem_u32(const void* p) { return (uint32_t)__cvta_generic_to_shared(p); }
__device__ __forceinline__ void mbar_init(uint32_t bar, uint32_t cnt) { asm volatile("mbarrier.init.shared::cta.b64 [%0], %1;" :: "r"(bar), "r"(cnt) : "memory"); }
__device__ __forceinline__ void mbar_expect_tx(uint32_t bar, uint32_t bytes) { asm volatile("mbarrier.arrive.expect_tx.shared::cta.b64 _, [%0], %1;" :: "r"(bar), "r"(bytes) : "memory"); }
__device__ __forceinline__ void mbar_arrive_if(bool p, uint32_t bar) {
    asm volatile("{\n.reg .pred q;\nsetp.ne.b32 q, %1, 0;\n@q mbarrier.arrive.shared::cta.b64 _, [%0];\n}" :: "r"(bar), "r"((int)p) : "memory");
}
__device__ __forceinline__ void mbar_wait(uint32_t bar, uint32_t parity) {
    asm volatile("{\n.reg .pred p;\n.reg .u32 n;\nmov.u32 n, 0;\n"
                 "WAIT_LOOP:\nmbarrier.try_wait.parity.shared::cta.b64 p, [%0], %1;\n@p bra WAIT_DONE;\n"
                 "add.u32 n, n, 1;\nsetp.lt.u32 p, n, 0x40000;\n@p bra WAIT_LOOP;\nWAIT_DONE:\n}" :: "r"(bar), "r"(parity) : "memory");
}
__device__ __forceinline__ void tma_2d(uint32_t dst, const CUtensorMap* tm, uint32_t bar, int c0, int c1) {
    asm volatile("cp.async.bulk.tensor.2d.shared::cluster.global.mbarrier::complete_tx::bytes [%0], [%1, {%3, %4}], [%2];"
        :: "r"(dst), "l"(tm), "r"(bar), "r"(c0), "r"(c1) : "memory");
}
__device__ __forceinline__ void tma_3d(uint32_t dst, const CUtensorMap* tm, uint32_t bar, int c0, int c1, int c2) {
    asm volatile("cp.async.bulk.tensor.3d.shared::cluster.global.mbarrier::complete_tx::bytes [%0], [%1, {%3, %4, %5}], [%2];"
        :: "r"(dst), "l"(tm), "r"(bar), "r"(c0), "r"(c1), "r"(c2) : "memory");
}
__device__ __forceinline__ void tma_4d(uint32_t dst, const CUtensorMap* tm, uint32_t bar, int c0, int c1, int c2, int c3) {
    asm volatile("cp.async.bulk.tensor.4d.shared::cluster.global.mbarrier::complete_tx::bytes [%0], [%1, {%3, %4, %5, %6}], [%2];"
        :: "r"(dst), "l"(tm), "r"(bar), "r"(c0), "r"(c1), "r"(c2), "r"(c3) : "memory");
}
__device__ __forceinline__ void prefetch_l2(const void* p, uint32_t bytes) { asm volatile("cp.async.bulk.prefetch.L2.global [%0], %1;" :: "l"(p), "r"(bytes) : "memory"); }
__device__ __forceinline__ void wgmma_fence() { asm volatile("wgmma.fence.sync.aligned;" ::: "memory"); }
__device__ __forceinline__ void wgmma_commit() { asm volatile("wgmma.commit_group.sync.aligned;" ::: "memory"); }
template <int N> __device__ __forceinline__ void wgmma_wait() { asm volatile("wgmma.wait_group.sync.aligned %0;" :: "n"(N) : "memory"); }
template <int N> __device__ __forceinline__ void fence_regs(float (&a)[N]) {
#pragma unroll
    for (int i = 0; i < N; i++) asm volatile("" : "+f"(a[i]) :: "memory");
}
template <int N> __device__ __forceinline__ void fence_regs(uint32_t (&a)[N]) {
#pragma unroll
    for (int i = 0; i < N; i++) asm volatile("" : "+r"(a[i]) :: "memory");
}
__device__ __forceinline__ uint64_t desc_from(uint32_t lo, uint32_t hi) { uint64_t d; asm("mov.b64 %0, {%1, %2};" : "=l"(d) : "r"(lo), "r"(hi)); return d; }
__device__ __forceinline__ uint32_t dlo(uint32_t addr, uint32_t lbo) { return ((addr & 0x3FFFF) >> 4) | ((lbo >> 4) << 16); }
__device__ __forceinline__ void nb_sync(int id, int cnt) { asm volatile("bar.sync %0, %1;" :: "r"(id), "r"(cnt) : "memory"); }
__device__ __forceinline__ void nb_arrive(int id, int cnt) { asm volatile("bar.arrive %0, %1;" :: "r"(id), "r"(cnt) : "memory"); }
__device__ __forceinline__ void fence_async_smem() { asm volatile("fence.proxy.async.shared::cta;" ::: "memory"); }
__device__ __forceinline__ void red_v4(float4* p, float a, float b, float c, float d) {
    asm volatile("red.relaxed.gpu.global.add.v4.f32 [%0], {%1, %2, %3, %4};" :: "l"(p), "f"(a), "f"(b), "f"(c), "f"(d) : "memory");
}
__device__ __forceinline__ float4 ld_gpu(const float4* p) {
    float4 v; asm volatile("ld.relaxed.gpu.global.v4.f32 {%0, %1, %2, %3}, [%4];" : "=f"(v.x), "=f"(v.y), "=f"(v.z), "=f"(v.w) : "l"(p) : "memory"); return v;
}
__device__ __forceinline__ uint4 ld_gpu(const uint4* p) {
    uint4 v; asm volatile("ld.relaxed.gpu.global.v4.u32 {%0, %1, %2, %3}, [%4];" : "=r"(v.x), "=r"(v.y), "=r"(v.z), "=r"(v.w) : "l"(p) : "memory"); return v;
}
__device__ __forceinline__ void poll_counter(const unsigned* p, unsigned target) {
    unsigned it = 0, v;
#pragma unroll 1
    do {
        asm volatile("ld.acquire.gpu.global.u32 %0, [%1];" : "=r"(v) : "l"(p) : "memory");
    } while (v < target && ++it < (1u << 20));
}
__device__ __forceinline__ uint32_t pack_bf16(float lo, float hi) { uint32_t r; asm("cvt.rn.bf16x2.f32 %0, %1, %2;" : "=r"(r) : "f"(hi), "f"(lo)); return r; }
__device__ __forceinline__ uint32_t pack_f16(float lo, float hi) { uint32_t r; asm("cvt.rn.f16x2.f32 %0, %1, %2;" : "=r"(r) : "f"(hi), "f"(lo)); return r; }
__device__ __forceinline__ float2 unpack_f16(uint32_t v) { float2 r; asm("{\n.reg .f16 l, h;\nmov.b32 {l, h}, %2;\ncvt.f32.f16 %0, l;\ncvt.f32.f16 %1, h;\n}" : "=f"(r.x), "=f"(r.y) : "r"(v)); return r; }
__device__ __forceinline__ float bf_lo(uint32_t v) { return __uint_as_float(v << 16); }
__device__ __forceinline__ float bf_hi(uint32_t v) { return __uint_as_float(v & 0xFFFF0000u); }
__device__ __forceinline__ float round_bf16(float v) { return bf_lo(pack_bf16(v, 0.f)); }
__device__ __forceinline__ float ex2(float v) { float r; asm("ex2.approx.ftz.f32 %0, %1;" : "=f"(r) : "f"(v)); return r; }
__device__ __forceinline__ float rcp(float v) { float r; asm("rcp.approx.ftz.f32 %0, %1;" : "=f"(r) : "f"(v)); return r; }
__device__ __forceinline__ float sqrt_a(float v) { float r; asm("sqrt.approx.f32 %0, %1;" : "=f"(r) : "f"(v)); return r; }
__device__ __forceinline__ void stsm(uint32_t addr, uint32_t r0, uint32_t r1, uint32_t r2, uint32_t r3) {
    asm volatile("stmatrix.sync.aligned.m8n8.x4.shared.b16 [%0], {%1, %2, %3, %4};" :: "r"(addr), "r"(r0), "r"(r1), "r"(r2), "r"(r3) : "memory");
}
__device__ __forceinline__ void stsm_t(uint32_t addr, uint32_t r0, uint32_t r1, uint32_t r2, uint32_t r3) {
    asm volatile("stmatrix.sync.aligned.m8n8.x4.trans.shared.b16 [%0], {%1, %2, %3, %4};" :: "r"(addr), "r"(r0), "r"(r1), "r"(r2), "r"(r3) : "memory");
}
__device__ __forceinline__ uint4 lds128(uint32_t addr) {
    uint4 v; asm volatile("ld.shared.v4.u32 {%0, %1, %2, %3}, [%4];" : "=r"(v.x), "=r"(v.y), "=r"(v.z), "=r"(v.w) : "r"(addr) : "memory"); return v;
}
__device__ __forceinline__ void sts128(uint32_t addr, uint32_t a, uint32_t b, uint32_t c, uint32_t d) {
    asm volatile("st.shared.v4.u32 [%0], {%1, %2, %3, %4};" :: "r"(addr), "r"(a), "r"(b), "r"(c), "r"(d) : "memory");
}
__device__ __forceinline__ void sts64(uint32_t addr, uint32_t a, uint32_t b) { asm volatile("st.shared.v2.u32 [%0], {%1, %2};" :: "r"(addr), "r"(a), "r"(b) : "memory"); }
__device__ __forceinline__ uint32_t lds32(uint32_t addr) { uint32_t v; asm volatile("ld.shared.u32 %0, [%1];" : "=r"(v) : "r"(addr) : "memory"); return v; }
__device__ __forceinline__ float ldsf(uint32_t addr) { return __uint_as_float(lds32(addr)); }
__device__ __forceinline__ void sts32(uint32_t addr, uint32_t v) { asm volatile("st.shared.u32 [%0], %1;" :: "r"(addr), "r"(v) : "memory"); }
__device__ __forceinline__ uint32_t hmul2(uint32_t a, uint32_t b) { uint32_t r; asm("mul.rn.bf16x2 %0, %1, %2;" : "=r"(r) : "r"(a), "r"(b)); return r; }
__device__ __forceinline__ uint32_t hadd2(uint32_t a, uint32_t b) { uint32_t r; asm("add.rn.bf16x2 %0, %1, %2;" : "=r"(r) : "r"(a), "r"(b)); return r; }
__device__ __forceinline__ uint32_t hsub2(uint32_t a, uint32_t b) { uint32_t r; asm("sub.rn.bf16x2 %0, %1, %2;" : "=r"(r) : "r"(a), "r"(b)); return r; }

__device__ __forceinline__ void wgmma_ss_n192_tb(float (&d)[96], uint64_t da, uint64_t db, int scale_d) {
    asm volatile(
        "{\n.reg .pred p;\nsetp.ne.b32 p, %98, 0;\n"
        "wgmma.mma_async.sync.aligned.m64n192k16.f32.bf16.bf16 "
        "{%0, %1, %2, %3, %4, %5, %6, %7, %8, %9, %10, %11, %12, %13, %14, %15, %16, %17, %18, %19, %20, %21, %22, %23, %24, %25, %26, %27, %28, %29, %30, %31, %32, %33, %34, %35, %36, %37, %38, %39, %40, %41, %42, %43, %44, %45, %46, %47, %48, %49, %50, %51, %52, %53, %54, %55, %56, %57, %58, %59, %60, %61, %62, %63, %64, %65, %66, %67, %68, %69, %70, %71, %72, %73, %74, %75, %76, %77, %78, %79, %80, %81, %82, %83, %84, %85, %86, %87, %88, %89, %90, %91, %92, %93, %94, %95}, %96, %97, p, 1, 1, 0, 1;\n}\n"
        : "+f"(d[0]), "+f"(d[1]), "+f"(d[2]), "+f"(d[3]), "+f"(d[4]), "+f"(d[5]), "+f"(d[6]), "+f"(d[7]), "+f"(d[8]), "+f"(d[9]), "+f"(d[10]), "+f"(d[11]), "+f"(d[12]), "+f"(d[13]), "+f"(d[14]), "+f"(d[15]), "+f"(d[16]), "+f"(d[17]), "+f"(d[18]), "+f"(d[19]), "+f"(d[20]), "+f"(d[21]), "+f"(d[22]), "+f"(d[23]), "+f"(d[24]), "+f"(d[25]), "+f"(d[26]), "+f"(d[27]), "+f"(d[28]), "+f"(d[29]), "+f"(d[30]), "+f"(d[31]), "+f"(d[32]), "+f"(d[33]), "+f"(d[34]), "+f"(d[35]), "+f"(d[36]), "+f"(d[37]), "+f"(d[38]), "+f"(d[39]), "+f"(d[40]), "+f"(d[41]), "+f"(d[42]), "+f"(d[43]), "+f"(d[44]), "+f"(d[45]), "+f"(d[46]), "+f"(d[47]), "+f"(d[48]), "+f"(d[49]), "+f"(d[50]), "+f"(d[51]), "+f"(d[52]), "+f"(d[53]), "+f"(d[54]), "+f"(d[55]), "+f"(d[56]), "+f"(d[57]), "+f"(d[58]), "+f"(d[59]), "+f"(d[60]), "+f"(d[61]), "+f"(d[62]), "+f"(d[63]), "+f"(d[64]), "+f"(d[65]), "+f"(d[66]), "+f"(d[67]), "+f"(d[68]), "+f"(d[69]), "+f"(d[70]), "+f"(d[71]), "+f"(d[72]), "+f"(d[73]), "+f"(d[74]), "+f"(d[75]), "+f"(d[76]), "+f"(d[77]), "+f"(d[78]), "+f"(d[79]), "+f"(d[80]), "+f"(d[81]), "+f"(d[82]), "+f"(d[83]), "+f"(d[84]), "+f"(d[85]), "+f"(d[86]), "+f"(d[87]), "+f"(d[88]), "+f"(d[89]), "+f"(d[90]), "+f"(d[91]), "+f"(d[92]), "+f"(d[93]), "+f"(d[94]), "+f"(d[95])
        : "l"(da), "l"(db), "r"(scale_d));
}
__device__ __forceinline__ void wgmma_ss_n128_tb(float (&d)[64], uint64_t da, uint64_t db, int scale_d) {
    asm volatile(
        "{\n.reg .pred p;\nsetp.ne.b32 p, %66, 0;\n"
        "wgmma.mma_async.sync.aligned.m64n128k16.f32.bf16.bf16 "
        "{%0, %1, %2, %3, %4, %5, %6, %7, %8, %9, %10, %11, %12, %13, %14, %15, %16, %17, %18, %19, %20, %21, %22, %23, %24, %25, %26, %27, %28, %29, %30, %31, %32, %33, %34, %35, %36, %37, %38, %39, %40, %41, %42, %43, %44, %45, %46, %47, %48, %49, %50, %51, %52, %53, %54, %55, %56, %57, %58, %59, %60, %61, %62, %63}, %64, %65, p, 1, 1, 0, 1;\n}\n"
        : "+f"(d[0]), "+f"(d[1]), "+f"(d[2]), "+f"(d[3]), "+f"(d[4]), "+f"(d[5]), "+f"(d[6]), "+f"(d[7]), "+f"(d[8]), "+f"(d[9]), "+f"(d[10]), "+f"(d[11]), "+f"(d[12]), "+f"(d[13]), "+f"(d[14]), "+f"(d[15]), "+f"(d[16]), "+f"(d[17]), "+f"(d[18]), "+f"(d[19]), "+f"(d[20]), "+f"(d[21]), "+f"(d[22]), "+f"(d[23]), "+f"(d[24]), "+f"(d[25]), "+f"(d[26]), "+f"(d[27]), "+f"(d[28]), "+f"(d[29]), "+f"(d[30]), "+f"(d[31]), "+f"(d[32]), "+f"(d[33]), "+f"(d[34]), "+f"(d[35]), "+f"(d[36]), "+f"(d[37]), "+f"(d[38]), "+f"(d[39]), "+f"(d[40]), "+f"(d[41]), "+f"(d[42]), "+f"(d[43]), "+f"(d[44]), "+f"(d[45]), "+f"(d[46]), "+f"(d[47]), "+f"(d[48]), "+f"(d[49]), "+f"(d[50]), "+f"(d[51]), "+f"(d[52]), "+f"(d[53]), "+f"(d[54]), "+f"(d[55]), "+f"(d[56]), "+f"(d[57]), "+f"(d[58]), "+f"(d[59]), "+f"(d[60]), "+f"(d[61]), "+f"(d[62]), "+f"(d[63])
        : "l"(da), "l"(db), "r"(scale_d));
}
__device__ __forceinline__ void wgmma_ss_n40(float (&d)[20], uint64_t da, uint64_t db, int scale_d) {
    asm volatile(
        "{\n.reg .pred p;\nsetp.ne.b32 p, %22, 0;\n"
        "wgmma.mma_async.sync.aligned.m64n40k16.f32.bf16.bf16 "
        "{%0, %1, %2, %3, %4, %5, %6, %7, %8, %9, %10, %11, %12, %13, %14, %15, %16, %17, %18, %19}, %20, %21, p, 1, 1, 0, 0;\n}\n"
        : "+f"(d[0]), "+f"(d[1]), "+f"(d[2]), "+f"(d[3]), "+f"(d[4]), "+f"(d[5]), "+f"(d[6]), "+f"(d[7]), "+f"(d[8]), "+f"(d[9]), "+f"(d[10]), "+f"(d[11]), "+f"(d[12]), "+f"(d[13]), "+f"(d[14]), "+f"(d[15]), "+f"(d[16]), "+f"(d[17]), "+f"(d[18]), "+f"(d[19])
        : "l"(da), "l"(db), "r"(scale_d));
}
__device__ __forceinline__ void wgmma_ss_n8_ta(float (&d)[4], uint64_t da, uint64_t db, int scale_d) {
    asm volatile(
        "{\n.reg .pred p;\nsetp.ne.b32 p, %6, 0;\n"
        "wgmma.mma_async.sync.aligned.m64n8k16.f32.bf16.bf16 "
        "{%0, %1, %2, %3}, %4, %5, p, 1, 1, 1, 0;\n}\n"
        : "+f"(d[0]), "+f"(d[1]), "+f"(d[2]), "+f"(d[3])
        : "l"(da), "l"(db), "r"(scale_d));
}
__device__ __forceinline__ void wgmma_rs_n32_tb(float (&d)[16], uint32_t a0, uint32_t a1, uint32_t a2, uint32_t a3, uint64_t db, int scale_d) {
    asm volatile(
        "{\n.reg .pred p;\nsetp.ne.b32 p, %21, 0;\n"
        "wgmma.mma_async.sync.aligned.m64n32k16.f32.bf16.bf16 "
        "{%0, %1, %2, %3, %4, %5, %6, %7, %8, %9, %10, %11, %12, %13, %14, %15}, {%16, %17, %18, %19}, %20, p, 1, 1, 1;\n}\n"
        : "+f"(d[0]), "+f"(d[1]), "+f"(d[2]), "+f"(d[3]), "+f"(d[4]), "+f"(d[5]), "+f"(d[6]), "+f"(d[7]), "+f"(d[8]), "+f"(d[9]), "+f"(d[10]), "+f"(d[11]), "+f"(d[12]), "+f"(d[13]), "+f"(d[14]), "+f"(d[15])
        : "r"(a0), "r"(a1), "r"(a2), "r"(a3), "l"(db), "r"(scale_d));
}
__device__ __forceinline__ void wgmma_rs_n40_tb(float (&d)[20], uint32_t a0, uint32_t a1, uint32_t a2, uint32_t a3, uint64_t db, int scale_d) {
    asm volatile(
        "{\n.reg .pred p;\nsetp.ne.b32 p, %25, 0;\n"
        "wgmma.mma_async.sync.aligned.m64n40k16.f32.bf16.bf16 "
        "{%0, %1, %2, %3, %4, %5, %6, %7, %8, %9, %10, %11, %12, %13, %14, %15, %16, %17, %18, %19}, {%20, %21, %22, %23}, %24, p, 1, 1, 1;\n}\n"
        : "+f"(d[0]), "+f"(d[1]), "+f"(d[2]), "+f"(d[3]), "+f"(d[4]), "+f"(d[5]), "+f"(d[6]), "+f"(d[7]), "+f"(d[8]), "+f"(d[9]), "+f"(d[10]), "+f"(d[11]), "+f"(d[12]), "+f"(d[13]), "+f"(d[14]), "+f"(d[15]), "+f"(d[16]), "+f"(d[17]), "+f"(d[18]), "+f"(d[19])
        : "r"(a0), "r"(a1), "r"(a2), "r"(a3), "l"(db), "r"(scale_d));
}

constexpr float LOG2E = 1.4426950408889634f;
constexpr uint32_t DH128 = (1024u >> 4) | (1u << 30);

__device__ __forceinline__ float silu_f(float v) { return v * rcp(1.0f + ex2(-v * LOG2E)); }
__device__ __forceinline__ float silu_t(float v) { const float h = 0.5f * v; float th; asm("tanh.approx.f32 %0, %1;" : "=f"(th) : "f"(h)); return fmaf(h, th, h); }
__device__ __forceinline__ uint32_t ln_pair(uint32_t xv, uint32_t m2, float rs) { const uint32_t a = hsub2(xv, m2); return pack_bf16(bf_lo(a) * rs, bf_hi(a) * rs); }
__device__ __forceinline__ uint32_t silu_pair(uint32_t v) { return pack_bf16(silu_t(bf_lo(v)), silu_t(bf_hi(v))); }
__device__ __forceinline__ uint32_t gate_pair(uint32_t v, float hr, float hm) {
    const float a = fmaf(bf_lo(v), hr, hm), b = fmaf(bf_hi(v), hr, hm);
    float ta, tb;
    asm("tanh.approx.f32 %0, %1;" : "=f"(ta) : "f"(a)); asm("tanh.approx.f32 %0, %1;" : "=f"(tb) : "f"(b));
    return pack_bf16(fmaf(a, ta, a), fmaf(b, tb, b));
}
__device__ __forceinline__ void gate_item(uint4& v, uint32_t sb, int row) {
    const float hr = 0.5f * ldsf(sb + SM_RS + row * 4), hm = -bf_lo(lds32(sb + SM_MD + row * 4)) * hr;
    v.x = gate_pair(v.x, hr, hm); v.y = gate_pair(v.y, hr, hm); v.z = gate_pair(v.z, hr, hm); v.w = gate_pair(v.w, hr, hm);
    asm volatile("" : "+r"(v.x), "+r"(v.y), "+r"(v.z), "+r"(v.w) :: "memory");
}
__device__ __forceinline__ uint32_t hfma2(uint32_t a, uint32_t b, uint32_t c) { uint32_t r; asm("fma.rn.bf16x2 %0, %1, %2, %3;" : "=r"(r) : "r"(a), "r"(b), "r"(c)); return r; }
__device__ __forceinline__ uint32_t dup_lo(uint32_t v) { uint32_t r; asm("{\n.reg .b16 l, h;\nmov.b32 {l, h}, %1;\nmov.b32 %0, {l, l};\n}" : "=r"(r) : "r"(v)); return r; }
__device__ __forceinline__ uint32_t dup_hi(uint32_t v) { uint32_t r; asm("{\n.reg .b16 l, h;\nmov.b32 {l, h}, %1;\nmov.b32 %0, {h, h};\n}" : "=r"(r) : "r"(v)); return r; }
template <bool SQ> __device__ __forceinline__ void colsum8(float (&a)[8], float& sq, const uint4 (&v)[8]) {
    uint32_t q = 0;
#pragma unroll
    for (int i = 0; i < 8; i++) {
        a[0] += bf_lo(v[i].x); a[1] += bf_hi(v[i].x); a[2] += bf_lo(v[i].y); a[3] += bf_hi(v[i].y);
        a[4] += bf_lo(v[i].z); a[5] += bf_hi(v[i].z); a[6] += bf_lo(v[i].w); a[7] += bf_hi(v[i].w);
        if (SQ) q = hfma2(v[i].x, v[i].x, hfma2(v[i].y, v[i].y, hfma2(v[i].z, v[i].z, hfma2(v[i].w, v[i].w, q))));
    }
    if (SQ) sq += bf_lo(q) + bf_hi(q);
}
__device__ __forceinline__ void hfma8(uint4& h, uint32_t w, const uint4& v) { h.x = hfma2(v.x, w, h.x); h.y = hfma2(v.y, w, h.y); h.z = hfma2(v.z, w, h.z); h.w = hfma2(v.w, w, h.w); }
template <int ST, class F>
__device__ __forceinline__ void gemv_run(float (&a)[8], int cnt, int b, uint32_t ph, uint32_t lo, uint32_t wa, uint32_t ws, uint32_t bar0, uint32_t pin, F done) {
    uint32_t rdy = 0;
#pragma unroll 1
    for (int m = 0; m < cnt; m++) {
        if (!rdy) mbar_wait(bar0 + b * 8, ph);
        uint4 A[8];
        const uint4 w = lds128(wa);
#pragma unroll
        for (int i = 0; i < 8; i++) A[i] = lds128(lo + b * 4096 + i * ST);
        const int bc = b;
        if (++b == 3) { b = 0; ph ^= 1; }
        asm volatile("{\n.reg .pred p;\nmbarrier.test_wait.parity.shared::cta.b64 p, [%1], %2;\nselp.u32 %0, 1, 0, p;\n}" : "=r"(rdy) : "r"(bar0 + b * 8), "r"(ph) : "memory");
        sts32(pin, 0u);
        wa += ws;
        uint4 h = make_uint4(0, 0, 0, 0);
        hfma8(h, dup_lo(w.x), A[0]); hfma8(h, dup_hi(w.x), A[1]); hfma8(h, dup_lo(w.y), A[2]); hfma8(h, dup_hi(w.y), A[3]);
        hfma8(h, dup_lo(w.z), A[4]); hfma8(h, dup_hi(w.z), A[5]); hfma8(h, dup_lo(w.w), A[6]); hfma8(h, dup_hi(w.w), A[7]);
        a[0] += bf_lo(h.x); a[1] += bf_hi(h.x); a[2] += bf_lo(h.y); a[3] += bf_hi(h.y);
        a[4] += bf_lo(h.z); a[5] += bf_hi(h.z); a[6] += bf_lo(h.w); a[7] += bf_hi(h.w);
        fence_regs(a);
        done(m, bc);
    }
}
template <int OFF> __device__ __forceinline__ void pack_head(const float (&acc)[96], uint32_t (&f)[8]) {
#pragma unroll
    for (int i = 0; i < 8; i++) f[i] = pack_bf16(acc[OFF + 2 * i], acc[OFF + 2 * i + 1]);
}
__device__ __forceinline__ void feat_mma(float (&p)[16], const uint32_t (&f)[8], uint32_t wlo) {
    constexpr uint32_t DH = (512u >> 4) | (2u << 30);
    wgmma_rs_n32_tb(p, f[0], f[1], f[2], f[3], desc_from(wlo, DH), 0);
    wgmma_rs_n32_tb(p, f[4], f[5], f[6], f[7], desc_from(wlo + 64, DH), 1);
}
template <int S> __device__ __forceinline__ void row_ext(const float (&p)[16], float& a, float& b) {
    auto op = [](float x, float y) { return S > 0 ? fmaxf(x, y) : fminf(x, y); };
    a = op(op(op(p[0], p[1]), op(p[4], p[5])), op(op(p[8], p[9]), op(p[12], p[13])));
    b = op(op(op(p[2], p[3]), op(p[6], p[7])), op(op(p[10], p[11]), op(p[14], p[15])));
#pragma unroll
    for (int o = 1; o <= 2; o <<= 1) { a = op(a, __shfl_xor_sync(0xffffffffu, a, o)); b = op(b, __shfl_xor_sync(0xffffffffu, b, o)); }
}
__device__ __forceinline__ void dual_exp(const float (&p)[16], float scA, float scB, uint32_t (&pos)[8], uint32_t (&neg)[8], uint32_t& chk) {
#pragma unroll
    for (int j = 0; j < 8; j += 2) {
        const float a0 = ex2(p[2 * j] * scA), a1 = ex2(p[2 * j + 1] * scA);
        const float b0 = ex2(p[2 * j + 2] * scB), b1 = ex2(p[2 * j + 3] * scB);
        const float pa = a0 * a1, pb = b0 * b1, R = rcp(pa * pb);
        const uint32_t r = pack_bf16(R * pb, R * pa);
        pos[j] = pack_bf16(a0, a1); pos[j + 1] = pack_bf16(b0, b1);
        neg[j] = hmul2(pos[j], dup_lo(r)); neg[j + 1] = hmul2(pos[j + 1], dup_hi(r));
        chk = hadd2(chk, hadd2(hadd2(pos[j], neg[j]), hadd2(pos[j + 1], neg[j + 1])));
    }
}
template <int S> __device__ __forceinline__ void exact_exp(const float (&p)[16], float scA, float scB, uint32_t (&o)[8]) {
    float mA, mB;
    row_ext<S>(p, mA, mB);
#pragma unroll
    for (int j = 0; j < 8; j++) {
        const float sc = S * ((j & 1) ? scB : scA), m = (j & 1) ? mB : mA;
        const float u = ex2((p[2 * j] - m) * sc), v = ex2((p[2 * j + 1] - m) * sc);
        o[j] = S > 0 ? pack_bf16(u, v) : pack_bf16(v, u);
    }
}
__device__ __forceinline__ void features(const float (&p0)[16], const float (&p1)[16], const float (&rs)[4],
                                         uint32_t (&pa)[8], uint32_t (&na)[8], uint32_t (&pb)[8], uint32_t (&nb)[8]) {
    uint32_t chk = 0;
    dual_exp(p0, rs[0] * LOG2E, rs[1] * LOG2E, pa, na, chk);
    dual_exp(p1, rs[2] * LOG2E, rs[3] * LOG2E, pb, nb, chk);
    if (__builtin_expect(!__all_sync(0xffffffffu, bf_lo(chk) + bf_hi(chk) < 1.0e9f), 0)) {
        exact_exp<1>(p0, rs[0] * LOG2E, rs[1] * LOG2E, pa); exact_exp<-1>(p0, rs[0] * LOG2E, rs[1] * LOG2E, na);
        exact_exp<1>(p1, rs[2] * LOG2E, rs[3] * LOG2E, pb); exact_exp<-1>(p1, rs[2] * LOG2E, rs[3] * LOG2E, nb);
    }
}
__device__ __forceinline__ float quad_sum(float v) { v += __shfl_xor_sync(0xffffffffu, v, 1); return v + __shfl_xor_sync(0xffffffffu, v, 2); }
__device__ __forceinline__ float key_block(const float (&p)[16], float rsA, float rsB, uint32_t d0, uint32_t d1, uint32_t off) {
    float r[8], sp[2], sn[2];
    uint32_t pos[8], neg[8];
    const float scA = rsA * LOG2E, scB = rsB * LOG2E;
#pragma unroll
    for (int j = 0; j < 8; j += 2) {
        const float a0 = ex2(p[2 * j] * scA), a1 = ex2(p[2 * j + 1] * scA);
        const float b0 = ex2(p[2 * j + 2] * scB), b1 = ex2(p[2 * j + 3] * scB);
        const float pa = a0 * a1, pb = b0 * b1, R = rcp(pa * pb), ta = a0 + a1, tb = b0 + b1;
        r[j] = R * pb; r[j + 1] = R * pa;
        if (j == 0) { sp[0] = ta; sp[1] = tb; sn[0] = r[0] * ta; sn[1] = r[1] * tb; }
        else { sp[0] += ta; sp[1] += tb; sn[0] = fmaf(r[j], ta, sn[0]); sn[1] = fmaf(r[j + 1], tb, sn[1]); }
        pos[j] = pack_bf16(a0, a1); pos[j + 1] = pack_bf16(b0, b1);
    }
    const float qa = quad_sum(sp[0]), qb = quad_sum(sp[1]), na = quad_sum(sn[0]), nb = quad_sum(sn[1]);
    const float iq = rcp(qa * qb), nA = rsA * rcp(na), nB = rsB * rcp(nb);
    const uint32_t fp = pack_bf16(rsA * qb * iq, rsB * qa * iq);
#pragma unroll
    for (int j = 0; j < 8; j += 2) {
        const uint32_t rn = pack_bf16(r[j] * nA, r[j + 1] * nB);
        neg[j] = hmul2(pos[j], dup_lo(rn)); neg[j + 1] = hmul2(pos[j + 1], dup_hi(rn));
        pos[j] = hmul2(pos[j], dup_lo(fp)); pos[j + 1] = hmul2(pos[j + 1], dup_hi(fp));
    }
    stsm_t(d0 + 4096, neg[0], neg[2], neg[4], neg[6]); stsm_t(d1 + 4096, neg[1], neg[3], neg[5], neg[7]);
    stsm_t(d0 + off, pos[0], pos[2], pos[4], pos[6]); stsm_t(d1 + off, pos[1], pos[3], pos[5], pos[7]);
    return (qa + qb) + (na + nb);
}
__device__ __forceinline__ void shift_max(float (&p)[16]) {
    float mA, mB;
    row_ext<1>(p, mA, mB);
#pragma unroll
    for (int j = 0; j < 16; j++) p[j] -= (j & 2) ? mB : mA;
}
__device__ __forceinline__ void key_head(float (&p0)[16], float (&p1)[16], const float (&rs)[4], uint32_t d0, uint32_t d1) {
    uint32_t st;
    asm volatile("mov.u32 %0, 0;" : "=r"(st));
    bool again;
#pragma unroll 1
    do {
        const uint32_t off = (st & 2u) << 11;
        const float chk = key_block(p0, rs[0], rs[1], d0, d1, off) + key_block(p1, rs[2], rs[3], d0 + 8192, d1 + 8192, off);
        again = st == 1u || (st == 0u && !__all_sync(0xffffffffu, chk < 1.0e9f));
        if (__builtin_expect(again, 0)) {
            if (st) {
#pragma unroll
                for (int j = 0; j < 16; j += 2) {
                    float t = p0[j]; p0[j] = -p0[j + 1]; p0[j + 1] = -t;
                    t = p1[j]; p1[j] = -p1[j + 1]; p1[j + 1] = -t;
                }
            }
            shift_max(p0); shift_max(p1);
            st++;
        }
        asm volatile("" ::: "memory");
    } while (again);
}
__device__ __forceinline__ void o_mma(float (&d)[20], float (&e)[20], const uint32_t (&pos)[8], const uint32_t (&neg)[8], uint32_t klo) {
    wgmma_rs_n40_tb(d, pos[0], pos[1], pos[2], pos[3], desc_from(klo, 1024u >> 4), 0);
    wgmma_rs_n40_tb(e, neg[0], neg[1], neg[2], neg[3], desc_from(klo + 32, 1024u >> 4), 0);
    wgmma_rs_n40_tb(d, pos[4], pos[5], pos[6], pos[7], desc_from(klo + 16, 1024u >> 4), 1);
    wgmma_rs_n40_tb(e, neg[4], neg[5], neg[6], neg[7], desc_from(klo + 48, 1024u >> 4), 1);
}
__device__ __forceinline__ void o_store(const float (&d)[20], const float (&e)[20], __nv_bfloat16* dst) {
    const float iA = rcp(fmaf(d[16], e[17], fmaf(e[16], d[17], 1e-6f * d[17] * e[17])));
    const float iB = rcp(fmaf(d[18], e[19], fmaf(e[18], d[19], 1e-6f * d[19] * e[19])));
    const float pA = e[17] * iA, nA = d[17] * iA, pB = e[19] * iB, nB = d[19] * iB;
    uint32_t oa[4], ob[4];
#pragma unroll
    for (int j = 0; j < 4; j++) {
        oa[j] = pack_bf16(fmaf(d[j * 4], pA, e[j * 4] * nA), fmaf(d[j * 4 + 1], pA, e[j * 4 + 1] * nA));
        ob[j] = pack_bf16(fmaf(d[j * 4 + 2], pB, e[j * 4 + 2] * nB), fmaf(d[j * 4 + 3], pB, e[j * 4 + 3] * nB));
    }
    *reinterpret_cast<uint4*>(dst) = make_uint4(oa[0] ? oa[0] : 0x8000u, oa[1], oa[2], oa[3]);
    *reinterpret_cast<uint4*>(dst + 8 * D_) = make_uint4(ob[0] ? ob[0] : 0x8000u, ob[1], ob[2], ob[3]);
}

template <int N> __device__ __forceinline__ void kv_gather(uint4 (&v)[3 * N], const uint4* src, uint32_t dst, int lane, float us) {
    unsigned it = 0;
#pragma unroll 1
    while (++it < (1u << 20)) {
        bool ok = true;
#pragma unroll
        for (int j = 0; j < 3 * N; j++) ok = ok && (v[j].w >> 16) == 0x4800u;
        if (__all_sync(0xffffffffu, ok)) break;
#pragma unroll
        for (int j = 0; j < 3 * N; j++) v[j] = ld_gpu(src + j * 32);
    }
    dst += (lane >> 2) * 16;
    auto cv = [&](uint32_t w) { const float2 f = unpack_f16(w); return pack_bf16(f.x * us, f.y * us); };
#pragma unroll
    for (int n = 0; n < N; n++) {
        sts128(dst + (lane & 3) * 1024 + n * 256, cv(v[3 * n].x), cv(v[3 * n].y), cv(v[3 * n].z), cv(v[3 * n + 2].x));
        sts128(dst + (lane & 3) * 1024 + n * 256 + 128, cv(v[3 * n + 1].x), cv(v[3 * n + 1].y), cv(v[3 * n + 1].z), cv(v[3 * n + 2].y));
        sts32(dst + 4096 + n * 256 + (lane & 3) * 4, pack_bf16(unpack_f16(v[3 * n].w).x, 1.0f));
        sts32(dst + 4096 + n * 256 + 128 + (lane & 3) * 4, pack_bf16(unpack_f16(v[3 * n + 1].w).x, 1.0f));
    }
    fence_async_smem();
    __syncwarp();
}

__global__ void __launch_bounds__(NTHREADS, 1)
fused_kernel(const Params P, const __grid_constant__ CUtensorMap tmX, const __grid_constant__ CUtensorMap tmW, const __grid_constant__ CUtensorMap tmX2,
             const __grid_constant__ SideMaps tmS, const __grid_constant__ CUtensorMap tmPhi,
             const __grid_constant__ CUtensorMap tmWo, const __grid_constant__ CUtensorMap tmO) {
    extern __shared__ __align__(1024) uint8_t smem_raw[];
    constexpr uint32_t sb = 1024;
    if (smem_u32(smem_raw) != sb) return;
    constexpr uint32_t bars = sb + SM_BARS;
    const int rb = blockIdx.x >> 4, hp = blockIdx.x & 15;
    TLP(threadIdx.x == 32, 0); TLG(threadIdx.x == 32, 48);
    auto load_stage = [&](int s, int ks) {
        mbar_expect_tx(bars + 8 * (B_FULL + s), STAGE);
        tma_2d(sb + s * STAGE, &tmX, bars + 8 * (B_FULL + s), ks * 64, rb * 256);
        tma_3d(sb + s * STAGE + 32768, &tmW, bars + 8 * (B_FULL + s), hp * 64, ks * 64, 0);
    };
    if (threadIdx.x < 256) {
        const uint32_t t = threadIdx.x, r = t >> 3, sw = ((t ^ r) & 7) * 16;
        const __nv_bfloat16* wp = P.wqkv + (size_t)r * 3 * D_ + hp * 64 + (t & 7) * 8;
        const __nv_bfloat16* xp = P.x + (size_t)(rb * 256 + (t >> 7) * 128 + (r & 15)) * D_ + (t & 7) * 8;
#pragma unroll
        for (int i = 0; i < 3; i++) asm volatile("cp.async.cg.shared.global [%0], [%1], 16;" :: "r"(sb + 32768 + i * 8192 + r * 128 + sw), "l"(wp + i * D_) : "memory");
#pragma unroll
        for (int i = 0; i < 8; i++) asm volatile("cp.async.cg.shared.global [%0], [%1], 16;" :: "r"(sb + (t >> 7) * 16384 + ((r & 15) + i * 16) * 128 + sw), "l"(xp + i * 16 * D_) : "memory");
        asm volatile("cp.async.commit_group;" ::: "memory");
#pragma unroll
        for (int i = 0; i < 3; i++) asm volatile("cp.async.cg.shared.global [%0], [%1], 16;" :: "r"(sb + 36864 + i * 8192 + r * 128 + sw), "l"(wp + 96 * D_ + i * D_) : "memory");
        asm volatile("cp.async.commit_group;" ::: "memory");
    }
    const int tid = threadIdx.x, warp = __shfl_sync(0xffffffffu, tid >> 5, 0), lane = tid & 31;
    const bool elect = lane == 0;

    if (warp >= 8) {
        const int aw = warp - 9;
        auto load_o = [&](int i, unsigned par) {
            mbar_expect_tx(bars + 8 * (B_OF + i), 16384);
            tma_2d(sb + o_slot(i) * 16384, &tmO, bars + 8 * (B_OF + i), i * 64, par * S_ + rb * 256 + (hp & 1) * 128);
        };
        auto load_wo = [&](int i) {
            mbar_expect_tx(bars + 8 * (B_OF + i), 16384);
            tma_4d(sb + wo_slot(i) * 16384, &tmWo, bars + 8 * (B_OF + i), 0, (i >> 3) * 32, (i & 7) * 2, hp & 14);
        };
        if (warp == 9) {
            if (elect_one()) {
#pragma unroll
                for (int i = B_OF; i < B_COUNT; i++)
                    mbar_init(bars + 8 * i, i < B_SD ? 2 : (i < B_WPHI ? 8 : ((i < B_KV || i >= B_FF || i == B_LN) ? 1 : 4)));
                asm volatile("fence.mbarrier_init.release.cluster;" ::: "memory");
            }
        }
        if (warp == 8) {
            if (elect_one()) {
#pragma unroll
                for (int i = 0; i < 3; i++) { mbar_init(bars + 8 * (B_FULL + i), 1); mbar_init(bars + 8 * (B_EMPTY + i), 8); }
                mbar_init(bars + 8 * B_XR, 1);
                asm volatile("fence.mbarrier_init.release.cluster;" ::: "memory");
                asm volatile("mbarrier.arrive.shared::cta.b64 _, [%0];" :: "r"(bars + 8 * B_FULL) : "memory");
            }
            __syncwarp();
            nb_arrive(0, NTHREADS);
        } else {
            __syncwarp();
            nb_sync(0, NTHREADS);
        }
        asm volatile("setmaxnreg.dec.sync.aligned.u32 56;");
        if (warp == 8 && elect_one()) {
            load_stage(1, 1); load_stage(2, 2);
            mbar_expect_tx(bars + 8 * B_XR, 32768);
            asm volatile("cp.async.bulk.shared::cluster.global.mbarrier::complete_tx::bytes [%0], [%1], 32768, [%2];"
                         :: "r"(sb + SM_FB + 4096), "l"(P.x + (size_t)blockIdx.x * 16 * D_), "r"(bars + 8 * B_XR) : "memory");
        }
        __syncwarp();
        nb_sync(NB_KV, 128);
        unsigned epoch;
        asm volatile("ld.relaxed.gpu.global.u32 %0, [%1];" : "=r"(epoch) : "l"(&P.scr->epoch) : "memory");
        auto get_acc = [&]() { return &P.scr->acc[epoch & 1u]; };
        if (warp == 8) {
            epoch = __shfl_sync(0xffffffffu, epoch, 0);
            int s = 0, ph = 0;
#pragma unroll 1
            for (int j = 0; j < 15; j++) {
                mbar_wait(bars + 8 * (B_EMPTY + s), ph);
                if (elect_one()) {
                    if (j < 13) load_stage(s, j + 3);
                    if (j < 2) {
                        prefetch_l2(P.wqkv + (size_t)(256 + j * 384 + blockIdx.x * 3) * 3 * D_, 18432);
                    } else if (j < 10) {
                        if (j == 2) asm volatile("mbarrier.arrive.shared::cta.b64 _, [%0];" :: "r"(bars + 8 * B_FF) : "memory");
                        const size_t o = (size_t)((j - 2) * 128 + blockIdx.x) * F_;
                        prefetch_l2(P.wg + o, F_ * 2); prefetch_l2(P.wu + o, F_ * 2);
                    }
                    if (j == JWO) prefetch_l2(P.wo + (size_t)blockIdx.x * 8 * D_, 16384);
                    if (j == 12) {
                        asm volatile("prefetch.tensormap [%0];" :: "l"(&tmO) : "memory");
                        asm volatile("prefetch.tensormap [%0];" :: "l"(&tmS.wd8) : "memory");
                        asm volatile("prefetch.tensormap [%0];" :: "l"(&tmWo) : "memory");
                        mbar_expect_tx(bars + 8 * B_WPHI, 4096);
                        tma_2d(sb + SM_WPHI, &tmPhi, bars + 8 * B_WPHI, 0, hp * 64);
                    }
                    if (j >= 13) {
                        if (blockIdx.x >= 112 || j == 13) { load_wo(2 * j - 26); load_wo(2 * j - 25); }
                        else {
                            mbar_expect_tx(bars + 8 * (B_DN + 1), 32768);
                            tma_3d(sb + 6 * 16384, &tmS.wd8, bars + 8 * (B_DN + 1), 0, blockIdx.x * 32, 8);
                        }
                    }
                }
                __syncwarp();
                if (++s == 3) { s = 0; ph ^= 1; }
                if (j == 12 && hp == 0 && lane < 4) P.scr->hint[rb * 32 + lane] = 0u;
                if (j >= 3 && j < 11) {
                    uint4* zp = reinterpret_cast<uint4*>(P.o + (size_t)((~epoch & 1u) * S_ + blockIdx.x * 16 + (j - 3) * 2) * D_) + lane;
#pragma unroll
                    for (int i = 0; i < 2; i++) zp[i * 128] = make_uint4(0, 0, 0, 0);
                    if (j == 3 && lane < ACC_VEC_PER_CTA) reinterpret_cast<uint4*>(&P.scr->acc[~epoch & 1u])[blockIdx.x * ACC_VEC_PER_CTA + lane] = make_uint4(0, 0, 0, 0);
                }
            }
            TLP(elect, 20);
        } else {
            const bool ffn = blockIdx.x < 112;
            const uint32_t fbuf = sb + SM_FB + 4096 + aw * 12288, fbar = bars + 8 * (B_FF + 1 + aw * 3);
        const int nc = aw == 0 ? NC0 : (aw == 1 ? 12 - NC0 - NC2 : NC2), c0 = aw == 0 ? 0 : (aw == 1 ? NC0 : 12 - NC2);
        const int ng = !ffn ? 0 : (aw == 0 ? NG0 : (aw == 1 ? NG1 : 32 - NG0 - NG1)), g0 = aw == 0 ? 0 : (aw == 1 ? NG0 : NG0 + NG1);
        auto issue = [&](int i, int b) {
            __syncwarp();
            if (i < nc + ng && elect_one()) {
                mbar_expect_tx(fbar + b * 8, 4096);
                if (i < nc) {
                    tma_2d(fbuf + b * 4096, &tmS.wc, fbar + b * 8, ((c0 + i) >> 2) * 1024 + hp * 64, rb * 128 + ((c0 + i) & 3) * 32);
                } else {
                    tma_2d(fbuf + b * 4096, &tmS.wg, fbar + b * 8, blockIdx.x * 32, (g0 + i - nc) * 32);
                    tma_2d(fbuf + b * 4096 + 2048, &tmS.wu, fbar + b * 8, blockIdx.x * 32, (g0 + i - nc) * 32);
                }
            }
            __syncwarp();
        };
            {
                uint4 wv[4];
#pragma unroll
                for (int i = 0; i < 4; i++) wv[i] = __ldg(reinterpret_cast<const uint4*>(P.wr) + i * 32 + lane);
                const uint32_t* ww = reinterpret_cast<const uint32_t*>(wv);
                float sw = 0.f;
#pragma unroll
                for (int i = 0; i < 16; i++) sw += bf_lo(ww[i]) + bf_hi(ww[i]);
#pragma unroll 1
                for (int o = 16; o > 0; o >>= 1) sw += __shfl_xor_sync(0xffffffffu, sw, o);
                sts32(sb + SM_MISC + 20, __float_as_uint(sw));
                if (aw == 2) {
#pragma unroll
                    for (int i = 0; i < 3; i++) P.scr->kv[(hp * 8 + rb) * 96 + i * 32 + lane] = make_uint4(0, 0, 0, 0);
                    if (hp == 0) reinterpret_cast<uint4*>(&P.scr->cnt_o[rb * 128])[lane] = make_uint4(0, 0, 0, 0);
                    asm volatile("fence.acq_rel.gpu;" ::: "memory");
                    __syncwarp();
                }
                mbar_wait(bars + 8 * B_XR, 0);
#pragma unroll 1
                for (int r = aw * 6; r < min(aw * 6 + 6, 16); r++) {
                    const uint32_t buf = sb + SM_FB + 4096 + r * 2048;
                    uint4 xv[4];
                    uint32_t c2 = lds32(buf);
#pragma unroll
                    for (int i = 0; i < 4; i++) xv[i] = lds128(buf + i * 512 + lane * 16);
                    sts32(sb + SM_MISC + 12, 0u);
                    c2 = fabsf(bf_lo(c2) - bf_hi(c2)) < 0.25f * fabsf(bf_lo(c2)) ? dup_lo(c2) : 0u;
                    const uint32_t* xw = reinterpret_cast<const uint32_t*>(xv);
                    uint32_t d2[2] = {0u, 0u};
                    float s0 = 0.f, s1 = 0.f, q0 = 0.f, q1 = 0.f;
#pragma unroll
                    for (int i = 0; i < 16; i++) {
                        const uint32_t a = hsub2(xw[i], c2);
                        s0 += bf_lo(a); s1 += bf_hi(a);
                        d2[i & 1] = hfma2(a, ww[i], d2[i & 1]);
                        q0 = fmaf(bf_lo(a), bf_lo(a), q0); q1 = fmaf(bf_hi(a), bf_hi(a), q1);
                    }
                    sts128(sb + SM_SP + r * 512 + lane * 16, __float_as_uint(s0 + s1), __float_as_uint(q0 + q1),
                           __float_as_uint((bf_lo(d2[0]) + bf_hi(d2[0])) + (bf_lo(d2[1]) + bf_hi(d2[1]))), c2 << 16);
                }
                epoch = __shfl_sync(0xffffffffu, epoch, 0);
                if (aw < 2) nb_arrive(NB_FFN, 96);
                mbar_wait(bars + 8 * B_FF, 0);
#pragma unroll 1
                for (int i = 0; i < 3; i++) issue(i, i);
                const unsigned tag = epoch + 1u;
                if (aw == 2) {
                    nb_sync(NB_FFN, 96);
                    TLP(elect, 23);
                    float s = 0.f, q = 0.f, dt = 0.f, x0;
#pragma unroll 8
                    for (int j = 0; j < 16; j++) {
                        const uint4 e = lds128(sb + SM_SP + lane * 256 + ((j + lane) & 15) * 16);
                        s += __uint_as_float(e.x); q += __uint_as_float(e.y); dt += __uint_as_float(e.z); x0 = __uint_as_float(e.w);
                    }
                    s += __shfl_xor_sync(0xffffffffu, s, 1); q += __shfl_xor_sync(0xffffffffu, q, 1); dt += __shfl_xor_sync(0xffffffffu, dt, 1);
                    const float ms = s * (1.0f / D_);
                    const float vb = round_bf16(fmaxf(q - s * ms, 0.f) * (1.0f / D_));
                    const uint32_t md = pack_bf16(x0 + ms, sqrt_a(round_bf16(vb + 1e-5f)));
                    const uint32_t rbits = pack_bf16((dt - (bf_lo(md) - x0) * ldsf(sb + SM_MISC + 20)) * rcp(bf_hi(md)), 0.f);
                    const int row = blockIdx.x * 16 + (lane >> 1);
                    const uint32_t key = ((((rbits & 0x8000u) ? (~rbits & 0xFFFFu) : (rbits | 0x8000u)) + 1u) << 11) | (uint32_t)(2047 - row);
                    asm volatile("st.relaxed.gpu.global.v2.u32 [%0], {%1, %2};" :: "l"(&P.scr->rows[row]), "r"(md), "r"(tag) : "memory");
                    if (key == __reduce_max_sync(0xffffffffu, key))
                        asm volatile("st.relaxed.gpu.global.v4.u32 [%0], {%1, %2, %3, %3};" :: "l"(&P.scr->best[blockIdx.x]), "r"(key), "r"(md), "r"(tag) : "memory");
                    TLP(elect, 24);
                }
                {
                    float a[8], sq = 0.f, wt = 0.f;
#pragma unroll
                    for (int i = 0; i < 8; i++) a[i] = 0.f;
#pragma unroll 1
                    for (int m = 0; m < nc; m++) {
                        const int b = m % 3, c = c0 + m;
                        mbar_wait(fbar + b * 8, (m / 3) & 1);
                        uint4 v[8];
#pragma unroll
                        for (int i = 0; i < 8; i++) v[i] = lds128(fbuf + b * 4096 + i * 512 + lane * 16);
                        sts32(sb + SM_MISC + 12, 0u);
                        colsum8<true>(a, sq, v);
                        fence_regs(a);
                        wt += 1.0f;
                        issue(m + 3, b);
                        if ((c & 3) == 3 || m == nc - 1) {
#pragma unroll 1
                            for (int o = 8; o <= 16; o <<= 1) {
#pragma unroll
                                for (int i = 0; i < 8; i++) a[i] += __shfl_xor_sync(0xffffffffu, a[i], o);
                                sq += __shfl_xor_sync(0xffffffffu, sq, o);
                            }
                            float4* dst = &get_acc()->cs[((c >> 2) * 16 + hp) * 24 + lane];
                            if (lane < 8) { red_v4(dst, a[0], a[1], a[2], wt); red_v4(dst + 8, a[3], a[4], a[5], wt); red_v4(dst + 16, a[6], a[7], sq, wt); }
#pragma unroll
                            for (int i = 0; i < 8; i++) a[i] = 0.f;
                            wt = 0.f;
                        }
                    }
                    TLP(tid == 288, 26); TLP(tid == 320, 15); TLP(tid == 352, 22);
                }
                if (aw == 0) {
                    uint4 v[4];
                    unsigned it = 0;
                    bool ok = true;
#pragma unroll 1
                    do {
                        if (!ok) __nanosleep(200);
#pragma unroll
                        for (int i = 0; i < 4; i++) v[i] = ld_gpu(&P.scr->best[i * 32 + lane]);
                        ok = v[0].z == tag && v[1].z == tag && v[2].z == tag && v[3].z == tag;
                    } while (!__all_sync(0xffffffffu, ok) && ++it < (1u << 20));
#pragma unroll
                    for (int i = 1; i < 4; i++) if (v[i].x > v[0].x) v[0] = v[i];
                    const uint32_t key = __reduce_max_sync(0xffffffffu, v[0].x);
                    const uint32_t md = __reduce_or_sync(0xffffffffu, v[0].x == key ? v[0].y : 0u);
                    const int sel = 2047 - (int)(key & 2047u);
                    const uint4* xp = reinterpret_cast<const uint4*>(P.x + (size_t)sel * D_) + lane;
#pragma unroll
                    for (int i = 0; i < 4; i++) v[i] = __ldg(xp + i * 32);
                    const uint32_t m2 = __byte_perm(md, 0, 0x1010);
                    const float rs = rcp(bf_hi(md));
                    const uint32_t ord = (key >> 11) - 1u;
                    const float r = __uint_as_float(((ord & 0x8000u) ? (ord & 0x7FFFu) : (~ord & 0xFFFFu)) << 16);
                    sts128(sb + SM_MISC, (uint32_t)sel, __float_as_uint(round_bf16(rcp(1.0f + ex2(-r * LOG2E)))), epoch, 0u);
#pragma unroll
                    for (int i = 0; i < 4; i++) {
                        const uint32_t e0 = ln_pair(v[i].x, m2, rs), e1 = ln_pair(v[i].y, m2, rs), e2 = ln_pair(v[i].z, m2, rs), e3 = ln_pair(v[i].w, m2, rs);
                        const uint32_t xa = sb + SM_XS + i * 512 + (lane >> 2) * 64 + (lane & 3) * 4;
                        sts32(xa, __byte_perm(e0, e2, 0x5410)); sts32(xa + 16, __byte_perm(e0, e2, 0x7632));
                        sts32(xa + 32, __byte_perm(e1, e3, 0x5410)); sts32(xa + 48, __byte_perm(e1, e3, 0x7632));
                    }
                    TLP(elect, 25);
                    __syncwarp();
                    mbar_arrive_if(elect, bars + 8 * B_XS);
                }
            }
            if (aw == 2) {
                    const int l = lane < 24 ? lane : 0;
                    const float4* src = &get_acc()->cs[((l >> 3) * 16 + hp) * 24 + (l & 7)];
                    float4 v0, v1, v2;
                    uint4 v[4];
                    unsigned it = 0;
                    bool ok;
#pragma unroll 1
                    do {
                        v0 = ld_gpu(src); v1 = ld_gpu(src + 8); v2 = ld_gpu(src + 16);
                        ok = v0.w == 32.0f && v1.w == 32.0f && v2.w == 32.0f;
#pragma unroll
                        for (int i = 0; i < 4; i++) v[i] = ld_gpu(reinterpret_cast<const uint4*>(&P.scr->rows[rb * 256]) + i * 32 + lane);
#pragma unroll
                        for (int i = 0; i < 4; i++) ok = ok && v[i].y == epoch + 1u && v[i].w == epoch + 1u;
                    } while (!__all_sync(0xffffffffu, ok) && ++it < (1u << 20));
#pragma unroll
                    for (int i = 0; i < 4; i++) {
                        const uint32_t o = i * 256 + lane * 8;
                        sts64(sb + SM_MD + o, v[i].x, v[i].z);
                        sts64(sb + SM_RS + o, __float_as_uint(rcp(bf_hi(v[i].x))), __float_as_uint(rcp(bf_hi(v[i].z))));
                        const uint32_t h0 = hmul2(dup_lo(v[i].x), 0xBF00BF00u), h1 = hmul2(dup_lo(v[i].z), 0xBF00BF00u);
                        sts128(sb + SM_AX + o * 4, h0, h0 & 0xFFFFu, 0u, 0u);
                        sts128(sb + SM_AX + o * 4 + 16, h1, h1 & 0xFFFFu, 0u, 0u);
                    }
                    sts128(sb + SM_H + lane * 16, 0u, 0u, 0u, 0u); sts128(sb + SM_H + 512 + lane * 16, 0u, 0u, 0u, 0u);
                    const uint32_t e2 = __reduce_max_sync(0xffffffffu, l >= 16 ? __float_as_uint(v2.z) : 0u) >> 23;
                    sts32(sb + SM_MISC + 16, (uint32_t)min(max(187 - (int)((e2 + 1) >> 1), 1), 180) << 23);
                    float cc[8] = {v0.x, v0.y, v0.z, v1.x, v1.y, v1.z, v2.x, v2.y};
                    const uint32_t bx = sb + SM_BX + (l >> 3) * 1024;
#pragma unroll 1
                    for (int k = 0; k < 8; k++) {
                        uint32_t w[4];
#pragma unroll
                        for (int i = 0; i < 4; i++) {
                            w[i] = pack_bf16(cc[2 * i], cc[2 * i + 1]);
                            cc[2 * i] -= bf_lo(w[i]); cc[2 * i + 1] -= bf_hi(w[i]);
                        }
                        sts128(bx + k * 128 + (((l & 7) ^ k) * 16), w[0], w[1], w[2], w[3]);
                    }
                    fence_async_smem();
                    __syncwarp();
                    mbar_arrive_if(elect, bars + 8 * B_LN);
                    TLP(elect, 28);
                }
            mbar_wait(bars + 8 * B_XS, 0);
            if (ffn) {
                float a[8];
#pragma unroll
                for (int i = 0; i < 8; i++) a[i] = 0.f;
                TLP(elect, 40 + aw);
                gemv_run<256>(a, ng, nc % 3, (nc / 3) & 1, fbuf + (lane >> 4) * 2048 + (lane & 15) * 16, sb + SM_XS + g0 * 64 + (lane & 12) * 4, 64, fbar, sb + SM_MISC + 12,
                              [&](int m, int b) { issue(nc + m + 3, b); });
                TLP(elect, 44 + aw);
#pragma unroll 1
                for (int o = 4; o <= 8; o <<= 1) {
#pragma unroll
                    for (int i = 0; i < 8; i++) a[i] += __shfl_xor_sync(0xffffffffu, a[i], o);
                }
                if ((lane & 12) == 0) {
                    const uint32_t ga = sb + SM_GU + aw * 256 + (lane >> 4) * 128 + (lane & 3) * 32;
                    sts128(ga, __float_as_uint(a[0]), __float_as_uint(a[1]), __float_as_uint(a[2]), __float_as_uint(a[3]));
                    sts128(ga + 16, __float_as_uint(a[4]), __float_as_uint(a[5]), __float_as_uint(a[6]), __float_as_uint(a[7]));
                }
                nb_sync(NB_AUX, 96);
                if (warp == 9) {
                    if (elect_one()) {
                        mbar_expect_tx(bars + 8 * B_DN, 32768);
                        tma_3d(sb + SM_FB + 8192, &tmS.wd8, bars + 8 * B_DN, 0, blockIdx.x * 32, 0);
                    }
                    const uint32_t ga = sb + SM_GU + lane * 4;
                    const float gg = round_bf16((ldsf(ga) + ldsf(ga + 256)) + ldsf(ga + 512));
                    const float uu = round_bf16((ldsf(ga + 128) + ldsf(ga + 384)) + ldsf(ga + 640));
                    asm volatile("st.shared.u16 [%0], %1;" :: "r"(sb + SM_H + (lane >> 3) * 256 + 112 + (lane & 7) * 2), "h"((uint16_t)pack_bf16(round_bf16(silu_f(gg)) * uu, 0.f)) : "memory");
                    fence_async_smem();
                }
                __syncwarp();
                TLP(tid == 288, 27);
            }
        }
        {
            TLP(tid == 288, 38);
            const int w4 = warp & 3;
            const uint32_t sp = sb + SM_FB + w4 * 1536;
            auto send = [&](int h) {
                if (elect_one()) {
                    asm volatile("cp.reduce.async.bulk.global.shared::cta.bulk_group.add.noftz.f16 [%0], [%1], 1536;"
                                 :: "l"(&P.scr->kv[(hp * 8 + h * 4 + w4) * 96]), "r"(sp) : "memory");
                    asm volatile("cp.async.bulk.commit_group;" ::: "memory");
                }
            };
            float ya[4] = {0.f, 0.f, 0.f, 0.f}, yb[4] = {0.f, 0.f, 0.f, 0.f};
            uint4 g0[3];
#pragma unroll 1
            for (int h = 0; h < 2; h++) {
                {
                    float d[20];
                    const uint32_t alo = dlo(sb + SM_PHI + h * 32768, 16), vlo = dlo(sb + SM_V + h * 20480, 16);
                    mbar_wait(bars + 8 * (B_PHI + h), 0);
                    wgmma_fence();
#pragma unroll
                    for (int k = 0; k < 16; k++)
                        wgmma_ss_n40(d, desc_from(alo + (k >> 2) * 512 + (k & 3) * 2, DH128), desc_from(vlo + (k >> 2) * 320 + (k & 3) * 2, DH128), k);
                    wgmma_commit();
#pragma unroll
                    for (int j = 0; j < 3; j++) g0[j] = ld_gpu(&P.scr->kv[(hp * 8 + w4) * 96 + j * 32 + lane]);
                    asm volatile("cp.async.bulk.wait_group.read 0;" ::: "memory");
                    __syncwarp();
                    const float ksc = ldsf(sb + SM_MISC + 16);
                    wgmma_wait<0>();
                    fence_regs(d);
#define U(x) pack_f16(d[x] * ksc, d[x + 1] * ksc)
                    sts128(sp + lane * 16, U(0), U(4), U(8), pack_f16(d[16], 1.0f));
                    sts128(sp + 512 + lane * 16, U(2), U(6), U(10), pack_f16(d[18], 1.0f));
                    sts128(sp + 1024 + lane * 16, U(12), U(14), 0u, 0x3C000000u);
#undef U
                    fence_async_smem();
                    __syncwarp();
                    send(h);
                    TLP(tid == 256, 30 + h);
                    nb_sync(NB_KV, 128);
                    if (h) break;
                    if (warp == 8 && elect_one()) {
                        mbar_expect_tx(bars + 8 * B_X, 32768);
                        tma_2d(sb, &tmX2, bars + 8 * B_X, (hp >> 1) * 128, rb * 256 + (hp & 1) * 128);
                        tma_2d(sb + 16384, &tmX2, bars + 8 * B_X, (hp >> 1) * 128 + 64, rb * 256 + (hp & 1) * 128);
                        load_wo(4);
                    }
                    __syncwarp();
                }
                if (blockIdx.x < 112) {
                    const uint32_t hlo = dlo(sb + SM_H, 256);
                    mbar_wait(bars + 8 * B_DN, 0);
                    mbar_wait(bars + 8 * (B_DN + 1), 0);
                    wgmma_fence();
#pragma unroll 2
                    for (int k = 0; k < 16; k++) {
                        wgmma_ss_n8_ta(yb, desc_from(dlo(sb + 6 * 16384, 16) + k * 128, DH128), desc_from(hlo + (k & 1) * 32 + 7 - (k >> 1), 8), k);
                        wgmma_ss_n8_ta(ya, desc_from(dlo(sb + SM_FB + 8192, 16) + k * 128, DH128), desc_from(hlo + (k & 1) * 32 + 7 - (k >> 1), 8), k);
                    }
                    wgmma_commit();
                    wgmma_wait<0>();
                    fence_regs(ya); fence_regs(yb);
                    if (warp == 8) {
                        nb_sync(NB_KV, 128);
                        if (elect_one()) { load_wo(2); load_wo(3); }
                        __syncwarp();
                    } else {
                        nb_arrive(NB_KV, 128);
                    }
                    TLP(tid == 288, 29);
                }
            }
            const float kus = __uint_as_float((254u << 23) - lds32(sb + SM_MISC + 16));
            kv_gather<1>(g0, &P.scr->kv[(hp * 8 + w4) * 96 + lane], sb + SM_KVOP + w4 * 256, lane, kus);
            mbar_arrive_if(elect, bars + 8 * B_KV);
            asm volatile("cp.async.bulk.wait_group.read 0;" ::: "memory");
            __syncwarp();
            if (blockIdx.x < 112) {
#define U(x) __float_as_uint(x)
                sts128(sp + lane * 16, U(ya[0]), U(ya[1]), U(ya[2]), U(1.0f));
                sts128(sp + 512 + lane * 16, U(ya[3]), U(yb[0]), U(yb[1]), U(1.0f));
                sts128(sp + 1024 + lane * 16, U(yb[2]), U(yb[3]), 0u, U(1.0f));
#undef U
                fence_async_smem();
                __syncwarp();
                if (elect_one()) {
                    asm volatile("cp.reduce.async.bulk.global.shared::cta.bulk_group.add.f32 [%0], [%1], 1536;"
                                 :: "l"(&get_acc()->y[((blockIdx.x & 3) * 4 + w4) * 96]), "r"(sp) : "memory");
                    asm volatile("cp.async.bulk.commit_group;" ::: "memory");
                }
                __syncwarp();
            }
            if (w4 >= 2) {
                uint4 g1[6];
#pragma unroll
                for (int j = 0; j < 6; j++) g1[j] = make_uint4(0, 0, 0, 0);
                kv_gather<2>(g1, &P.scr->kv[(hp * 8 + 2 * w4) * 96 + lane], sb + SM_KVOP - 5120 + (w4 - 2) * 512, lane, kus);
                mbar_arrive_if(lane < 2, bars + 8 * (B_KV + 1));
            }
            asm volatile("cp.async.bulk.wait_group.read 0;" ::: "memory");
            __syncwarp();
            mbar_arrive_if(elect, bars + 8 * B_S1);
        }
        if (warp == 8) {
            if (elect_one()) {
                const unsigned* flag = &P.scr->cnt_o[rb * 128];
                uint4 hint = make_uint4(0, 0, 0, 0);
                mbar_wait(bars + 8 * B_O, 0);
#pragma unroll
                for (int i = 0; i < 16; i++) {
                    if (i < 4) {
                        unsigned it = 0;
#pragma unroll 1
                        while ((i == 0 ? hint.x : (i == 1 ? hint.y : (i == 2 ? hint.z : hint.w))) < 16u && ++it < (1u << 14)) hint = ld_gpu(reinterpret_cast<const uint4*>(&P.scr->hint[rb * 32]));
                    }
                    if (i == 4) poll_counter(flag + 32, 16);
                    if (i == 8) mbar_wait(bars + 8 * B_C1, 0);
                    if (i == 4 || i == 8) asm volatile("fence.proxy.async.global;" ::: "memory");
                    if ((i & 3) == 0 && i < 12) TL(i == 0 ? 21 : (i == 4 ? 34 : 36));
                    if (i == 4 || i > 5) mbar_wait(bars + 8 * (B_SD + max(i - 5, 0)), 0);
                    load_o(i, epoch & 1u);
                    if (i == 3) { load_wo(5); mbar_wait(bars + 8 * B_S1, 0); load_wo(6); }
                    if (i >= 5 && i < 14) load_wo(i + 2);
                }
            }
        } else if (warp == 9) {
            if (elect_one()) {
                unsigned* flag = &P.scr->cnt_o[rb * 128];
                mbar_wait(bars + 8 * B_O, 0);
                asm volatile("red.release.gpu.global.add.u32 [%0], 1;" :: "l"(flag + 32) : "memory");
                TL(35);
            }
        } else if (warp == 10) {
            if (elect_one()) {
                unsigned* f = &P.scr->cnt_o[rb * 128 + 96];
                mbar_wait(bars + 8 * (B_O + 1), 0);
                asm volatile("red.release.gpu.global.add.u32 [%0], 1;" :: "l"(f) : "memory");
                TL(37);
                poll_counter(f, 16);
                asm volatile("mbarrier.arrive.shared::cta.b64 _, [%0];" :: "r"(bars + 8 * B_C1) : "memory");
            }
        } else if (warp == 11) {
            const uint4 misc = lds128(sb + SM_MISC);
            if ((int)(misc.x >> 7) == rb * 2 + (hp & 1)) {
                float y[4] = {0.f, 0.f, 0.f, 0.f};
#pragma unroll 1
                for (int rep = 0; rep < 4; rep++) {
                    const float4* yp = &get_acc()->y[(rep * 4 + (lane >> 3)) * 96 + (hp >> 3) * 32 + (lane & 7) * 4 + ((hp >> 1) & 3)];
                    float4 u, v;
                    unsigned it = 0;
#pragma unroll 1
                    do { u = ld_gpu(yp); v = ld_gpu(yp + 32); } while (!__all_sync(0xffffffffu, u.w == 28.0f && v.w == 28.0f) && ++it < (1u << 20));
                    if (hp & 8) { y[0] += u.y; y[1] += v.x; y[2] += u.z; y[3] += v.y; } else { y[0] += u.x; y[1] += u.z; y[2] += u.y; y[3] += v.x; }
                }
                const uint32_t sg = __byte_perm(misc.y, 0, 0x3232), ya = sb + SM_Y + ((lane >> 3) * 16 + (lane & 7)) * 2;
                const uint32_t w0 = hmul2(pack_bf16(y[0], y[1]), sg), w1 = hmul2(pack_bf16(y[2], y[3]), sg);
                asm volatile("st.shared.u16 [%0], %1;" :: "r"(ya), "h"((uint16_t)w0) : "memory");
                asm volatile("st.shared.u16 [%0], %1;" :: "r"(ya + 16), "h"((uint16_t)(w0 >> 16)) : "memory");
                asm volatile("st.shared.u16 [%0], %1;" :: "r"(ya + 128), "h"((uint16_t)w1) : "memory");
                asm volatile("st.shared.u16 [%0], %1;" :: "r"(ya + 144), "h"((uint16_t)(w1 >> 16)) : "memory");
                __syncwarp();
                if (lane < 16) {
                    const uint4 xc = __ldg(reinterpret_cast<const uint4*>(P.x + (size_t)misc.x * D_ + (hp >> 1) * 128) + lane);
                    const uint32_t m2 = __byte_perm(lds32(sb + SM_MD + (misc.x & 255u) * 4), 0, 0x1010);
                    const float r = ldsf(sb + SM_RS + (misc.x & 255u) * 4);
                    const uint4 yv = lds128(sb + SM_Y + lane * 16);
                    sts128(sb + SM_Y + lane * 16, silu_pair(hadd2(ln_pair(xc.x, m2, r), yv.x)), silu_pair(hadd2(ln_pair(xc.y, m2, r), yv.y)),
                           silu_pair(hadd2(ln_pair(xc.z, m2, r), yv.z)), silu_pair(hadd2(ln_pair(xc.w, m2, r), yv.w)));
                    sts128(sb + SM_Y + 256 + lane * 16, xc.x, xc.y, xc.z, xc.w);
                }
                __syncwarp();
                mbar_arrive_if(elect, bars + 8 * B_Y);
                TLP(elect, 39);
            }
        }
    } else {
        const int wg = warp >> 2, w4 = warp & 3, g = lane >> 2;
        nb_sync(0, NTHREADS);
        asm volatile("setmaxnreg.inc.sync.aligned.u32 224;");
        TLP(tid == 0, 1);
        const int row0 = wg * 128 + w4 * 16 + g;
        float pq0[16], pq1[16];
        float rs[4];
        uint32_t f2[8], f3[8], q0[8], q1[8], q2[8], q3[8];
        float qa[16], qb[16];
        const uint32_t wlo = dlo(sb + SM_WPHI, 16);
        const uint32_t sw0 = (uint32_t)(((w4 * 2) ^ (lane & 7)) * 16), sw1 = sw0 ^ 16u;
        {
            float acc0[96], acc1[96];
            {
                const uint32_t alo0 = dlo(sb + wg * 16384, 16), blo0 = dlo(sb + 32768, 8192);
                {
#pragma unroll
                    for (int k = 0; k < 4; k++) {
                        if (k == 0) asm volatile("cp.async.wait_group 1;" ::: "memory");
                        if (k == 2) { wgmma_commit(); asm volatile("cp.async.wait_group 0;" ::: "memory"); }
                        if (!(k & 1)) { fence_async_smem(); nb_sync(NB_STAG, 256); wgmma_fence(); }
                        if (k == 0) { TLP(tid == 0, 2); TLG(tid == 0, 49); }
                        wgmma_ss_n192_tb(acc0, desc_from(alo0 + k * 2, DH128), desc_from(blo0 + k * 128, DH128), k);
                        wgmma_ss_n192_tb(acc1, desc_from(alo0 + 512 + k * 2, DH128), desc_from(blo0 + k * 128, DH128), k);
                    }
                    wgmma_commit();
                }
                int s = 1, ph = 0, ps = 0;
#pragma unroll 1
                for (int ks = 1; ks < 16; ks++) {
                    const bool hold = wg && ks == 15;
                    if (hold) {
                        wgmma_wait<0>();
                        mbar_arrive_if(elect, bars + 8 * (B_EMPTY + ps));
                        nb_sync(NB_LEAD, 256);
                    }
                    mbar_wait(bars + 8 * (B_FULL + s), ph);
                    const uint32_t alo = alo0 + s * (STAGE >> 4), blo = blo0 + s * (STAGE >> 4);
                    wgmma_fence();
#pragma unroll
                    for (int k = 0; k < 4; k++) {
                        if (k == SARR && !wg && ks == 15) nb_arrive(NB_LEAD, 256);
                        wgmma_ss_n192_tb(acc0, desc_from(alo + k * 2, DH128), desc_from(blo + k * 128, DH128), 1);
                        wgmma_ss_n192_tb(acc1, desc_from(alo + 512 + k * 2, DH128), desc_from(blo + k * 128, DH128), 1);
                        if (k == 0) {
                            wgmma_commit();
                            wgmma_wait<1>();
                            mbar_arrive_if(elect && !hold, bars + 8 * (B_EMPTY + ps));
                        }
                    }
                    wgmma_commit();
                    ps = s;
                    if (++s == 3) { s = 0; ph ^= 1; }
                }
            }
            mbar_wait(bars + 8 * B_LN, 0);
            wgmma_fence();
            wgmma_ss_n192_tb(acc0, desc_from(dlo(sb + SM_AX + wg * 2048, 0), 128u >> 4), desc_from(dlo(sb + SM_BX, 1024), 1u << 30), 1);
            wgmma_ss_n192_tb(acc1, desc_from(dlo(sb + SM_AX + wg * 2048 + 1024, 0), 128u >> 4), desc_from(dlo(sb + SM_BX, 1024), 1u << 30), 1);
            wgmma_commit();
            mbar_wait(bars + 8 * (B_EMPTY + 2), 0);
            mbar_wait(bars + 8 * B_WPHI, 0);
            {
                uint32_t md[4];
#pragma unroll
                for (int i = 0; i < 4; i++) {
                    const int r = row0 + (i >> 1) * 64 + (i & 1) * 8;
                    md[i] = __byte_perm(lds32(sb + SM_MD + r * 4), 0, 0x3232);
                    rs[i] = ldsf(sb + SM_RS + r * 4);
                }
                const uint32_t zb = sb + SM_V + wg * 10240 + (lane >> 4) * 5120 + 4096 + (lane & 7) * 128 + (sw0 ^ ((lane & 8) * 2));
                stsm_t(zb, md[0], md[1], md[2], md[3]);
                stsm_t(zb + 20480, md[0], md[1], md[2], md[3]);
            }
            wgmma_wait<0>();
            fence_regs(acc0); fence_regs(acc1);
            TLP(tid == 0, 3); TLG(tid == 0, 50);
            const uint32_t vb = sb + SM_V + wg * 10240 + lane * 128;
            uint32_t f0[8], f1[8], v[8];
            pack_head<64>(acc0, v); stsm_t(vb + sw0, v[0], v[2], v[4], v[6]); stsm_t(vb + sw1, v[1], v[3], v[5], v[7]);
            pack_head<64>(acc1, v); stsm_t(vb + 5120 + sw0, v[0], v[2], v[4], v[6]); stsm_t(vb + 5120 + sw1, v[1], v[3], v[5], v[7]);
#pragma unroll
            for (int i = 32; i < 48; i++) { asm volatile("" : "+f"(acc0[i]) :: "memory"); asm volatile("" : "+f"(acc1[i]) :: "memory"); }
            pack_head<32>(acc0, f0); pack_head<32>(acc1, f1);
            wgmma_fence();
            feat_mma(pq0, f0, wlo); feat_mma(pq1, f1, wlo);
            wgmma_commit();
            pack_head<80>(acc0, v); stsm_t(vb + 20480 + sw0, v[0], v[2], v[4], v[6]); stsm_t(vb + 20480 + sw1, v[1], v[3], v[5], v[7]);
            pack_head<80>(acc1, v); stsm_t(vb + 25600 + sw0, v[0], v[2], v[4], v[6]); stsm_t(vb + 25600 + sw1, v[1], v[3], v[5], v[7]);
            pack_head<48>(acc0, f2); pack_head<48>(acc1, f3);
            pack_head<0>(acc0, q0); pack_head<0>(acc1, q1);
#pragma unroll
            for (int i = 0; i < 16; i++) { qa[i] = acc0[16 + i]; qb[i] = acc1[16 + i]; }
            fence_regs(f2); fence_regs(f3); fence_regs(q0); fence_regs(q1);
            wgmma_wait<0>();
            fence_regs(pq0); fence_regs(pq1); fence_regs(f0); fence_regs(f1);
            mbar_arrive_if(elect, bars + 8 * B_T);
            TLP(tid == 0, 4);
        }
#pragma unroll 1
        for (int h = 0; h < 2; h++) {
            const uint32_t pb = sb + SM_PHI + wg * 16384 + lane * 128 + h * 32768;
            key_head(pq0, pq1, rs, pb + sw0, pb + sw1);
            wgmma_fence();
            feat_mma(pq0, f2, wlo + 128 - h * 128); feat_mma(pq1, f3, wlo + 128 - h * 128);
            wgmma_commit();
            fence_async_smem();
            __syncwarp();
            mbar_arrive_if(elect, bars + 8 * (B_PHI + h));
            TLP(tid == 0, 6 + 2 * h);
            mbar_wait(bars + 8 * B_T, 0);
            wgmma_wait<0>();
            fence_regs(pq0); fence_regs(pq1); fence_regs(f2); fence_regs(f3);
#pragma unroll
            for (int j = 0; j < 8; j++) { f2[j] = q0[j]; f3[j] = q1[j]; }
            fence_regs(f2); fence_regs(f3);
        }
#pragma unroll
        for (int j = 0; j < 8; j++) { q2[j] = pack_bf16(qa[2 * j], qa[2 * j + 1]); q3[j] = pack_bf16(qb[2 * j], qb[2 * j + 1]); }
        const uint32_t par = lds32(sb + SM_MISC + 8) & 1u;
        const int orow = (hp & 1) * 128 + wg * 64 + w4 * 16 + (lane >> 4);
        const size_t goff = (size_t)(rb * 256 + orow) * D_ + (hp >> 1) * 128 + (lane & 15) * 8;
        uint4 gv[8], xv[8];
#pragma unroll
        for (int i = 0; i < 8; i++) xv[i] = make_uint4(0, 0, 0, 0);
#pragma unroll
        for (int i = 0; i < GSPLIT2; i++) gv[i] = make_uint4(0, 0, 0, 0);
        const uint32_t rowc = sb + ((lane >> 3) & 1) * 16384 + (wg * 64 + w4 * 16 + (lane >> 4)) * 128;
        {
            uint32_t hbump;
            asm volatile("mov.u32 %0, %1;" : "=r"(hbump) : "r"((uint32_t)(hp < 8 && elect)));
            __nv_bfloat16* od = P.o + (size_t)(par * S_ + rb * 256 + row0) * D_ + hp * 32 + (lane & 3) * 8;
#pragma unroll 1
            for (int h = 0; h < 2; h++) {
                uint32_t pa[8], na[8], pb[8], nb[8];
                features(pq0, pq1, rs, pa, na, pb, nb);
                TLP(tid == 0, 16 + h);
                if (h == 0) {
                    wgmma_fence();
                    feat_mma(pq0, q2, wlo + 128); feat_mma(pq1, q3, wlo + 128);
                    wgmma_commit();
                    mbar_wait(bars + 8 * B_X, 0);
#pragma unroll
                    for (int i = 0; i < 8; i++) xv[i] = lds128(rowc + i * 256 + (((lane & 7) ^ ((2 * i + (lane >> 4)) & 7)) * 16));
#pragma unroll
                    for (int i = 0; i < GSPLIT; i++) { gv[i] = xv[i]; gate_item(gv[i], sb, orow + 2 * i); }
                    wgmma_wait<0>();
                    fence_regs(pq0); fence_regs(pq1); fence_regs(q2); fence_regs(q3);
                    TLP(tid == 0, 18);
                } else {
#pragma unroll
                    for (int i = GSPLIT; i < GSPLIT2; i++) { gv[i] = xv[i]; gate_item(gv[i], sb, orow + 2 * i); }
                    TLP(tid == 0, 10);
                }
                {
                    float d0[20], e0[20], d1[20], e1[20];
                    const uint32_t klo = dlo(sb + SM_KVOP - h * 5120, 128);
                    fence_regs(pa); fence_regs(na); fence_regs(pb); fence_regs(nb);
                    mbar_wait(bars + 8 * (B_KV + h), 0);
                    TLP(tid == 0, 32 + h);
                    wgmma_fence();
                    o_mma(d0, e0, pa, na, klo);
                    o_mma(d1, e1, pb, nb, klo);
                    wgmma_commit();
                    wgmma_wait<0>();
                    fence_regs(d0); fence_regs(e0); fence_regs(pa); fence_regs(na);
                    fence_regs(d1); fence_regs(e1); fence_regs(pb); fence_regs(nb);
                    o_store(d0, e0, od + h * 512);
                    asm volatile("{\n.reg .pred q;\nsetp.gt.s32 q, %1, %2;\n@q red.relaxed.gpu.global.add.u32 [%0], %1;\n}" :: "l"(&P.scr->hint[rb * 32 + (hp >> 1) + lane]), "r"(hbump), "r"(h) : "memory");
                    o_store(d1, e1, od + h * 512 + 64 * D_);
                    __syncwarp();
                    mbar_arrive_if(elect, bars + 8 * (B_O + h));
                }
                TLP(tid == 0, 9 + 2 * h);
            }
        }
        float ghr[8], ghm[8];
#pragma unroll
        for (int i = GSPLIT2; i < 8; i++) { ghr[i] = 0.5f * ldsf(sb + SM_RS + (orow + 2 * i) * 4); ghm[i] = -bf_lo(lds32(sb + SM_MD + (orow + 2 * i) * 4)) * ghr[i]; }
        float acc[64];
        {
            const uint32_t alo0 = dlo(sb + wg * 8192, 16), blo0 = dlo(sb, 8192);
            const uint32_t ta0 = sb + (wg * 64 + w4 * 16) * 128 + lane * 16;
            uint32_t cv[2][4];
#pragma unroll
            for (int i = 0; i < 1; i++) {
                mbar_wait(bars + 8 * (B_OF + i), 0);
#pragma unroll
                for (int j = 0; j < 4; j++) cv[i][j] = lds32(ta0 + i * 16384 + j * 512);
            }
#pragma unroll
            for (int i = 0; i < 16; i++) {
                const uint32_t alo = alo0 + o_slot(i) * 1024, blo = blo0 + wo_slot(i) * 1024;
                if (i < 4) {
                    if (__builtin_expect(__any_sync(0xffffffffu, min(min(cv[i & 1][0], cv[i & 1][1]), min(cv[i & 1][2], cv[i & 1][3])) == 0u), 0)) {
                        uint4 v[4];
                        unsigned it = 0;
#pragma unroll 1
                        do {
#pragma unroll
                            for (int j = 0; j < 4; j++) {
                                const int r = j * 4 + (lane >> 3);
                                v[j] = ld_gpu(reinterpret_cast<const uint4*>(P.o + (size_t)(par * S_ + rb * 256 + (orow & ~1) + r) * D_ + i * 64) + ((lane ^ r) & 7));
                            }
                        } while (__any_sync(0xffffffffu, min(min(v[0].x, v[1].x), min(v[2].x, v[3].x)) == 0u) && ++it < (1u << 18));
#pragma unroll
                        for (int j = 0; j < 4; j++) sts128(ta0 + (i & 3) * 16384 + j * 512, v[j].x, v[j].y, v[j].z, v[j].w);
                        fence_async_smem();
                        __syncwarp();
                    }
                } else {
                    mbar_wait(bars + 8 * (B_OF + i), 0);
                }
                if (i == OSTAG && wg == 0) nb_sync(NB_STAG, 256);
                wgmma_fence();
#pragma unroll
                for (int k = 0; k < 4; k++) {
                    if (i == 15 && k == OARR && wg) nb_arrive(NB_STAG, 256);
                    wgmma_ss_n128_tb(acc, desc_from(alo + k * 2, DH128), desc_from(blo + k * 128, DH128), k | i);
                    if (k == OREL) {
                        if (i > 0 && i < 12) {
                            wgmma_commit();
                            wgmma_wait<1>();
                            mbar_arrive_if(elect, bars + 8 * (B_SD + i - 1));
                        }
                    }
                }
                wgmma_commit();
                if (i == 0) { TLP(tid == 0, 12); TLG(tid == 0, 51); }
                if (i < 3) {
                    mbar_wait(bars + 8 * (B_OF + i + 1), 0);
#pragma unroll
                    for (int j = 0; j < 4; j++) cv[~i & 1][j] = lds32(ta0 + (i + 1) * 16384 + j * 512);
                }
                static_assert(2 * (8 - GSPLIT2) <= 16 - GST, "");
                if (i >= GST && GSPLIT2 + (i - GST) / 2 < 8) {
                    const int q = GSPLIT2 + (i - GST) / 2;
                    if ((i - GST) & 1) { gv[q].z = gate_pair(xv[q].z, ghr[q], ghm[q]); gv[q].w = gate_pair(xv[q].w, ghr[q], ghm[q]); asm volatile("" : "+r"(gv[q].z), "+r"(gv[q].w) :: "memory"); }
                    else { gv[q].x = gate_pair(xv[q].x, ghr[q], ghm[q]); gv[q].y = gate_pair(xv[q].y, ghr[q], ghm[q]); asm volatile("" : "+r"(gv[q].x), "+r"(gv[q].y) :: "memory"); }
                }
            }
        }
        wgmma_wait<0>();
        fence_regs(acc);
        TLP(tid == 0, 13); TLG(tid == 0, 52);
        {
            const uint32_t stg = sb + (wg * 64 + w4 * 16) * 128;
            const int rr = lane & 7;
#pragma unroll
            for (int c = 0; c < 4; c++) {
                const uint32_t a0 = stg + (c >> 1) * 16384 + rr * 128 + ((((c & 1) * 4 + (lane >> 3)) ^ rr) * 16);
                stsm(a0, pack_bf16(acc[c * 16 + 0], acc[c * 16 + 1]), pack_bf16(acc[c * 16 + 4], acc[c * 16 + 5]),
                     pack_bf16(acc[c * 16 + 8], acc[c * 16 + 9]), pack_bf16(acc[c * 16 + 12], acc[c * 16 + 13]));
                stsm(a0 + 1024, pack_bf16(acc[c * 16 + 2], acc[c * 16 + 3]), pack_bf16(acc[c * 16 + 6], acc[c * 16 + 7]),
                     pack_bf16(acc[c * 16 + 10], acc[c * 16 + 11]), pack_bf16(acc[c * 16 + 14], acc[c * 16 + 15]));
            }
            __syncwarp();
#pragma unroll
            for (int i = 0; i < 8; i++) {
                const uint4 sv = lds128(rowc + i * 256 + (((lane & 7) ^ ((2 * i + (lane >> 4)) & 7)) * 16));
                uint4 o;
                o.x = hadd2(xv[i].x, hmul2(sv.x, gv[i].x)); o.y = hadd2(xv[i].y, hmul2(sv.y, gv[i].y));
                o.z = hadd2(xv[i].z, hmul2(sv.z, gv[i].z)); o.w = hadd2(xv[i].w, hmul2(sv.w, gv[i].w));
                *reinterpret_cast<uint4*>(P.out + goff + (size_t)i * 2 * D_) = o;
            }
            const uint32_t sel = lds32(sb + SM_MISC);
            if ((int)(sel >> 4) == rb * 16 + (orow >> 4)) {
                mbar_wait(bars + 8 * B_Y, 0);
                if ((sel & 1u) == (uint32_t)(lane >> 4)) {
                    const int i = (sel & 15u) >> 1;
                    const uint4 sv = lds128(rowc + i * 256 + (((lane & 7) ^ (sel & 7u)) * 16));
                    const uint4 gq = lds128(sb + SM_Y + (lane & 15) * 16), xq = lds128(sb + SM_Y + 256 + (lane & 15) * 16);
                    *reinterpret_cast<uint4*>(P.out + goff + (size_t)i * 2 * D_) = make_uint4(hadd2(xq.x, hmul2(sv.x, gq.x)), hadd2(xq.y, hmul2(sv.y, gq.y)), hadd2(xq.z, hmul2(sv.z, gq.z)), hadd2(xq.w, hmul2(sv.w, gq.w)));
                }
            }
        }
        TLG(tid == 0, 53);
        if (tid == 0) { TL(14); TL_DUMP(); }
        if (blockIdx.x == 0 && tid == 0) asm volatile("st.relaxed.gpu.global.u32 [%0], %1;" :: "l"(&P.scr->epoch), "r"(lds32(sb + SM_MISC + 8) + 1u) : "memory");
    }
}

typedef CUresult (*PFN_encodeTiled)(CUtensorMap*, CUtensorMapDataType, cuuint32_t, void*, const cuuint64_t*, const cuuint64_t*,
                                    const cuuint32_t*, const cuuint32_t*, CUtensorMapInterleave, CUtensorMapSwizzle,
                                    CUtensorMapL2promotion, CUtensorMapFloatOOBfill);

void make_map(PFN_encodeTiled fn, CUtensorMap* m, const void* ptr, int rank, const cuuint64_t* dims, const cuuint64_t* strides, const cuuint32_t* box, CUtensorMapSwizzle sw) {
    const cuuint32_t es[5] = {1, 1, 1, 1, 1};
    fn(m, CU_TENSOR_MAP_DATA_TYPE_BFLOAT16, rank, const_cast<void*>(ptr), dims, strides, box, es, CU_TENSOR_MAP_INTERLEAVE_NONE,
       sw, CU_TENSOR_MAP_L2_PROMOTION_L2_256B, CU_TENSOR_MAP_FLOAT_OOB_FILL_NONE);
}
void make_2d(PFN_encodeTiled fn, CUtensorMap* m, const void* ptr, uint64_t rows, uint64_t cols, uint32_t box_rows, uint32_t box_cols, CUtensorMapSwizzle sw) {
    const cuuint64_t gd[2] = {cols, rows}, gs[1] = {cols * 2};
    const cuuint32_t bd[2] = {box_cols, box_rows};
    make_map(fn, m, ptr, 2, gd, gs, bd, sw);
}

}

extern "C" void kernel_launch(void* const* d_in, const int* in_sizes, int n_in, void* d_out, int out_size) {
    (void)in_sizes; (void)n_in; (void)out_size;
    static PFN_encodeTiled fn = nullptr;
    static void* o_ptr = nullptr;
    static void* scr_ptr = nullptr;
    static void* tl_ptr = nullptr;
    if (!fn) {
        void* p = nullptr;
        cudaDriverEntryPointQueryResult st;
        cudaGetDriverEntryPoint("cuTensorMapEncodeTiled", &p, cudaEnableDefault, &st);
        fn = (PFN_encodeTiled)p;
        cudaGetSymbolAddress(&o_ptr, g_o);
        cudaGetSymbolAddress(&scr_ptr, g_scr);
        cudaFuncSetAttribute(fused_kernel, cudaFuncAttributeMaxDynamicSharedMemorySize, SM_TOTAL);
    }
    CUtensorMap tmX, tmW, tmPhi, tmWo, tmO, tmX2;
    SideMaps tmS;
    make_2d(fn, &tmX, d_in[0], S_, D_, 256, 64, CU_TENSOR_MAP_SWIZZLE_128B);
    {
        const cuuint64_t gd[3] = {1024, 1024, 3}, gs[2] = {6144, 2048};
        const cuuint32_t bd[3] = {64, 64, 3};
        make_map(fn, &tmW, d_in[1], 3, gd, gs, bd, CU_TENSOR_MAP_SWIZZLE_128B);
    }
    make_2d(fn, &tmS.wc, d_in[1], D_, 3 * D_, 32, 64, CU_TENSOR_MAP_SWIZZLE_NONE);
    make_2d(fn, &tmPhi, d_in[2], 1024, 32, 64, 32, CU_TENSOR_MAP_SWIZZLE_64B);
    make_2d(fn, &tmS.wg, d_in[6], D_, F_, 32, 32, CU_TENSOR_MAP_SWIZZLE_NONE);
    make_2d(fn, &tmS.wu, d_in[7], D_, F_, 32, 32, CU_TENSOR_MAP_SWIZZLE_NONE);
    {
        const cuuint64_t gd[3] = {64, F_, 16}, gs[2] = {2048, 128};
        const cuuint32_t bd[3] = {64, 32, 8};
        make_map(fn, &tmS.wd8, d_in[8], 3, gd, gs, bd, CU_TENSOR_MAP_SWIZZLE_128B);
    }
    {
        const cuuint64_t gd[4] = {64, 64, 16, 16}, gs[3] = {2048, 64 * 2048, 128};
        const cuuint32_t bd[4] = {64, 32, 2, 2};
        make_map(fn, &tmWo, d_in[3], 4, gd, gs, bd, CU_TENSOR_MAP_SWIZZLE_128B);
    }
    make_2d(fn, &tmO, o_ptr, 2 * S_, D_, 128, 64, CU_TENSOR_MAP_SWIZZLE_128B);
    make_2d(fn, &tmX2, d_in[0], S_, D_, 128, 64, CU_TENSOR_MAP_SWIZZLE_128B);
    Params P;
    P.x = (const __nv_bfloat16*)d_in[0];
    P.wr = (const __nv_bfloat16*)d_in[5];
    P.wqkv = (const __nv_bfloat16*)d_in[1];
    P.wg = (const __nv_bfloat16*)d_in[6];
    P.wu = (const __nv_bfloat16*)d_in[7];
    P.wd = (const __nv_bfloat16*)d_in[8];
    P.wo = (const __nv_bfloat16*)d_in[3];
    P.out = (__nv_bfloat16*)d_out;
    P.o = (__nv_bfloat16*)o_ptr;
    P.scr = (Scratch*)scr_ptr;
    P.tl = (unsigned long long*)tl_ptr;
    cudaLaunchConfig_t cfg = {};
    cfg.gridDim = dim3(NCTA); cfg.blockDim = dim3(NTHREADS); cfg.dynamicSmemBytes = SM_TOTAL; cfg.stream = cudaStreamPerThread;
    cudaLaunchAttribute at[1];
    at[0].id = cudaLaunchAttributeCooperative; at[0].val.cooperative = 1;
    cfg.attrs = at; cfg.numAttrs = 1;
    cudaLaunchKernelEx(&cfg, fused_kernel, P, tmX, tmW, tmX2, tmS, tmPhi, tmWo, tmO);
}
```

```cpp
#include <cuda_runtime.h>
#include <cuda_bf16.h>
#include <cuda.h>
#include <stdint.h>

namespace {

constexpr int S_ = 2048, D_ = 1024, F_ = 3584;
constexpr int NCTA = 128, NTHREADS = 384;
#define OREL 2
#define OSTAG 12
#define OARR 3
#define NC0 3
#define NC2 4
#define NG0 12
#define NG1 12
#define GSPLIT 1
#define GSPLIT2 2
#define GST 3
#define SARR 3
#define PFENCE 1
#define JWO 12

constexpr int STAGE = 57344;
constexpr int SM_PHI = 0;
constexpr int SM_V = 131072;
constexpr int SM_AX = 172032;
constexpr int SM_BX = 176128;
constexpr int SM_SP = 172032;
constexpr int SM_FB = 180224;
constexpr int SM_OS = 196608;
constexpr int SM_XS = 221184;
constexpr int SM_KVOP = 172032;
constexpr int SM_MD = 223232;
constexpr int SM_RS = 224256;
constexpr int SM_Y = 225280;
constexpr int SM_GU = 225536;
constexpr int SM_MISC = 226688;
constexpr int SM_H = 179200;
constexpr int SM_BARS = 226816;
constexpr int SM_WPHI = 227840;
constexpr int SM_TOTAL = 232448;

constexpr int B_FULL = 0, B_EMPTY = 3, B_OF = 6, B_SD = 22, B_O = 33, B_PHI = 35, B_T = 37, B_WPHI = 38, B_Y = 39, B_KV = 40, B_LN = 42, B_S1 = 43, B_FF = 44, B_X = 54, B_C1 = 55, B_DN = 56, B_XS = 58, B_COUNT = 59, B_XR = 59, B_OS = 60;
constexpr int NB_KV = 1, NB_FFN = 2, NB_AUX = 3, NB_LEAD = 4, NB_STAG = 5;
__device__ __forceinline__ int o_slot(int i) { const int r = i % 5; return r == 4 ? 10 : r; }
__device__ __forceinline__ int wo_slot(int i) { const int r = i % 7; return r == 6 ? 11 : 4 + r; }

struct __align__(128) Acc {
    float4 cs[48 * 8 * 3];
    float4 y[4 * 4 * 3 * 32];
};
constexpr int ACC_VEC_PER_CTA = (int)(sizeof(Acc) / 16 / NCTA);
static_assert(sizeof(Acc) == ACC_VEC_PER_CTA * 16 * NCTA && ACC_VEC_PER_CTA <= 32, "");
struct __align__(128) Scratch {
    Acc acc[2];
    uint4 kv[32 * 4 * 3 * 32];
    unsigned cnt_o[8 * 128];
    uint2 rows[S_];
    uint4 best[NCTA];
    unsigned epoch;
};
__device__ Scratch g_scr;
__device__ __align__(1024) __nv_bfloat16 g_o[S_ * D_];

#define TL(e) do {} while (0)
#define TLP(c, e) do {} while (0)
#define TLG(c, e) do {} while (0)
#define TL_DUMP() do {} while (0)

struct SideMaps { CUtensorMap wc, wg, wu, wd8; };
struct Params {
    const __nv_bfloat16* x;
    const __nv_bfloat16* wr;
    const __nv_bfloat16* wqkv;
    const __nv_bfloat16* wg;
    const __nv_bfloat16* wu;
    const __nv_bfloat16* wd;
    const __nv_bfloat16* wo;
    __nv_bfloat16* out;
        Scratch* scr;
    unsigned long long* tl;
};

__device__ __forceinline__ bool elect_one() {
    uint32_t p; asm volatile("{\n.reg .pred q;\nelect.sync _|q, 0xffffffff;\nselp.u32 %0, 1, 0, q;\n}" : "=r"(p)); return p;
}
__device__ __forceinline__ uint32_t smem_u32(const void* p) { return (uint32_t)__cvta_generic_to_shared(p); }
__device__ __forceinline__ void mbar_init(uint32_t bar, uint32_t cnt) { asm volatile("mbarrier.init.shared::cta.b64 [%0], %1;" :: "r"(bar), "r"(cnt) : "memory"); }
__device__ __forceinline__ void mbar_expect_tx(uint32_t bar, uint32_t bytes) { asm volatile("mbarrier.arrive.expect_tx.shared::cta.b64 _, [%0], %1;" :: "r"(bar), "r"(bytes) : "memory"); }
__device__ __forceinline__ void mbar_arrive_if(bool p, uint32_t bar) {
    asm volatile("{\n.reg .pred q;\nsetp.ne.b32 q, %1, 0;\n@q mbarrier.arrive.shared::cta.b64 _, [%0];\n}" :: "r"(bar), "r"((int)p) : "memory");
}
__device__ __forceinline__ void mbar_wait(uint32_t bar, uint32_t parity) {
    asm volatile("{\n.reg .pred p;\n.reg .u32 n;\nmov.u32 n, 0;\n"
                 "WAIT_LOOP:\nmbarrier.try_wait.parity.shared::cta.b64 p, [%0], %1;\n@p bra WAIT_DONE;\n"
                 "add.u32 n, n, 1;\nsetp.lt.u32 p, n, 0x40000;\n@p bra WAIT_LOOP;\nWAIT_DONE:\n}" :: "r"(bar), "r"(parity) : "memory");
}
__device__ __forceinline__ void tma_2d(uint32_t dst, const CUtensorMap* tm, uint32_t bar, int c0, int c1) {
    asm volatile("cp.async.bulk.tensor.2d.shared::cluster.global.mbarrier::complete_tx::bytes [%0], [%1, {%3, %4}], [%2];"
        :: "r"(dst), "l"(tm), "r"(bar), "r"(c0), "r"(c1) : "memory");
}
__device__ __forceinline__ void tma_3d(uint32_t dst, const CUtensorMap* tm, uint32_t bar, int c0, int c1, int c2) {
    asm volatile("cp.async.bulk.tensor.3d.shared::cluster.global.mbarrier::complete_tx::bytes [%0], [%1, {%3, %4, %5}], [%2];"
        :: "r"(dst), "l"(tm), "r"(bar), "r"(c0), "r"(c1), "r"(c2) : "memory");
}
__device__ __forceinline__ void tma_4d(uint32_t dst, const CUtensorMap* tm, uint32_t bar, int c0, int c1, int c2, int c3) {
    asm volatile("cp.async.bulk.tensor.4d.shared::cluster.global.mbarrier::complete_tx::bytes [%0], [%1, {%3, %4, %5, %6}], [%2];"
        :: "r"(dst), "l"(tm), "r"(bar), "r"(c0), "r"(c1), "r"(c2), "r"(c3) : "memory");
}
__device__ __forceinline__ void prefetch_l2(const void* p, uint32_t bytes) { asm volatile("cp.async.bulk.prefetch.L2.global [%0], %1;" :: "l"(p), "r"(bytes) : "memory"); }
__device__ __forceinline__ void wgmma_fence() { asm volatile("wgmma.fence.sync.aligned;" ::: "memory"); }
__device__ __forceinline__ void wgmma_commit() { asm volatile("wgmma.commit_group.sync.aligned;" ::: "memory"); }
template <int N> __device__ __forceinline__ void wgmma_wait() { asm volatile("wgmma.wait_group.sync.aligned %0;" :: "n"(N) : "memory"); }
template <int N> __device__ __forceinline__ void fence_regs(float (&a)[N]) {
#pragma unroll
    for (int i = 0; i < N; i++) asm volatile("" : "+f"(a[i]) :: "memory");
}
template <int N> __device__ __forceinline__ void fence_regs(uint32_t (&a)[N]) {
#pragma unroll
    for (int i = 0; i < N; i++) asm volatile("" : "+r"(a[i]) :: "memory");
}
__device__ __forceinline__ uint64_t desc_from(uint32_t lo, uint32_t hi) { uint64_t d; asm("mov.b64 %0, {%1, %2};" : "=l"(d) : "r"(lo), "r"(hi)); return d; }
__device__ __forceinline__ uint32_t dlo(uint32_t addr, uint32_t lbo) { return ((addr & 0x3FFFF) >> 4) | ((lbo >> 4) << 16); }
__device__ __forceinline__ void nb_sync(int id, int cnt) { asm volatile("bar.sync %0, %1;" :: "r"(id), "r"(cnt) : "memory"); }
__device__ __forceinline__ void nb_arrive(int id, int cnt) { asm volatile("bar.arrive %0, %1;" :: "r"(id), "r"(cnt) : "memory"); }
__device__ __forceinline__ void fence_async_smem() { asm volatile("fence.proxy.async.shared::cta;" ::: "memory"); }
__device__ __forceinline__ void red_v4(float4* p, float a, float b, float c, float d) {
    asm volatile("red.relaxed.gpu.global.add.v4.f32 [%0], {%1, %2, %3, %4};" :: "l"(p), "f"(a), "f"(b), "f"(c), "f"(d) : "memory");
}
__device__ __forceinline__ float4 ld_gpu(const float4* p) {
    float4 v; asm volatile("ld.relaxed.gpu.global.v4.f32 {%0, %1, %2, %3}, [%4];" : "=f"(v.x), "=f"(v.y), "=f"(v.z), "=f"(v.w) : "l"(p) : "memory"); return v;
}
__device__ __forceinline__ uint4 ld_gpu(const uint4* p) {
    uint4 v; asm volatile("ld.relaxed.gpu.global.v4.u32 {%0, %1, %2, %3}, [%4];" : "=r"(v.x), "=r"(v.y), "=r"(v.z), "=r"(v.w) : "l"(p) : "memory"); return v;
}
__device__ __forceinline__ uint32_t pack_bf16(float lo, float hi) { uint32_t r; asm("cvt.rn.bf16x2.f32 %0, %1, %2;" : "=r"(r) : "f"(hi), "f"(lo)); return r; }
__device__ __forceinline__ uint32_t pack_f16(float lo, float hi) { uint32_t r; asm("cvt.rn.f16x2.f32 %0, %1, %2;" : "=r"(r) : "f"(hi), "f"(lo)); return r; }
__device__ __forceinline__ float2 unpack_f16(uint32_t v) { float2 r; asm("{\n.reg .f16 l, h;\nmov.b32 {l, h}, %2;\ncvt.f32.f16 %0, l;\ncvt.f32.f16 %1, h;\n}" : "=f"(r.x), "=f"(r.y) : "r"(v)); return r; }
__device__ __forceinline__ float bf_lo(uint32_t v) { return __uint_as_float(v << 16); }
__device__ __forceinline__ float bf_hi(uint32_t v) { return __uint_as_float(v & 0xFFFF0000u); }
__device__ __forceinline__ float round_bf16(float v) { return bf_lo(pack_bf16(v, 0.f)); }
__device__ __forceinline__ float ex2(float v) { float r; asm("ex2.approx.ftz.f32 %0, %1;" : "=f"(r) : "f"(v)); return r; }
__device__ __forceinline__ float rcp(float v) { float r; asm("rcp.approx.ftz.f32 %0, %1;" : "=f"(r) : "f"(v)); return r; }
__device__ __forceinline__ float sqrt_a(float v) { float r; asm("sqrt.approx.f32 %0, %1;" : "=f"(r) : "f"(v)); return r; }
__device__ __forceinline__ void stsm(uint32_t addr, uint32_t r0, uint32_t r1, uint32_t r2, uint32_t r3) {
    asm volatile("stmatrix.sync.aligned.m8n8.x4.shared.b16 [%0], {%1, %2, %3, %4};" :: "r"(addr), "r"(r0), "r"(r1), "r"(r2), "r"(r3) : "memory");
}
__device__ __forceinline__ void stsm_t(uint32_t addr, uint32_t r0, uint32_t r1, uint32_t r2, uint32_t r3) {
    asm volatile("stmatrix.sync.aligned.m8n8.x4.trans.shared.b16 [%0], {%1, %2, %3, %4};" :: "r"(addr), "r"(r0), "r"(r1), "r"(r2), "r"(r3) : "memory");
}
__device__ __forceinline__ uint4 lds128(uint32_t addr) {
    uint4 v; asm volatile("ld.shared.v4.u32 {%0, %1, %2, %3}, [%4];" : "=r"(v.x), "=r"(v.y), "=r"(v.z), "=r"(v.w) : "r"(addr) : "memory"); return v;
}
__device__ __forceinline__ void sts128(uint32_t addr, uint32_t a, uint32_t b, uint32_t c, uint32_t d) {
    asm volatile("st.shared.v4.u32 [%0], {%1, %2, %3, %4};" :: "r"(addr), "r"(a), "r"(b), "r"(c), "r"(d) : "memory");
}
__device__ __forceinline__ void sts64(uint32_t addr, uint32_t a, uint32_t b) { asm volatile("st.shared.v2.u32 [%0], {%1, %2};" :: "r"(addr), "r"(a), "r"(b) : "memory"); }
__device__ __forceinline__ uint32_t lds32(uint32_t addr) { uint32_t v; asm volatile("ld.shared.u32 %0, [%1];" : "=r"(v) : "r"(addr) : "memory"); return v; }
__device__ __forceinline__ float ldsf(uint32_t addr) { return __uint_as_float(lds32(addr)); }
__device__ __forceinline__ void sts32(uint32_t addr, uint32_t v) { asm volatile("st.shared.u32 [%0], %1;" :: "r"(addr), "r"(v) : "memory"); }
__device__ __forceinline__ uint32_t hmul2(uint32_t a, uint32_t b) { uint32_t r; asm("mul.rn.bf16x2 %0, %1, %2;" : "=r"(r) : "r"(a), "r"(b)); return r; }
__device__ __forceinline__ uint32_t hadd2(uint32_t a, uint32_t b) { uint32_t r; asm("add.rn.bf16x2 %0, %1, %2;" : "=r"(r) : "r"(a), "r"(b)); return r; }
__device__ __forceinline__ uint32_t hsub2(uint32_t a, uint32_t b) { uint32_t r; asm("sub.rn.bf16x2 %0, %1, %2;" : "=r"(r) : "r"(a), "r"(b)); return r; }

__device__ __forceinline__ void wgmma_ss_n192_tb(float (&d)[96], uint64_t da, uint64_t db, int scale_d) {
    asm volatile(
        "{\n.reg .pred p;\nsetp.ne.b32 p, %98, 0;\n"
        "wgmma.mma_async.sync.aligned.m64n192k16.f32.bf16.bf16 "
        "{%0, %1, %2, %3, %4, %5, %6, %7, %8, %9, %10, %11, %12, %13, %14, %15, %16, %17, %18, %19, %20, %21, %22, %23, %24, %25, %26, %27, %28, %29, %30, %31, %32, %33, %34, %35, %36, %37, %38, %39, %40, %41, %42, %43, %44, %45, %46, %47, %48, %49, %50, %51, %52, %53, %54, %55, %56, %57, %58, %59, %60, %61, %62, %63, %64, %65, %66, %67, %68, %69, %70, %71, %72, %73, %74, %75, %76, %77, %78, %79, %80, %81, %82, %83, %84, %85, %86, %87, %88, %89, %90, %91, %92, %93, %94, %95}, %96, %97, p, 1, 1, 0, 1;\n}\n"
        : "+f"(d[0]), "+f"(d[1]), "+f"(d[2]), "+f"(d[3]), "+f"(d[4]), "+f"(d[5]), "+f"(d[6]), "+f"(d[7]), "+f"(d[8]), "+f"(d[9]), "+f"(d[10]), "+f"(d[11]), "+f"(d[12]), "+f"(d[13]), "+f"(d[14]), "+f"(d[15]), "+f"(d[16]), "+f"(d[17]), "+f"(d[18]), "+f"(d[19]), "+f"(d[20]), "+f"(d[21]), "+f"(d[22]), "+f"(d[23]), "+f"(d[24]), "+f"(d[25]), "+f"(d[26]), "+f"(d[27]), "+f"(d[28]), "+f"(d[29]), "+f"(d[30]), "+f"(d[31]), "+f"(d[32]), "+f"(d[33]), "+f"(d[34]), "+f"(d[35]), "+f"(d[36]), "+f"(d[37]), "+f"(d[38]), "+f"(d[39]), "+f"(d[40]), "+f"(d[41]), "+f"(d[42]), "+f"(d[43]), "+f"(d[44]), "+f"(d[45]), "+f"(d[46]), "+f"(d[47]), "+f"(d[48]), "+f"(d[49]), "+f"(d[50]), "+f"(d[51]), "+f"(d[52]), "+f"(d[53]), "+f"(d[54]), "+f"(d[55]), "+f"(d[56]), "+f"(d[57]), "+f"(d[58]), "+f"(d[59]), "+f"(d[60]), "+f"(d[61]), "+f"(d[62]), "+f"(d[63]), "+f"(d[64]), "+f"(d[65]), "+f"(d[66]), "+f"(d[67]), "+f"(d[68]), "+f"(d[69]), "+f"(d[70]), "+f"(d[71]), "+f"(d[72]), "+f"(d[73]), "+f"(d[74]), "+f"(d[75]), "+f"(d[76]), "+f"(d[77]), "+f"(d[78]), "+f"(d[79]), "+f"(d[80]), "+f"(d[81]), "+f"(d[82]), "+f"(d[83]), "+f"(d[84]), "+f"(d[85]), "+f"(d[86]), "+f"(d[87]), "+f"(d[88]), "+f"(d[89]), "+f"(d[90]), "+f"(d[91]), "+f"(d[92]), "+f"(d[93]), "+f"(d[94]), "+f"(d[95])
        : "l"(da), "l"(db), "r"(scale_d));
}
__device__ __forceinline__ void wgmma_ss_n128_tb(float (&d)[64], uint64_t da, uint64_t db, int scale_d) {
    asm volatile(
        "{\n.reg .pred p;\nsetp.ne.b32 p, %66, 0;\n"
        "wgmma.mma_async.sync.aligned.m64n128k16.f32.bf16.bf16 "
        "{%0, %1, %2, %3, %4, %5, %6, %7, %8, %9, %10, %11, %12, %13, %14, %15, %16, %17, %18, %19, %20, %21, %22, %23, %24, %25, %26, %27, %28, %29, %30, %31, %32, %33, %34, %35, %36, %37, %38, %39, %40, %41, %42, %43, %44, %45, %46, %47, %48, %49, %50, %51, %52, %53, %54, %55, %56, %57, %58, %59, %60, %61, %62, %63}, %64, %65, p, 1, 1, 0, 1;\n}\n"
        : "+f"(d[0]), "+f"(d[1]), "+f"(d[2]), "+f"(d[3]), "+f"(d[4]), "+f"(d[5]), "+f"(d[6]), "+f"(d[7]), "+f"(d[8]), "+f"(d[9]), "+f"(d[10]), "+f"(d[11]), "+f"(d[12]), "+f"(d[13]), "+f"(d[14]), "+f"(d[15]), "+f"(d[16]), "+f"(d[17]), "+f"(d[18]), "+f"(d[19]), "+f"(d[20]), "+f"(d[21]), "+f"(d[22]), "+f"(d[23]), "+f"(d[24]), "+f"(d[25]), "+f"(d[26]), "+f"(d[27]), "+f"(d[28]), "+f"(d[29]), "+f"(d[30]), "+f"(d[31]), "+f"(d[32]), "+f"(d[33]), "+f"(d[34]), "+f"(d[35]), "+f"(d[36]), "+f"(d[37]), "+f"(d[38]), "+f"(d[39]), "+f"(d[40]), "+f"(d[41]), "+f"(d[42]), "+f"(d[43]), "+f"(d[44]), "+f"(d[45]), "+f"(d[46]), "+f"(d[47]), "+f"(d[48]), "+f"(d[49]), "+f"(d[50]), "+f"(d[51]), "+f"(d[52]), "+f"(d[53]), "+f"(d[54]), "+f"(d[55]), "+f"(d[56]), "+f"(d[57]), "+f"(d[58]), "+f"(d[59]), "+f"(d[60]), "+f"(d[61]), "+f"(d[62]), "+f"(d[63])
        : "l"(da), "l"(db), "r"(scale_d));
}
__device__ __forceinline__ void wgmma_ss_n40(float (&d)[20], uint64_t da, uint64_t db, int scale_d) {
    asm volatile(
        "{\n.reg .pred p;\nsetp.ne.b32 p, %22, 0;\n"
        "wgmma.mma_async.sync.aligned.m64n40k16.f32.bf16.bf16 "
        "{%0, %1, %2, %3, %4, %5, %6, %7, %8, %9, %10, %11, %12, %13, %14, %15, %16, %17, %18, %19}, %20, %21, p, 1, 1, 0, 0;\n}\n"
        : "+f"(d[0]), "+f"(d[1]), "+f"(d[2]), "+f"(d[3]), "+f"(d[4]), "+f"(d[5]), "+f"(d[6]), "+f"(d[7]), "+f"(d[8]), "+f"(d[9]), "+f"(d[10]), "+f"(d[11]), "+f"(d[12]), "+f"(d[13]), "+f"(d[14]), "+f"(d[15]), "+f"(d[16]), "+f"(d[17]), "+f"(d[18]), "+f"(d[19])
        : "l"(da), "l"(db), "r"(scale_d));
}
__device__ __forceinline__ void wgmma_ss_n8_ta(float (&d)[4], uint64_t da, uint64_t db, int scale_d) {
    asm volatile(
        "{\n.reg .pred p;\nsetp.ne.b32 p, %6, 0;\n"
        "wgmma.mma_async.sync.aligned.m64n8k16.f32.bf16.bf16 "
        "{%0, %1, %2, %3}, %4, %5, p, 1, 1, 1, 0;\n}\n"
        : "+f"(d[0]), "+f"(d[1]), "+f"(d[2]), "+f"(d[3])
        : "l"(da), "l"(db), "r"(scale_d));
}
__device__ __forceinline__ void wgmma_rs_n32_tb(float (&d)[16], uint32_t a0, uint32_t a1, uint32_t a2, uint32_t a3, uint64_t db, int scale_d) {
    asm volatile(
        "{\n.reg .pred p;\nsetp.ne.b32 p, %21, 0;\n"
        "wgmma.mma_async.sync.aligned.m64n32k16.f32.bf16.bf16 "
        "{%0, %1, %2, %3, %4, %5, %6, %7, %8, %9, %10, %11, %12, %13, %14, %15}, {%16, %17, %18, %19}, %20, p, 1, 1, 1;\n}\n"
        : "+f"(d[0]), "+f"(d[1]), "+f"(d[2]), "+f"(d[3]), "+f"(d[4]), "+f"(d[5]), "+f"(d[6]), "+f"(d[7]), "+f"(d[8]), "+f"(d[9]), "+f"(d[10]), "+f"(d[11]), "+f"(d[12]), "+f"(d[13]), "+f"(d[14]), "+f"(d[15])
        : "r"(a0), "r"(a1), "r"(a2), "r"(a3), "l"(db), "r"(scale_d));
}
__device__ __forceinline__ void wgmma_rs_n40_tb(float (&d)[20], uint32_t a0, uint32_t a1, uint32_t a2, uint32_t a3, uint64_t db, int scale_d) {
    asm volatile(
        "{\n.reg .pred p;\nsetp.ne.b32 p, %25, 0;\n"
        "wgmma.mma_async.sync.aligned.m64n40k16.f32.bf16.bf16 "
        "{%0, %1, %2, %3, %4, %5, %6, %7, %8, %9, %10, %11, %12, %13, %14, %15, %16, %17, %18, %19}, {%20, %21, %22, %23}, %24, p, 1, 1, 1;\n}\n"
        : "+f"(d[0]), "+f"(d[1]), "+f"(d[2]), "+f"(d[3]), "+f"(d[4]), "+f"(d[5]), "+f"(d[6]), "+f"(d[7]), "+f"(d[8]), "+f"(d[9]), "+f"(d[10]), "+f"(d[11]), "+f"(d[12]), "+f"(d[13]), "+f"(d[14]), "+f"(d[15]), "+f"(d[16]), "+f"(d[17]), "+f"(d[18]), "+f"(d[19])
        : "r"(a0), "r"(a1), "r"(a2), "r"(a3), "l"(db), "r"(scale_d));
}

constexpr float LOG2E = 1.4426950408889634f;
constexpr uint32_t DH128 = (1024u >> 4) | (1u << 30);

__device__ __forceinline__ float silu_f(float v) { return v * rcp(1.0f + ex2(-v * LOG2E)); }
__device__ __forceinline__ float silu_t(float v) { const float h = 0.5f * v; float th; asm("tanh.approx.f32 %0, %1;" : "=f"(th) : "f"(h)); return fmaf(h, th, h); }
__device__ __forceinline__ uint32_t ln_pair(uint32_t xv, uint32_t m2, float rs) { const uint32_t a = hsub2(xv, m2); return pack_bf16(bf_lo(a) * rs, bf_hi(a) * rs); }
__device__ __forceinline__ uint32_t silu_pair(uint32_t v) { return pack_bf16(silu_t(bf_lo(v)), silu_t(bf_hi(v))); }
__device__ __forceinline__ uint32_t gate_pair(uint32_t v, float hr, float hm) {
    const float a = fmaf(bf_lo(v), hr, hm), b = fmaf(bf_hi(v), hr, hm);
    float ta, tb;
    asm("tanh.approx.f32 %0, %1;" : "=f"(ta) : "f"(a)); asm("tanh.approx.f32 %0, %1;" : "=f"(tb) : "f"(b));
    return pack_bf16(fmaf(a, ta, a), fmaf(b, tb, b));
}
__device__ __forceinline__ void gate_item(uint4& v, uint32_t sb, int row) {
    const float hr = 0.5f * ldsf(sb + SM_RS + row * 4), hm = -bf_lo(lds32(sb + SM_MD + row * 4)) * hr;
    v.x = gate_pair(v.x, hr, hm); v.y = gate_pair(v.y, hr, hm); v.z = gate_pair(v.z, hr, hm); v.w = gate_pair(v.w, hr, hm);
    asm volatile("" : "+r"(v.x), "+r"(v.y), "+r"(v.z), "+r"(v.w) :: "memory");
}
__device__ __forceinline__ uint32_t hfma2(uint32_t a, uint32_t b, uint32_t c) { uint32_t r; asm("fma.rn.bf16x2 %0, %1, %2, %3;" : "=r"(r) : "r"(a), "r"(b), "r"(c)); return r; }
__device__ __forceinline__ uint32_t dup_lo(uint32_t v) { uint32_t r; asm("{\n.reg .b16 l, h;\nmov.b32 {l, h}, %1;\nmov.b32 %0, {l, l};\n}" : "=r"(r) : "r"(v)); return r; }
__device__ __forceinline__ uint32_t dup_hi(uint32_t v) { uint32_t r; asm("{\n.reg .b16 l, h;\nmov.b32 {l, h}, %1;\nmov.b32 %0, {h, h};\n}" : "=r"(r) : "r"(v)); return r; }
template <bool SQ> __device__ __forceinline__ void colsum8(float (&a)[8], float& sq, const uint4 (&v)[8]) {
    uint32_t q = 0;
#pragma unroll
    for (int i = 0; i < 8; i++) {
        a[0] += bf_lo(v[i].x); a[1] += bf_hi(v[i].x); a[2] += bf_lo(v[i].y); a[3] += bf_hi(v[i].y);
        a[4] += bf_lo(v[i].z); a[5] += bf_hi(v[i].z); a[6] += bf_lo(v[i].w); a[7] += bf_hi(v[i].w);
        if (SQ) q = hfma2(v[i].x, v[i].x, hfma2(v[i].y, v[i].y, hfma2(v[i].z, v[i].z, hfma2(v[i].w, v[i].w, q))));
    }
    if (SQ) sq += bf_lo(q) + bf_hi(q);
}
__device__ __forceinline__ void hfma8(uint4& h, uint32_t w, const uint4& v) { h.x = hfma2(v.x, w, h.x); h.y = hfma2(v.y, w, h.y); h.z = hfma2(v.z, w, h.z); h.w = hfma2(v.w, w, h.w); }
template <int ST, class F>
__device__ __forceinline__ void gemv_run(float (&a)[8], int cnt, int b, uint32_t ph, uint32_t lo, uint32_t wa, uint32_t ws, uint32_t bar0, uint32_t pin, F done) {
    uint32_t rdy = 0;
#pragma unroll 1
    for (int m = 0; m < cnt; m++) {
        if (!rdy) mbar_wait(bar0 + b * 8, ph);
        uint4 A[8];
        const uint4 w = lds128(wa);
#pragma unroll
        for (int i = 0; i < 8; i++) A[i] = lds128(lo + b * 4096 + i * ST);
        const int bc = b;
        if (++b == 3) { b = 0; ph ^= 1; }
        asm volatile("{\n.reg .pred p;\nmbarrier.test_wait.parity.shared::cta.b64 p, [%1], %2;\nselp.u32 %0, 1, 0, p;\n}" : "=r"(rdy) : "r"(bar0 + b * 8), "r"(ph) : "memory");
        sts32(pin, 0u);
        wa += ws;
        uint4 h = make_uint4(0, 0, 0, 0);
        hfma8(h, dup_lo(w.x), A[0]); hfma8(h, dup_hi(w.x), A[1]); hfma8(h, dup_lo(w.y), A[2]); hfma8(h, dup_hi(w.y), A[3]);
        hfma8(h, dup_lo(w.z), A[4]); hfma8(h, dup_hi(w.z), A[5]); hfma8(h, dup_lo(w.w), A[6]); hfma8(h, dup_hi(w.w), A[7]);
        a[0] += bf_lo(h.x); a[1] += bf_hi(h.x); a[2] += bf_lo(h.y); a[3] += bf_hi(h.y);
        a[4] += bf_lo(h.z); a[5] += bf_hi(h.z); a[6] += bf_lo(h.w); a[7] += bf_hi(h.w);
        fence_regs(a);
        done(m, bc);
    }
}
template <int OFF> __device__ __forceinline__ void pack_head(const float (&acc)[96], uint32_t (&f)[8]) {
#pragma unroll
    for (int i = 0; i < 8; i++) f[i] = pack_bf16(acc[OFF + 2 * i], acc[OFF + 2 * i + 1]);
}
__device__ __forceinline__ void feat_mma(float (&p)[16], const uint32_t (&f)[8], uint32_t wlo) {
    constexpr uint32_t DH = (512u >> 4) | (2u << 30);
    wgmma_rs_n32_tb(p, f[0], f[1], f[2], f[3], desc_from(wlo, DH), 0);
    wgmma_rs_n32_tb(p, f[4], f[5], f[6], f[7], desc_from(wlo + 64, DH), 1);
}
template <int S> __device__ __forceinline__ void row_ext(const float (&p)[16], float& a, float& b) {
    auto op = [](float x, float y) { return S > 0 ? fmaxf(x, y) : fminf(x, y); };
    a = op(op(op(p[0], p[1]), op(p[4], p[5])), op(op(p[8], p[9]), op(p[12], p[13])));
    b = op(op(op(p[2], p[3]), op(p[6], p[7])), op(op(p[10], p[11]), op(p[14], p[15])));
#pragma unroll
    for (int o = 1; o <= 2; o <<= 1) { a = op(a, __shfl_xor_sync(0xffffffffu, a, o)); b = op(b, __shfl_xor_sync(0xffffffffu, b, o)); }
}
__device__ __forceinline__ void dual_exp(const float (&p)[16], float scA, float scB, uint32_t (&pos)[8], uint32_t (&neg)[8], uint32_t& chk) {
#pragma unroll
    for (int j = 0; j < 8; j += 2) {
        const float a0 = ex2(p[2 * j] * scA), a1 = ex2(p[2 * j + 1] * scA);
        const float b0 = ex2(p[2 * j + 2] * scB), b1 = ex2(p[2 * j + 3] * scB);
        const float pa = a0 * a1, pb = b0 * b1, R = rcp(pa * pb);
        const uint32_t r = pack_bf16(R * pb, R * pa);
        pos[j] = pack_bf16(a0, a1); pos[j + 1] = pack_bf16(b0, b1);
        neg[j] = hmul2(pos[j], dup_lo(r)); neg[j + 1] = hmul2(pos[j + 1], dup_hi(r));
        chk = hadd2(chk, hadd2(hadd2(pos[j], neg[j]), hadd2(pos[j + 1], neg[j + 1])));
    }
}
template <int S> __device__ __forceinline__ void exact_exp(const float (&p)[16], float scA, float scB, uint32_t (&o)[8]) {
    float mA, mB;
    row_ext<S>(p, mA, mB);
#pragma unroll
    for (int j = 0; j < 8; j++) {
        const float sc = S * ((j & 1) ? scB : scA), m = (j & 1) ? mB : mA;
        const float u = ex2((p[2 * j] - m) * sc), v = ex2((p[2 * j + 1] - m) * sc);
        o[j] = S > 0 ? pack_bf16(u, v) : pack_bf16(v, u);
    }
}
__device__ __forceinline__ void features(const float (&p0)[16], const float (&p1)[16], const float (&rs)[4],
                                         uint32_t (&pa)[8], uint32_t (&na)[8], uint32_t (&pb)[8], uint32_t (&nb)[8]) {
    uint32_t chk = 0;
    dual_exp(p0, rs[0] * LOG2E, rs[1] * LOG2E, pa, na, chk);
    dual_exp(p1, rs[2] * LOG2E, rs[3] * LOG2E, pb, nb, chk);
    if (__builtin_expect(!__all_sync(0xffffffffu, bf_lo(chk) + bf_hi(chk) < 1.0e9f), 0)) {
        exact_exp<1>(p0, rs[0] * LOG2E, rs[1] * LOG2E, pa); exact_exp<-1>(p0, rs[0] * LOG2E, rs[1] * LOG2E, na);
        exact_exp<1>(p1, rs[2] * LOG2E, rs[3] * LOG2E, pb); exact_exp<-1>(p1, rs[2] * LOG2E, rs[3] * LOG2E, nb);
    }
}
__device__ __forceinline__ float quad_sum(float v) { v += __shfl_xor_sync(0xffffffffu, v, 1); return v + __shfl_xor_sync(0xffffffffu, v, 2); }
__device__ __forceinline__ float key_block(const float (&p)[16], float rsA, float rsB, uint32_t d0, uint32_t d1, uint32_t off) {
    float r[8], sp[2], sn[2];
    uint32_t pos[8], neg[8];
    const float scA = rsA * LOG2E, scB = rsB * LOG2E;
#pragma unroll
    for (int j = 0; j < 8; j += 2) {
        const float a0 = ex2(p[2 * j] * scA), a1 = ex2(p[2 * j + 1] * scA);
        const float b0 = ex2(p[2 * j + 2] * scB), b1 = ex2(p[2 * j + 3] * scB);
        const float pa = a0 * a1, pb = b0 * b1, R = rcp(pa * pb), ta = a0 + a1, tb = b0 + b1;
        r[j] = R * pb; r[j + 1] = R * pa;
        if (j == 0) { sp[0] = ta; sp[1] = tb; sn[0] = r[0] * ta; sn[1] = r[1] * tb; }
        else { sp[0] += ta; sp[1] += tb; sn[0] = fmaf(r[j], ta, sn[0]); sn[1] = fmaf(r[j + 1], tb, sn[1]); }
        pos[j] = pack_bf16(a0, a1); pos[j + 1] = pack_bf16(b0, b1);
    }
    const float qa = quad_sum(sp[0]), qb = quad_sum(sp[1]), na = quad_sum(sn[0]), nb = quad_sum(sn[1]);
    const float iq = rcp(qa * qb), nA = rsA * rcp(na), nB = rsB * rcp(nb);
    const uint32_t fp = pack_bf16(rsA * qb * iq, rsB * qa * iq);
#pragma unroll
    for (int j = 0; j < 8; j += 2) {
        const uint32_t rn = pack_bf16(r[j] * nA, r[j + 1] * nB);
        neg[j] = hmul2(pos[j], dup_lo(rn)); neg[j + 1] = hmul2(pos[j + 1], dup_hi(rn));
        pos[j] = hmul2(pos[j], dup_lo(fp)); pos[j + 1] = hmul2(pos[j + 1], dup_hi(fp));
    }
    stsm_t(d0 + 4096, neg[0], neg[2], neg[4], neg[6]); stsm_t(d1 + 4096, neg[1], neg[3], neg[5], neg[7]);
    stsm_t(d0 + off, pos[0], pos[2], pos[4], pos[6]); stsm_t(d1 + off, pos[1], pos[3], pos[5], pos[7]);
    return (qa + qb) + (na + nb);
}
__device__ __forceinline__ void shift_max(float (&p)[16]) {
    float mA, mB;
    row_ext<1>(p, mA, mB);
#pragma unroll
    for (int j = 0; j < 16; j++) p[j] -= (j & 2) ? mB : mA;
}
__device__ __forceinline__ void key_head(float (&p0)[16], float (&p1)[16], const float (&rs)[4], uint32_t d0, uint32_t d1) {
    uint32_t st;
    asm volatile("mov.u32 %0, 0;" : "=r"(st));
    bool again;
#pragma unroll 1
    do {
        const uint32_t off = (st & 2u) << 11;
        const float chk = key_block(p0, rs[0], rs[1], d0, d1, off) + key_block(p1, rs[2], rs[3], d0 + 8192, d1 + 8192, off);
        again = st == 1u || (st == 0u && !__all_sync(0xffffffffu, chk < 1.0e9f));
        if (__builtin_expect(again, 0)) {
            if (st) {
#pragma unroll
                for (int j = 0; j < 16; j += 2) {
                    float t = p0[j]; p0[j] = -p0[j + 1]; p0[j + 1] = -t;
                    t = p1[j]; p1[j] = -p1[j + 1]; p1[j + 1] = -t;
                }
            }
            shift_max(p0); shift_max(p1);
            st++;
        }
        asm volatile("" ::: "memory");
    } while (again);
}
__device__ __forceinline__ void o_mma(float (&d)[20], float (&e)[20], const uint32_t (&pos)[8], const uint32_t (&neg)[8], uint32_t klo) {
    wgmma_rs_n40_tb(d, pos[0], pos[1], pos[2], pos[3], desc_from(klo, 1024u >> 4), 0);
    wgmma_rs_n40_tb(e, neg[0], neg[1], neg[2], neg[3], desc_from(klo + 32, 1024u >> 4), 0);
    wgmma_rs_n40_tb(d, pos[4], pos[5], pos[6], pos[7], desc_from(klo + 16, 1024u >> 4), 1);
    wgmma_rs_n40_tb(e, neg[4], neg[5], neg[6], neg[7], desc_from(klo + 48, 1024u >> 4), 1);
}
__device__ __forceinline__ void o_store(const float (&d)[20], const float (&e)[20], uint32_t dst) {
    const float iA = rcp(fmaf(d[16], e[17], fmaf(e[16], d[17], 1e-6f * d[17] * e[17])));
    const float iB = rcp(fmaf(d[18], e[19], fmaf(e[18], d[19], 1e-6f * d[19] * e[19])));
    const float pA = e[17] * iA, nA = d[17] * iA, pB = e[19] * iB, nB = d[19] * iB;
    uint32_t oa[4], ob[4];
#pragma unroll
    for (int j = 0; j < 4; j++) {
        oa[j] = pack_bf16(fmaf(d[j * 4], pA, e[j * 4] * nA), fmaf(d[j * 4 + 1], pA, e[j * 4 + 1] * nA));
        ob[j] = pack_bf16(fmaf(d[j * 4 + 2], pB, e[j * 4 + 2] * nB), fmaf(d[j * 4 + 3], pB, e[j * 4 + 3] * nB));
    }
    sts128(dst, oa[0], oa[1], oa[2], oa[3]);
    sts128(dst + 512, ob[0], ob[1], ob[2], ob[3]);
}

template <int N> __device__ __forceinline__ void kv_gather(uint4 (&v)[3 * N], const uint4* src, uint32_t dst, int lane, float us) {
    unsigned it = 0;
#pragma unroll 1
    while (++it < (1u << 20)) {
        bool ok = true;
#pragma unroll
        for (int j = 0; j < 3 * N; j++) ok = ok && (v[j].w >> 16) == 0x4800u;
        if (__all_sync(0xffffffffu, ok)) break;
#pragma unroll
        for (int j = 0; j < 3 * N; j++) v[j] = ld_gpu(src + j * 32);
    }
    dst += (lane >> 2) * 16;
    auto cv = [&](uint32_t w) { const float2 f = unpack_f16(w); return pack_bf16(f.x * us, f.y * us); };
#pragma unroll
    for (int n = 0; n < N; n++) {
        sts128(dst + (lane & 3) * 1024 + n * 256, cv(v[3 * n].x), cv(v[3 * n].y), cv(v[3 * n].z), cv(v[3 * n + 2].x));
        sts128(dst + (lane & 3) * 1024 + n * 256 + 128, cv(v[3 * n + 1].x), cv(v[3 * n + 1].y), cv(v[3 * n + 1].z), cv(v[3 * n + 2].y));
        sts32(dst + 4096 + n * 256 + (lane & 3) * 4, pack_bf16(unpack_f16(v[3 * n].w).x, 1.0f));
        sts32(dst + 4096 + n * 256 + 128 + (lane & 3) * 4, pack_bf16(unpack_f16(v[3 * n + 1].w).x, 1.0f));
    }
    fence_async_smem();
    __syncwarp();
}

__global__ void __launch_bounds__(NTHREADS, 1)
fused_kernel(const Params P, const __grid_constant__ CUtensorMap tmX, const __grid_constant__ CUtensorMap tmW, const __grid_constant__ CUtensorMap tmX2,
             const __grid_constant__ SideMaps tmS, const __grid_constant__ CUtensorMap tmPhi,
             const __grid_constant__ CUtensorMap tmWo, const __grid_constant__ CUtensorMap tmO, const __grid_constant__ CUtensorMap tmOs) {
    extern __shared__ __align__(1024) uint8_t smem_raw[];
    constexpr uint32_t sb = 1024;
    if (smem_u32(smem_raw) != sb) return;
    constexpr uint32_t bars = sb + SM_BARS;
    const int rb = blockIdx.x >> 4, hp = blockIdx.x & 15;
    TLP(threadIdx.x == 32, 0); TLG(threadIdx.x == 32, 48);
    auto load_stage = [&](int s, int ks) {
        mbar_expect_tx(bars + 8 * (B_FULL + s), STAGE);
        tma_2d(sb + s * STAGE, &tmX, bars + 8 * (B_FULL + s), ks * 64, rb * 256);
        tma_3d(sb + s * STAGE + 32768, &tmW, bars + 8 * (B_FULL + s), hp * 64, ks * 64, 0);
    };
    if (threadIdx.x < 256) {
        const uint32_t t = threadIdx.x, r = t >> 3, sw = ((t ^ r) & 7) * 16;
        const __nv_bfloat16* wp = P.wqkv + (size_t)r * 3 * D_ + hp * 64 + (t & 7) * 8;
        const __nv_bfloat16* xp = P.x + (size_t)(rb * 256 + (t >> 7) * 128 + (r & 15)) * D_ + (t & 7) * 8;
#pragma unroll
        for (int i = 0; i < 3; i++) asm volatile("cp.async.cg.shared.global [%0], [%1], 16;" :: "r"(sb + 32768 + i * 8192 + r * 128 + sw), "l"(wp + i * D_) : "memory");
#pragma unroll
        for (int i = 0; i < 8; i++) asm volatile("cp.async.cg.shared.global [%0], [%1], 16;" :: "r"(sb + (t >> 7) * 16384 + ((r & 15) + i * 16) * 128 + sw), "l"(xp + i * 16 * D_) : "memory");
        asm volatile("cp.async.commit_group;" ::: "memory");
#pragma unroll
        for (int i = 0; i < 3; i++) asm volatile("cp.async.cg.shared.global [%0], [%1], 16;" :: "r"(sb + 36864 + i * 8192 + r * 128 + sw), "l"(wp + 96 * D_ + i * D_) : "memory");
        asm volatile("cp.async.commit_group;" ::: "memory");
    }
    const int tid = threadIdx.x, warp = __shfl_sync(0xffffffffu, tid >> 5, 0), lane = tid & 31;
    const bool elect = lane == 0;

    if (warp >= 8) {
        const int aw = warp - 9;
        auto load_o = [&](int i) {
            mbar_expect_tx(bars + 8 * (B_OF + i), 16384);
            tma_2d(sb + o_slot(i) * 16384, &tmO, bars + 8 * (B_OF + i), i * 64, rb * 256 + (hp & 1) * 128);
        };
        auto load_wo = [&](int i) {
            mbar_expect_tx(bars + 8 * (B_OF + i), 16384);
            tma_4d(sb + wo_slot(i) * 16384, &tmWo, bars + 8 * (B_OF + i), 0, (i >> 3) * 32, (i & 7) * 2, hp & 14);
        };
        if (warp == 9) {
            if (elect_one()) {
#pragma unroll
                for (int i = B_OF; i < B_COUNT; i++)
                    mbar_init(bars + 8 * i, i < B_SD ? 2 : (i < B_WPHI ? 8 : ((i < B_KV || i >= B_FF || i == B_LN) ? 1 : 4)));
                mbar_init(bars + 8 * B_OS, 1);
                asm volatile("fence.mbarrier_init.release.cluster;" ::: "memory");
            }
        }
        if (warp == 8) {
            if (elect_one()) {
#pragma unroll
                for (int i = 0; i < 3; i++) { mbar_init(bars + 8 * (B_FULL + i), 1); mbar_init(bars + 8 * (B_EMPTY + i), 8); }
                mbar_init(bars + 8 * B_XR, 1);
                asm volatile("fence.mbarrier_init.release.cluster;" ::: "memory");
                asm volatile("mbarrier.arrive.shared::cta.b64 _, [%0];" :: "r"(bars + 8 * B_FULL) : "memory");
            }
            __syncwarp();
            nb_arrive(0, NTHREADS);
        } else {
            __syncwarp();
            nb_sync(0, NTHREADS);
        }
        asm volatile("setmaxnreg.dec.sync.aligned.u32 56;");
        if (warp == 8 && elect_one()) {
            load_stage(1, 1); load_stage(2, 2);
            mbar_expect_tx(bars + 8 * B_XR, 32768);
            asm volatile("cp.async.bulk.shared::cluster.global.mbarrier::complete_tx::bytes [%0], [%1], 32768, [%2];"
                         :: "r"(sb + SM_FB + 4096), "l"(P.x + (size_t)blockIdx.x * 16 * D_), "r"(bars + 8 * B_XR) : "memory");
        }
        __syncwarp();
        nb_sync(NB_KV, 128);
        unsigned epoch;
        asm volatile("ld.relaxed.gpu.global.u32 %0, [%1];" : "=r"(epoch) : "l"(&P.scr->epoch) : "memory");
        auto get_acc = [&]() { return &P.scr->acc[epoch & 1u]; };
        if (warp == 8) {
            epoch = __shfl_sync(0xffffffffu, epoch, 0);
            int s = 0, ph = 0;
#pragma unroll 1
            for (int j = 0; j < 15; j++) {
                mbar_wait(bars + 8 * (B_EMPTY + s), ph);
                if (elect_one()) {
                    if (j < 13) load_stage(s, j + 3);
                    if (j < 2) {
                        prefetch_l2(P.wqkv + (size_t)(256 + j * 384 + blockIdx.x * 3) * 3 * D_, 18432);
                    } else if (j < 10) {
                        if (j == 2) asm volatile("mbarrier.arrive.shared::cta.b64 _, [%0];" :: "r"(bars + 8 * B_FF) : "memory");
                        const size_t o = (size_t)((j - 2) * 128 + blockIdx.x) * F_;
                        prefetch_l2(P.wg + o, F_ * 2); prefetch_l2(P.wu + o, F_ * 2);
                    }
                    if (j == JWO) prefetch_l2(P.wo + (size_t)blockIdx.x * 8 * D_, 16384);
                    if (j == 12) {
                        asm volatile("prefetch.tensormap [%0];" :: "l"(&tmO) : "memory");
                        asm volatile("prefetch.tensormap [%0];" :: "l"(&tmOs) : "memory");
                        asm volatile("prefetch.tensormap [%0];" :: "l"(&tmS.wd8) : "memory");
                        asm volatile("prefetch.tensormap [%0];" :: "l"(&tmWo) : "memory");
                        mbar_expect_tx(bars + 8 * B_WPHI, 4096);
                        tma_2d(sb + SM_WPHI, &tmPhi, bars + 8 * B_WPHI, 0, hp * 64);
                    }
                    if (j >= 13) {
                        if (blockIdx.x >= 112 || j == 13) { load_wo(2 * j - 26); load_wo(2 * j - 25); }
                        else {
                            mbar_expect_tx(bars + 8 * (B_DN + 1), 32768);
                            tma_3d(sb + 6 * 16384, &tmS.wd8, bars + 8 * (B_DN + 1), 0, blockIdx.x * 32, 8);
                        }
                    }
                }
                __syncwarp();
                if (++s == 3) { s = 0; ph ^= 1; }
                if (j == 3 && lane < ACC_VEC_PER_CTA) reinterpret_cast<uint4*>(&P.scr->acc[~epoch & 1u])[blockIdx.x * ACC_VEC_PER_CTA + lane] = make_uint4(0, 0, 0, 0);
            }
            TLP(elect, 20);
        } else {
            const bool ffn = blockIdx.x < 112;
            const uint32_t fbuf = sb + SM_FB + 4096 + aw * 12288, fbar = bars + 8 * (B_FF + 1 + aw * 3);
        const int nc = aw == 0 ? NC0 : (aw == 1 ? 12 - NC0 - NC2 : NC2), c0 = aw == 0 ? 0 : (aw == 1 ? NC0 : 12 - NC2);
        const int ng = !ffn ? 0 : (aw == 0 ? NG0 : (aw == 1 ? NG1 : 32 - NG0 - NG1)), g0 = aw == 0 ? 0 : (aw == 1 ? NG0 : NG0 + NG1);
        auto issue = [&](int i, int b) {
            __syncwarp();
            if (i < nc + ng && elect_one()) {
                mbar_expect_tx(fbar + b * 8, 4096);
                if (i < nc) {
                    tma_2d(fbuf + b * 4096, &tmS.wc, fbar + b * 8, ((c0 + i) >> 2) * 1024 + hp * 64, rb * 128 + ((c0 + i) & 3) * 32);
                } else {
                    tma_2d(fbuf + b * 4096, &tmS.wg, fbar + b * 8, blockIdx.x * 32, (g0 + i - nc) * 32);
                    tma_2d(fbuf + b * 4096 + 2048, &tmS.wu, fbar + b * 8, blockIdx.x * 32, (g0 + i - nc) * 32);
                }
            }
            __syncwarp();
        };
            {
                uint4 wv[4];
#pragma unroll
                for (int i = 0; i < 4; i++) wv[i] = __ldg(reinterpret_cast<const uint4*>(P.wr) + i * 32 + lane);
                const uint32_t* ww = reinterpret_cast<const uint32_t*>(wv);
                float sw = 0.f;
#pragma unroll
                for (int i = 0; i < 16; i++) sw += bf_lo(ww[i]) + bf_hi(ww[i]);
#pragma unroll 1
                for (int o = 16; o > 0; o >>= 1) sw += __shfl_xor_sync(0xffffffffu, sw, o);
                sts32(sb + SM_MISC + 20, __float_as_uint(sw));
                if (aw == 2) {
#pragma unroll
                    for (int i = 0; i < 3; i++) P.scr->kv[(hp * 8 + rb) * 96 + i * 32 + lane] = make_uint4(0, 0, 0, 0);
                    if (hp == 0) reinterpret_cast<uint4*>(&P.scr->cnt_o[rb * 128])[lane] = make_uint4(0, 0, 0, 0);
                    asm volatile("fence.acq_rel.gpu;" ::: "memory");
                    __syncwarp();
                }
                mbar_wait(bars + 8 * B_XR, 0);
#pragma unroll 1
                for (int r = aw * 6; r < min(aw * 6 + 6, 16); r++) {
                    const uint32_t buf = sb + SM_FB + 4096 + r * 2048;
                    uint4 xv[4];
                    uint32_t c2 = lds32(buf);
#pragma unroll
                    for (int i = 0; i < 4; i++) xv[i] = lds128(buf + i * 512 + lane * 16);
                    sts32(sb + SM_MISC + 12, 0u);
                    c2 = fabsf(bf_lo(c2) - bf_hi(c2)) < 0.25f * fabsf(bf_lo(c2)) ? dup_lo(c2) : 0u;
                    const uint32_t* xw = reinterpret_cast<const uint32_t*>(xv);
                    uint32_t d2[2] = {0u, 0u};
                    float s0 = 0.f, s1 = 0.f, q0 = 0.f, q1 = 0.f;
#pragma unroll
                    for (int i = 0; i < 16; i++) {
                        const uint32_t a = hsub2(xw[i], c2);
                        s0 += bf_lo(a); s1 += bf_hi(a);
                        d2[i & 1] = hfma2(a, ww[i], d2[i & 1]);
                        q0 = fmaf(bf_lo(a), bf_lo(a), q0); q1 = fmaf(bf_hi(a), bf_hi(a), q1);
                    }
                    sts128(sb + SM_SP + r * 512 + lane * 16, __float_as_uint(s0 + s1), __float_as_uint(q0 + q1),
                           __float_as_uint((bf_lo(d2[0]) + bf_hi(d2[0])) + (bf_lo(d2[1]) + bf_hi(d2[1]))), c2 << 16);
                }
                epoch = __shfl_sync(0xffffffffu, epoch, 0);
                if (aw < 2) nb_arrive(NB_FFN, 96);
                mbar_wait(bars + 8 * B_FF, 0);
#pragma unroll 1
                for (int i = 0; i < 3; i++) issue(i, i);
                const unsigned tag = epoch + 1u;
                if (aw == 2) {
                    nb_sync(NB_FFN, 96);
                    TLP(elect, 23);
                    float s = 0.f, q = 0.f, dt = 0.f, x0;
#pragma unroll 8
                    for (int j = 0; j < 16; j++) {
                        const uint4 e = lds128(sb + SM_SP + lane * 256 + ((j + lane) & 15) * 16);
                        s += __uint_as_float(e.x); q += __uint_as_float(e.y); dt += __uint_as_float(e.z); x0 = __uint_as_float(e.w);
                    }
                    s += __shfl_xor_sync(0xffffffffu, s, 1); q += __shfl_xor_sync(0xffffffffu, q, 1); dt += __shfl_xor_sync(0xffffffffu, dt, 1);
                    const float ms = s * (1.0f / D_);
                    const float vb = round_bf16(fmaxf(q - s * ms, 0.f) * (1.0f / D_));
                    const uint32_t md = pack_bf16(x0 + ms, sqrt_a(round_bf16(vb + 1e-5f)));
                    const uint32_t rbits = pack_bf16((dt - (bf_lo(md) - x0) * ldsf(sb + SM_MISC + 20)) * rcp(bf_hi(md)), 0.f);
                    const int row = blockIdx.x * 16 + (lane >> 1);
                    const uint32_t key = ((((rbits & 0x8000u) ? (~rbits & 0xFFFFu) : (rbits | 0x8000u)) + 1u) << 11) | (uint32_t)(2047 - row);
                    asm volatile("st.relaxed.gpu.global.v2.u32 [%0], {%1, %2};" :: "l"(&P.scr->rows[row]), "r"(md), "r"(tag) : "memory");
                    if (key == __reduce_max_sync(0xffffffffu, key))
                        asm volatile("st.relaxed.gpu.global.v4.u32 [%0], {%1, %2, %3, %3};" :: "l"(&P.scr->best[blockIdx.x]), "r"(key), "r"(md), "r"(tag) : "memory");
                    TLP(elect, 24);
                }
                {
                    float a[8], sq = 0.f, wt = 0.f;
#pragma unroll
                    for (int i = 0; i < 8; i++) a[i] = 0.f;
#pragma unroll 1
                    for (int m = 0; m < nc; m++) {
                        const int b = m % 3, c = c0 + m;
                        mbar_wait(fbar + b * 8, (m / 3) & 1);
                        uint4 v[8];
#pragma unroll
                        for (int i = 0; i < 8; i++) v[i] = lds128(fbuf + b * 4096 + i * 512 + lane * 16);
                        sts32(sb + SM_MISC + 12, 0u);
                        colsum8<true>(a, sq, v);
                        fence_regs(a);
                        wt += 1.0f;
                        issue(m + 3, b);
                        if ((c & 3) == 3 || m == nc - 1) {
#pragma unroll 1
                            for (int o = 8; o <= 16; o <<= 1) {
#pragma unroll
                                for (int i = 0; i < 8; i++) a[i] += __shfl_xor_sync(0xffffffffu, a[i], o);
                                sq += __shfl_xor_sync(0xffffffffu, sq, o);
                            }
                            float4* dst = &get_acc()->cs[((c >> 2) * 16 + hp) * 24 + lane];
                            if (lane < 8) { red_v4(dst, a[0], a[1], a[2], wt); red_v4(dst + 8, a[3], a[4], a[5], wt); red_v4(dst + 16, a[6], a[7], sq, wt); }
#pragma unroll
                            for (int i = 0; i < 8; i++) a[i] = 0.f;
                            wt = 0.f;
                        }
                    }
                    TLP(tid == 288, 26); TLP(tid == 320, 15); TLP(tid == 352, 22);
                }
                if (aw == 0) {
                    uint4 v[4];
                    unsigned it = 0;
                    bool ok = true;
#pragma unroll 1
                    do {
                        if (!ok) __nanosleep(200);
#pragma unroll
                        for (int i = 0; i < 4; i++) v[i] = ld_gpu(&P.scr->best[i * 32 + lane]);
                        ok = v[0].z == tag && v[1].z == tag && v[2].z == tag && v[3].z == tag;
                    } while (!__all_sync(0xffffffffu, ok) && ++it < (1u << 20));
#pragma unroll
                    for (int i = 1; i < 4; i++) if (v[i].x > v[0].x) v[0] = v[i];
                    const uint32_t key = __reduce_max_sync(0xffffffffu, v[0].x);
                    const uint32_t md = __reduce_or_sync(0xffffffffu, v[0].x == key ? v[0].y : 0u);
                    const int sel = 2047 - (int)(key & 2047u);
                    const uint4* xp = reinterpret_cast<const uint4*>(P.x + (size_t)sel * D_) + lane;
#pragma unroll
                    for (int i = 0; i < 4; i++) v[i] = __ldg(xp + i * 32);
                    const uint32_t m2 = __byte_perm(md, 0, 0x1010);
                    const float rs = rcp(bf_hi(md));
                    const uint32_t ord = (key >> 11) - 1u;
                    const float r = __uint_as_float(((ord & 0x8000u) ? (ord & 0x7FFFu) : (~ord & 0xFFFFu)) << 16);
                    sts128(sb + SM_MISC, (uint32_t)sel, __float_as_uint(round_bf16(rcp(1.0f + ex2(-r * LOG2E)))), epoch, 0u);
#pragma unroll
                    for (int i = 0; i < 4; i++) {
                        const uint32_t e0 = ln_pair(v[i].x, m2, rs), e1 = ln_pair(v[i].y, m2, rs), e2 = ln_pair(v[i].z, m2, rs), e3 = ln_pair(v[i].w, m2, rs);
                        const uint32_t xa = sb + SM_XS + i * 512 + (lane >> 2) * 64 + (lane & 3) * 4;
                        sts32(xa, __byte_perm(e0, e2, 0x5410)); sts32(xa + 16, __byte_perm(e0, e2, 0x7632));
                        sts32(xa + 32, __byte_perm(e1, e3, 0x5410)); sts32(xa + 48, __byte_perm(e1, e3, 0x7632));
                    }
                    TLP(elect, 25);
                    __syncwarp();
                    mbar_arrive_if(elect, bars + 8 * B_XS);
                }
            }
            if (aw == 2) {
                    const int l = lane < 24 ? lane : 0;
                    const float4* src = &get_acc()->cs[((l >> 3) * 16 + hp) * 24 + (l & 7)];
                    float4 v0, v1, v2;
                    uint4 v[4];
                    unsigned it = 0;
                    bool ok;
#pragma unroll 1
                    do {
                        v0 = ld_gpu(src); v1 = ld_gpu(src + 8); v2 = ld_gpu(src + 16);
                        ok = v0.w == 32.0f && v1.w == 32.0f && v2.w == 32.0f;
#pragma unroll
                        for (int i = 0; i < 4; i++) v[i] = ld_gpu(reinterpret_cast<const uint4*>(&P.scr->rows[rb * 256]) + i * 32 + lane);
#pragma unroll
                        for (int i = 0; i < 4; i++) ok = ok && v[i].y == epoch + 1u && v[i].w == epoch + 1u;
                    } while (!__all_sync(0xffffffffu, ok) && ++it < (1u << 20));
#pragma unroll
                    for (int i = 0; i < 4; i++) {
                        const uint32_t o = i * 256 + lane * 8;
                        sts64(sb + SM_MD + o, v[i].x, v[i].z);
                        sts64(sb + SM_RS + o, __float_as_uint(rcp(bf_hi(v[i].x))), __float_as_uint(rcp(bf_hi(v[i].z))));
                        const uint32_t h0 = hmul2(dup_lo(v[i].x), 0xBF00BF00u), h1 = hmul2(dup_lo(v[i].z), 0xBF00BF00u);
                        sts128(sb + SM_AX + o * 4, h0, h0 & 0xFFFFu, 0u, 0u);
                        sts128(sb + SM_AX + o * 4 + 16, h1, h1 & 0xFFFFu, 0u, 0u);
                    }
                    sts128(sb + SM_H + lane * 16, 0u, 0u, 0u, 0u); sts128(sb + SM_H + 512 + lane * 16, 0u, 0u, 0u, 0u);
                    const uint32_t e2 = __reduce_max_sync(0xffffffffu, l >= 16 ? __float_as_uint(v2.z) : 0u) >> 23;
                    sts32(sb + SM_MISC + 16, (uint32_t)min(max(187 - (int)((e2 + 1) >> 1), 1), 180) << 23);
                    float cc[8] = {v0.x, v0.y, v0.z, v1.x, v1.y, v1.z, v2.x, v2.y};
                    const uint32_t bx = sb + SM_BX + (l >> 3) * 1024;
#pragma unroll 1
                    for (int k = 0; k < 8; k++) {
                        uint32_t w[4];
#pragma unroll
                        for (int i = 0; i < 4; i++) {
                            w[i] = pack_bf16(cc[2 * i], cc[2 * i + 1]);
                            cc[2 * i] -= bf_lo(w[i]); cc[2 * i + 1] -= bf_hi(w[i]);
                        }
                        sts128(bx + k * 128 + (((l & 7) ^ k) * 16), w[0], w[1], w[2], w[3]);
                    }
                    fence_async_smem();
                    __syncwarp();
                    mbar_arrive_if(elect, bars + 8 * B_LN);
                    TLP(elect, 28);
                }
            mbar_wait(bars + 8 * B_XS, 0);
            if (ffn) {
                float a[8];
#pragma unroll
                for (int i = 0; i < 8; i++) a[i] = 0.f;
                TLP(elect, 40 + aw);
                gemv_run<256>(a, ng, nc % 3, (nc / 3) & 1, fbuf + (lane >> 4) * 2048 + (lane & 15) * 16, sb + SM_XS + g0 * 64 + (lane & 12) * 4, 64, fbar, sb + SM_MISC + 12,
                              [&](int m, int b) { issue(nc + m + 3, b); });
                TLP(elect, 44 + aw);
#pragma unroll 1
                for (int o = 4; o <= 8; o <<= 1) {
#pragma unroll
                    for (int i = 0; i < 8; i++) a[i] += __shfl_xor_sync(0xffffffffu, a[i], o);
                }
                if ((lane & 12) == 0) {
                    const uint32_t ga = sb + SM_GU + aw * 256 + (lane >> 4) * 128 + (lane & 3) * 32;
                    sts128(ga, __float_as_uint(a[0]), __float_as_uint(a[1]), __float_as_uint(a[2]), __float_as_uint(a[3]));
                    sts128(ga + 16, __float_as_uint(a[4]), __float_as_uint(a[5]), __float_as_uint(a[6]), __float_as_uint(a[7]));
                }
                nb_sync(NB_AUX, 96);
                if (warp == 9) {
                    if (elect_one()) {
                        mbar_expect_tx(bars + 8 * B_DN, 32768);
                        tma_3d(sb + SM_FB + 8192, &tmS.wd8, bars + 8 * B_DN, 0, blockIdx.x * 32, 0);
                    }
                    const uint32_t ga = sb + SM_GU + lane * 4;
                    const float gg = round_bf16((ldsf(ga) + ldsf(ga + 256)) + ldsf(ga + 512));
                    const float uu = round_bf16((ldsf(ga + 128) + ldsf(ga + 384)) + ldsf(ga + 640));
                    asm volatile("st.shared.u16 [%0], %1;" :: "r"(sb + SM_H + (lane >> 3) * 256 + 112 + (lane & 7) * 2), "h"((uint16_t)pack_bf16(round_bf16(silu_f(gg)) * uu, 0.f)) : "memory");
                    fence_async_smem();
                }
                __syncwarp();
                TLP(tid == 288, 27);
            }
        }
        {
            TLP(tid == 288, 38);
            const int w4 = warp & 3;
            const uint32_t sp = sb + SM_FB + w4 * 1536;
            auto send = [&](int h) {
                if (elect_one()) {
                    asm volatile("cp.reduce.async.bulk.global.shared::cta.bulk_group.add.noftz.f16 [%0], [%1], 1536;"
                                 :: "l"(&P.scr->kv[(hp * 8 + h * 4 + w4) * 96]), "r"(sp) : "memory");
                    asm volatile("cp.async.bulk.commit_group;" ::: "memory");
                }
            };
            float ya[4] = {0.f, 0.f, 0.f, 0.f}, yb[4] = {0.f, 0.f, 0.f, 0.f};
            uint4 g0[3];
#pragma unroll 1
            for (int h = 0; h < 2; h++) {
                {
                    float d[20];
                    const uint32_t alo = dlo(sb + SM_PHI + h * 32768, 16), vlo = dlo(sb + SM_V + h * 20480, 16);
                    mbar_wait(bars + 8 * (B_PHI + h), 0);
                    wgmma_fence();
#pragma unroll
                    for (int k = 0; k < 16; k++)
                        wgmma_ss_n40(d, desc_from(alo + (k >> 2) * 512 + (k & 3) * 2, DH128), desc_from(vlo + (k >> 2) * 320 + (k & 3) * 2, DH128), k);
                    wgmma_commit();
#pragma unroll
                    for (int j = 0; j < 3; j++) g0[j] = ld_gpu(&P.scr->kv[(hp * 8 + w4) * 96 + j * 32 + lane]);
                    asm volatile("cp.async.bulk.wait_group.read 0;" ::: "memory");
                    __syncwarp();
                    const float ksc = ldsf(sb + SM_MISC + 16);
                    wgmma_wait<0>();
                    fence_regs(d);
#define U(x) pack_f16(d[x] * ksc, d[x + 1] * ksc)
                    sts128(sp + lane * 16, U(0), U(4), U(8), pack_f16(d[16], 1.0f));
                    sts128(sp + 512 + lane * 16, U(2), U(6), U(10), pack_f16(d[18], 1.0f));
                    sts128(sp + 1024 + lane * 16, U(12), U(14), 0u, 0x3C000000u);
#undef U
                    fence_async_smem();
                    __syncwarp();
                    send(h);
                    TLP(tid == 256, 30 + h);
                    nb_sync(NB_KV, 128);
                    if (h) break;
                    if (warp == 8 && elect_one()) {
                        mbar_expect_tx(bars + 8 * B_X, 32768);
                        tma_2d(sb, &tmX2, bars + 8 * B_X, (hp >> 1) * 128, rb * 256 + (hp & 1) * 128);
                        tma_2d(sb + 16384, &tmX2, bars + 8 * B_X, (hp >> 1) * 128 + 64, rb * 256 + (hp & 1) * 128);
                        load_wo(4);
                    }
                    __syncwarp();
                }
                if (blockIdx.x < 112) {
                    const uint32_t hlo = dlo(sb + SM_H, 256);
                    mbar_wait(bars + 8 * B_DN, 0);
                    mbar_wait(bars + 8 * (B_DN + 1), 0);
                    wgmma_fence();
#pragma unroll 2
                    for (int k = 0; k < 16; k++) {
                        wgmma_ss_n8_ta(yb, desc_from(dlo(sb + 6 * 16384, 16) + k * 128, DH128), desc_from(hlo + (k & 1) * 32 + 7 - (k >> 1), 8), k);
                        wgmma_ss_n8_ta(ya, desc_from(dlo(sb + SM_FB + 8192, 16) + k * 128, DH128), desc_from(hlo + (k & 1) * 32 + 7 - (k >> 1), 8), k);
                    }
                    wgmma_commit();
                    wgmma_wait<0>();
                    fence_regs(ya); fence_regs(yb);
                    if (warp == 8) {
                        nb_sync(NB_KV, 128);
                        if (elect_one()) { load_wo(2); load_wo(3); }
                        __syncwarp();
                    } else {
                        nb_arrive(NB_KV, 128);
                    }
                    TLP(tid == 288, 29);
                }
            }
            const float kus = __uint_as_float((254u << 23) - lds32(sb + SM_MISC + 16));
            kv_gather<1>(g0, &P.scr->kv[(hp * 8 + w4) * 96 + lane], sb + SM_KVOP + w4 * 256, lane, kus);
            mbar_arrive_if(elect, bars + 8 * B_KV);
            asm volatile("cp.async.bulk.wait_group.read 0;" ::: "memory");
            __syncwarp();
            if (blockIdx.x < 112) {
#define U(x) __float_as_uint(x)
                sts128(sp + lane * 16, U(ya[0]), U(ya[1]), U(ya[2]), U(1.0f));
                sts128(sp + 512 + lane * 16, U(ya[3]), U(yb[0]), U(yb[1]), U(1.0f));
                sts128(sp + 1024 + lane * 16, U(yb[2]), U(yb[3]), 0u, U(1.0f));
#undef U
                fence_async_smem();
                __syncwarp();
                if (elect_one()) {
                    asm volatile("cp.reduce.async.bulk.global.shared::cta.bulk_group.add.f32 [%0], [%1], 1536;"
                                 :: "l"(&get_acc()->y[((blockIdx.x & 3) * 4 + w4) * 96]), "r"(sp) : "memory");
                    asm volatile("cp.async.bulk.commit_group;" ::: "memory");
                }
                __syncwarp();
            }
            if (w4 >= 2) {
                uint4 g1[6];
#pragma unroll
                for (int j = 0; j < 6; j++) g1[j] = make_uint4(0, 0, 0, 0);
                kv_gather<2>(g1, &P.scr->kv[(hp * 8 + 2 * w4) * 96 + lane], sb + SM_KVOP - 5120 + (w4 - 2) * 512, lane, kus);
                mbar_arrive_if(lane < 2, bars + 8 * (B_KV + 1));
            }
            asm volatile("cp.async.bulk.wait_group.read 0;" ::: "memory");
            __syncwarp();
            mbar_arrive_if(elect, bars + 8 * B_S1);
        }
        if (warp == 8) {
            if (elect_one()) {
                uint4 cnt;
                mbar_wait(bars + 8 * B_O, 0);
#pragma unroll
                for (int i = 0; i < 16; i++) {
                    if (!(i & 3)) cnt = make_uint4(0, 0, 0, 0);
                    unsigned it = 0;
#pragma unroll 1
                    while (((i & 3) == 0 ? cnt.x : ((i & 3) == 1 ? cnt.y : ((i & 3) == 2 ? cnt.z : cnt.w))) < 2u && ++it < (1u << 20))
                        cnt = ld_gpu(reinterpret_cast<const uint4*>(&P.scr->cnt_o[rb * 128 + (i >> 3) * 32 + (i & 4)]));
                    if (PFENCE) asm volatile("fence.proxy.async.global;" ::: "memory");
                    if ((i & 3) == 0 && i < 12) TL(i == 0 ? 21 : (i == 4 ? 34 : 36));
                    if (i == 4 || i > 5) mbar_wait(bars + 8 * (B_SD + max(i - 5, 0)), 0);
                    load_o(i);
                    if (i == 3) { load_wo(5); mbar_wait(bars + 8 * B_S1, 0); load_wo(6); }
                    if (i >= 5 && i < 14) load_wo(i + 2);
                }
            }
        } else if (warp < 11) {
            if (elect_one()) {
                mbar_wait(bars + 8 * (B_O + aw), 0);
                asm volatile("cp.async.bulk.tensor.2d.global.shared::cta.bulk_group [%0, {%2, %3}], [%1];"
                             :: "l"(&tmOs), "r"(sb + SM_OS), "r"(aw * 512 + hp * 32), "r"(rb * 256) : "memory");
                asm volatile("cp.async.bulk.commit_group;" ::: "memory");
                asm volatile("cp.async.bulk.wait_group 0;" ::: "memory");
                if (PFENCE) asm volatile("fence.proxy.async.global;" ::: "memory");
                asm volatile("red.relaxed.gpu.global.add.u32 [%0], 1;" :: "l"(&P.scr->cnt_o[rb * 128 + aw * 32 + (hp >> 1)]) : "memory");
                asm volatile("mbarrier.arrive.shared::cta.b64 _, [%0];" :: "r"(bars + 8 * B_OS) : "memory");
                TL(35 + 2 * aw);
            }
        } else if (warp == 11) {
            const uint4 misc = lds128(sb + SM_MISC);
            if ((int)(misc.x >> 7) == rb * 2 + (hp & 1)) {
                float y[4] = {0.f, 0.f, 0.f, 0.f};
#pragma unroll 1
                for (int rep = 0; rep < 4; rep++) {
                    const float4* yp = &get_acc()->y[(rep * 4 + (lane >> 3)) * 96 + (hp >> 3) * 32 + (lane & 7) * 4 + ((hp >> 1) & 3)];
                    float4 u, v;
                    unsigned it = 0;
#pragma unroll 1
                    do { u = ld_gpu(yp); v = ld_gpu(yp + 32); } while (!__all_sync(0xffffffffu, u.w == 28.0f && v.w == 28.0f) && ++it < (1u << 20));
                    if (hp & 8) { y[0] += u.y; y[1] += v.x; y[2] += u.z; y[3] += v.y; } else { y[0] += u.x; y[1] += u.z; y[2] += u.y; y[3] += v.x; }
                }
                const uint32_t sg = __byte_perm(misc.y, 0, 0x3232), ya = sb + SM_Y + ((lane >> 3) * 16 + (lane & 7)) * 2;
                const uint32_t w0 = hmul2(pack_bf16(y[0], y[1]), sg), w1 = hmul2(pack_bf16(y[2], y[3]), sg);
                asm volatile("st.shared.u16 [%0], %1;" :: "r"(ya), "h"((uint16_t)w0) : "memory");
                asm volatile("st.shared.u16 [%0], %1;" :: "r"(ya + 16), "h"((uint16_t)(w0 >> 16)) : "memory");
                asm volatile("st.shared.u16 [%0], %1;" :: "r"(ya + 128), "h"((uint16_t)w1) : "memory");
                asm volatile("st.shared.u16 [%0], %1;" :: "r"(ya + 144), "h"((uint16_t)(w1 >> 16)) : "memory");
                __syncwarp();
                if (lane < 16) {
                    const uint4 xc = __ldg(reinterpret_cast<const uint4*>(P.x + (size_t)misc.x * D_ + (hp >> 1) * 128) + lane);
                    const uint32_t m2 = __byte_perm(lds32(sb + SM_MD + (misc.x & 255u) * 4), 0, 0x1010);
                    const float r = ldsf(sb + SM_RS + (misc.x & 255u) * 4);
                    const uint4 yv = lds128(sb + SM_Y + lane * 16);
                    sts128(sb + SM_Y + lane * 16, silu_pair(hadd2(ln_pair(xc.x, m2, r), yv.x)), silu_pair(hadd2(ln_pair(xc.y, m2, r), yv.y)),
                           silu_pair(hadd2(ln_pair(xc.z, m2, r), yv.z)), silu_pair(hadd2(ln_pair(xc.w, m2, r), yv.w)));
                    sts128(sb + SM_Y + 256 + lane * 16, xc.x, xc.y, xc.z, xc.w);
                }
                __syncwarp();
                mbar_arrive_if(elect, bars + 8 * B_Y);
                TLP(elect, 39);
            }
        }
    } else {
        const int wg = warp >> 2, w4 = warp & 3, g = lane >> 2;
        nb_sync(0, NTHREADS);
        asm volatile("setmaxnreg.inc.sync.aligned.u32 224;");
        TLP(tid == 0, 1);
        const int row0 = wg * 128 + w4 * 16 + g;
        float pq0[16], pq1[16];
        float rs[4];
        uint32_t f2[8], f3[8], q0[8], q1[8], q2[8], q3[8];
        float qa[16], qb[16];
        const uint32_t wlo = dlo(sb + SM_WPHI, 16);
        const uint32_t sw0 = (uint32_t)(((w4 * 2) ^ (lane & 7)) * 16), sw1 = sw0 ^ 16u;
        {
            float acc0[96], acc1[96];
            {
                const uint32_t alo0 = dlo(sb + wg * 16384, 16), blo0 = dlo(sb + 32768, 8192);
                {
#pragma unroll
                    for (int k = 0; k < 4; k++) {
                        if (k == 0) asm volatile("cp.async.wait_group 1;" ::: "memory");
                        if (k == 2) { wgmma_commit(); asm volatile("cp.async.wait_group 0;" ::: "memory"); }
                        if (!(k & 1)) { fence_async_smem(); nb_sync(NB_STAG, 256); wgmma_fence(); }
                        if (k == 0) { TLP(tid == 0, 2); TLG(tid == 0, 49); }
                        wgmma_ss_n192_tb(acc0, desc_from(alo0 + k * 2, DH128), desc_from(blo0 + k * 128, DH128), k);
                        wgmma_ss_n192_tb(acc1, desc_from(alo0 + 512 + k * 2, DH128), desc_from(blo0 + k * 128, DH128), k);
                    }
                    wgmma_commit();
                }
                int s = 1, ph = 0, ps = 0;
#pragma unroll 1
                for (int ks = 1; ks < 16; ks++) {
                    const bool hold = wg && ks == 15;
                    if (hold) {
                        wgmma_wait<0>();
                        mbar_arrive_if(elect, bars + 8 * (B_EMPTY + ps));
                        nb_sync(NB_LEAD, 256);
                    }
                    mbar_wait(bars + 8 * (B_FULL + s), ph);
                    const uint32_t alo = alo0 + s * (STAGE >> 4), blo = blo0 + s * (STAGE >> 4);
                    wgmma_fence();
#pragma unroll
                    for (int k = 0; k < 4; k++) {
                        if (k == SARR && !wg && ks == 15) nb_arrive(NB_LEAD, 256);
                        wgmma_ss_n192_tb(acc0, desc_from(alo + k * 2, DH128), desc_from(blo + k * 128, DH128), 1);
                        wgmma_ss_n192_tb(acc1, desc_from(alo + 512 + k * 2, DH128), desc_from(blo + k * 128, DH128), 1);
                        if (k == 0) {
                            wgmma_commit();
                            wgmma_wait<1>();
                            mbar_arrive_if(elect && !hold, bars + 8 * (B_EMPTY + ps));
                        }
                    }
                    wgmma_commit();
                    ps = s;
                    if (++s == 3) { s = 0; ph ^= 1; }
                }
            }
            mbar_wait(bars + 8 * B_LN, 0);
            wgmma_fence();
            wgmma_ss_n192_tb(acc0, desc_from(dlo(sb + SM_AX + wg * 2048, 0), 128u >> 4), desc_from(dlo(sb + SM_BX, 1024), 1u << 30), 1);
            wgmma_ss_n192_tb(acc1, desc_from(dlo(sb + SM_AX + wg * 2048 + 1024, 0), 128u >> 4), desc_from(dlo(sb + SM_BX, 1024), 1u << 30), 1);
            wgmma_commit();
            mbar_wait(bars + 8 * (B_EMPTY + 2), 0);
            mbar_wait(bars + 8 * B_WPHI, 0);
            {
                uint32_t md[4];
#pragma unroll
                for (int i = 0; i < 4; i++) {
                    const int r = row0 + (i >> 1) * 64 + (i & 1) * 8;
                    md[i] = __byte_perm(lds32(sb + SM_MD + r * 4), 0, 0x3232);
                    rs[i] = ldsf(sb + SM_RS + r * 4);
                }
                const uint32_t zb = sb + SM_V + wg * 10240 + (lane >> 4) * 5120 + 4096 + (lane & 7) * 128 + (sw0 ^ ((lane & 8) * 2));
                stsm_t(zb, md[0], md[1], md[2], md[3]);
                stsm_t(zb + 20480, md[0], md[1], md[2], md[3]);
            }
            wgmma_wait<0>();
            fence_regs(acc0); fence_regs(acc1);
            TLP(tid == 0, 3); TLG(tid == 0, 50);
            const uint32_t vb = sb + SM_V + wg * 10240 + lane * 128;
            uint32_t f0[8], f1[8], v[8];
            pack_head<64>(acc0, v); stsm_t(vb + sw0, v[0], v[2], v[4], v[6]); stsm_t(vb + sw1, v[1], v[3], v[5], v[7]);
            pack_head<64>(acc1, v); stsm_t(vb + 5120 + sw0, v[0], v[2], v[4], v[6]); stsm_t(vb + 5120 + sw1, v[1], v[3], v[5], v[7]);
#pragma unroll
            for (int i = 32; i < 48; i++) { asm volatile("" : "+f"(acc0[i]) :: "memory"); asm volatile("" : "+f"(acc1[i]) :: "memory"); }
            pack_head<32>(acc0, f0); pack_head<32>(acc1, f1);
            wgmma_fence();
            feat_mma(pq0, f0, wlo); feat_mma(pq1, f1, wlo);
            wgmma_commit();
            pack_head<80>(acc0, v); stsm_t(vb + 20480 + sw0, v[0], v[2], v[4], v[6]); stsm_t(vb + 20480 + sw1, v[1], v[3], v[5], v[7]);
            pack_head<80>(acc1, v); stsm_t(vb + 25600 + sw0, v[0], v[2], v[4], v[6]); stsm_t(vb + 25600 + sw1, v[1], v[3], v[5], v[7]);
            pack_head<48>(acc0, f2); pack_head<48>(acc1, f3);
            pack_head<0>(acc0, q0); pack_head<0>(acc1, q1);
#pragma unroll
            for (int i = 0; i < 16; i++) { qa[i] = acc0[16 + i]; qb[i] = acc1[16 + i]; }
            fence_regs(f2); fence_regs(f3); fence_regs(q0); fence_regs(q1);
            wgmma_wait<0>();
            fence_regs(pq0); fence_regs(pq1); fence_regs(f0); fence_regs(f1);
            mbar_arrive_if(elect, bars + 8 * B_T);
            TLP(tid == 0, 4);
        }
#pragma unroll 1
        for (int h = 0; h < 2; h++) {
            const uint32_t pb = sb + SM_PHI + wg * 16384 + lane * 128 + h * 32768;
            key_head(pq0, pq1, rs, pb + sw0, pb + sw1);
            wgmma_fence();
            feat_mma(pq0, f2, wlo + 128 - h * 128); feat_mma(pq1, f3, wlo + 128 - h * 128);
            wgmma_commit();
            fence_async_smem();
            __syncwarp();
            mbar_arrive_if(elect, bars + 8 * (B_PHI + h));
            TLP(tid == 0, 6 + 2 * h);
            mbar_wait(bars + 8 * B_T, 0);
            wgmma_wait<0>();
            fence_regs(pq0); fence_regs(pq1); fence_regs(f2); fence_regs(f3);
#pragma unroll
            for (int j = 0; j < 8; j++) { f2[j] = q0[j]; f3[j] = q1[j]; }
            fence_regs(f2); fence_regs(f3);
        }
#pragma unroll
        for (int j = 0; j < 8; j++) { q2[j] = pack_bf16(qa[2 * j], qa[2 * j + 1]); q3[j] = pack_bf16(qb[2 * j], qb[2 * j + 1]); }
        const int orow = (hp & 1) * 128 + wg * 64 + w4 * 16 + (lane >> 4);
        const size_t goff = (size_t)(rb * 256 + orow) * D_ + (hp >> 1) * 128 + (lane & 15) * 8;
        uint4 gv[8], xv[8];
#pragma unroll
        for (int i = 0; i < 8; i++) xv[i] = make_uint4(0, 0, 0, 0);
#pragma unroll
        for (int i = 0; i < GSPLIT2; i++) gv[i] = make_uint4(0, 0, 0, 0);
        const uint32_t rowc = sb + ((lane >> 3) & 1) * 16384 + (wg * 64 + w4 * 16 + (lane >> 4)) * 128;
        {
            const uint32_t od = sb + SM_OS + (wg * 128 + w4 * 16) * 64 + lane * 16;
#pragma unroll 1
            for (int h = 0; h < 2; h++) {
                uint32_t pa[8], na[8], pb[8], nb[8];
                features(pq0, pq1, rs, pa, na, pb, nb);
                TLP(tid == 0, 16 + h);
                if (h == 0) {
                    wgmma_fence();
                    feat_mma(pq0, q2, wlo + 128); feat_mma(pq1, q3, wlo + 128);
                    wgmma_commit();
                    mbar_wait(bars + 8 * B_X, 0);
#pragma unroll
                    for (int i = 0; i < 8; i++) xv[i] = lds128(rowc + i * 256 + (((lane & 7) ^ ((2 * i + (lane >> 4)) & 7)) * 16));
#pragma unroll
                    for (int i = 0; i < GSPLIT; i++) { gv[i] = xv[i]; gate_item(gv[i], sb, orow + 2 * i); }
                    wgmma_wait<0>();
                    fence_regs(pq0); fence_regs(pq1); fence_regs(q2); fence_regs(q3);
                    TLP(tid == 0, 18);
                } else {
#pragma unroll
                    for (int i = GSPLIT; i < GSPLIT2; i++) { gv[i] = xv[i]; gate_item(gv[i], sb, orow + 2 * i); }
                    TLP(tid == 0, 10);
                }
                {
                    float d0[20], e0[20], d1[20], e1[20];
                    const uint32_t klo = dlo(sb + SM_KVOP - h * 5120, 128);
                    fence_regs(pa); fence_regs(na); fence_regs(pb); fence_regs(nb);
                    mbar_wait(bars + 8 * (B_KV + h), 0);
                    TLP(tid == 0, 32 + h);
                    wgmma_fence();
                    o_mma(d0, e0, pa, na, klo);
                    o_mma(d1, e1, pb, nb, klo);
                    wgmma_commit();
                    wgmma_wait<0>();
                    fence_regs(d0); fence_regs(e0); fence_regs(pa); fence_regs(na);
                    fence_regs(d1); fence_regs(e1); fence_regs(pb); fence_regs(nb);
                    if (h) mbar_wait(bars + 8 * B_OS, 0);
                    o_store(d0, e0, od);
                    o_store(d1, e1, od + 4096);
                    fence_async_smem();
                    __syncwarp();
                    mbar_arrive_if(elect, bars + 8 * (B_O + h));
                }
                TLP(tid == 0, 9 + 2 * h);
            }
        }
        float ghr[8], ghm[8];
#pragma unroll
        for (int i = GSPLIT2; i < 8; i++) { ghr[i] = 0.5f * ldsf(sb + SM_RS + (orow + 2 * i) * 4); ghm[i] = -bf_lo(lds32(sb + SM_MD + (orow + 2 * i) * 4)) * ghr[i]; }
        float acc[64];
        {
            const uint32_t alo0 = dlo(sb + wg * 8192, 16), blo0 = dlo(sb, 8192);
#pragma unroll
            for (int i = 0; i < 16; i++) {
                const uint32_t alo = alo0 + o_slot(i) * 1024, blo = blo0 + wo_slot(i) * 1024;
                mbar_wait(bars + 8 * (B_OF + i), 0);
                if (i == OSTAG && wg == 0) nb_sync(NB_STAG, 256);
                wgmma_fence();
#pragma unroll
                for (int k = 0; k < 4; k++) {
                    if (i == 15 && k == OARR && wg) nb_arrive(NB_STAG, 256);
                    wgmma_ss_n128_tb(acc, desc_from(alo + k * 2, DH128), desc_from(blo + k * 128, DH128), k | i);
                    if (k == OREL) {
                        if (i > 0 && i < 12) {
                            wgmma_commit();
                            wgmma_wait<1>();
                            mbar_arrive_if(elect, bars + 8 * (B_SD + i - 1));
                        }
                    }
                }
                wgmma_commit();
                if (i == 0) { TLP(tid == 0, 12); TLG(tid == 0, 51); }
                static_assert(2 * (8 - GSPLIT2) <= 16 - GST, "");
                if (i >= GST && GSPLIT2 + (i - GST) / 2 < 8) {
                    const int q = GSPLIT2 + (i - GST) / 2;
                    if ((i - GST) & 1) { gv[q].z = gate_pair(xv[q].z, ghr[q], ghm[q]); gv[q].w = gate_pair(xv[q].w, ghr[q], ghm[q]); asm volatile("" : "+r"(gv[q].z), "+r"(gv[q].w) :: "memory"); }
                    else { gv[q].x = gate_pair(xv[q].x, ghr[q], ghm[q]); gv[q].y = gate_pair(xv[q].y, ghr[q], ghm[q]); asm volatile("" : "+r"(gv[q].x), "+r"(gv[q].y) :: "memory"); }
                }
            }
        }
        wgmma_wait<0>();
        fence_regs(acc);
        TLP(tid == 0, 13); TLG(tid == 0, 52);
        {
            const uint32_t stg = sb + (wg * 64 + w4 * 16) * 128;
            const int rr = lane & 7;
#pragma unroll
            for (int c = 0; c < 4; c++) {
                const uint32_t a0 = stg + (c >> 1) * 16384 + rr * 128 + ((((c & 1) * 4 + (lane >> 3)) ^ rr) * 16);
                stsm(a0, pack_bf16(acc[c * 16 + 0], acc[c * 16 + 1]), pack_bf16(acc[c * 16 + 4], acc[c * 16 + 5]),
                     pack_bf16(acc[c * 16 + 8], acc[c * 16 + 9]), pack_bf16(acc[c * 16 + 12], acc[c * 16 + 13]));
                stsm(a0 + 1024, pack_bf16(acc[c * 16 + 2], acc[c * 16 + 3]), pack_bf16(acc[c * 16 + 6], acc[c * 16 + 7]),
                     pack_bf16(acc[c * 16 + 10], acc[c * 16 + 11]), pack_bf16(acc[c * 16 + 14], acc[c * 16 + 15]));
            }
            __syncwarp();
#pragma unroll
            for (int i = 0; i < 8; i++) {
                const uint4 sv = lds128(rowc + i * 256 + (((lane & 7) ^ ((2 * i + (lane >> 4)) & 7)) * 16));
                uint4 o;
                o.x = hadd2(xv[i].x, hmul2(sv.x, gv[i].x)); o.y = hadd2(xv[i].y, hmul2(sv.y, gv[i].y));
                o.z = hadd2(xv[i].z, hmul2(sv.z, gv[i].z)); o.w = hadd2(xv[i].w, hmul2(sv.w, gv[i].w));
                *reinterpret_cast<uint4*>(P.out + goff + (size_t)i * 2 * D_) = o;
            }
            const uint32_t sel = lds32(sb + SM_MISC);
            if ((int)(sel >> 4) == rb * 16 + (orow >> 4)) {
                mbar_wait(bars + 8 * B_Y, 0);
                if ((sel & 1u) == (uint32_t)(lane >> 4)) {
                    const int i = (sel & 15u) >> 1;
                    const uint4 sv = lds128(rowc + i * 256 + (((lane & 7) ^ (sel & 7u)) * 16));
                    const uint4 gq = lds128(sb + SM_Y + (lane & 15) * 16), xq = lds128(sb + SM_Y + 256 + (lane & 15) * 16);
                    *reinterpret_cast<uint4*>(P.out + goff + (size_t)i * 2 * D_) = make_uint4(hadd2(xq.x, hmul2(sv.x, gq.x)), hadd2(xq.y, hmul2(sv.y, gq.y)), hadd2(xq.z, hmul2(sv.z, gq.z)), hadd2(xq.w, hmul2(sv.w, gq.w)));
                }
            }
        }
        TLG(tid == 0, 53);
        if (tid == 0) { TL(14); TL_DUMP(); }
        if (blockIdx.x == 0 && tid == 0) asm volatile("st.relaxed.gpu.global.u32 [%0], %1;" :: "l"(&P.scr->epoch), "r"(lds32(sb + SM_MISC + 8) + 1u) : "memory");
    }
}

typedef CUresult (*PFN_encodeTiled)(CUtensorMap*, CUtensorMapDataType, cuuint32_t, void*, const cuuint64_t*, const cuuint64_t*,
                                    const cuuint32_t*, const cuuint32_t*, CUtensorMapInterleave, CUtensorMapSwizzle,
                                    CUtensorMapL2promotion, CUtensorMapFloatOOBfill);

void make_map(PFN_encodeTiled fn, CUtensorMap* m, const void* ptr, int rank, const cuuint64_t* dims, const cuuint64_t* strides, const cuuint32_t* box, CUtensorMapSwizzle sw) {
    const cuuint32_t es[5] = {1, 1, 1, 1, 1};
    fn(m, CU_TENSOR_MAP_DATA_TYPE_BFLOAT16, rank, const_cast<void*>(ptr), dims, strides, box, es, CU_TENSOR_MAP_INTERLEAVE_NONE,
       sw, CU_TENSOR_MAP_L2_PROMOTION_L2_256B, CU_TENSOR_MAP_FLOAT_OOB_FILL_NONE);
}
void make_2d(PFN_encodeTiled fn, CUtensorMap* m, const void* ptr, uint64_t rows, uint64_t cols, uint32_t box_rows, uint32_t box_cols, CUtensorMapSwizzle sw) {
    const cuuint64_t gd[2] = {cols, rows}, gs[1] = {cols * 2};
    const cuuint32_t bd[2] = {box_cols, box_rows};
    make_map(fn, m, ptr, 2, gd, gs, bd, sw);
}

}

extern "C" void kernel_launch(void* const* d_in, const int* in_sizes, int n_in, void* d_out, int out_size) {
    (void)in_sizes; (void)n_in; (void)out_size;
    static PFN_encodeTiled fn = nullptr;
    static void* o_ptr = nullptr;
    static void* scr_ptr = nullptr;
    static void* tl_ptr = nullptr;
    if (!fn) {
        void* p = nullptr;
        cudaDriverEntryPointQueryResult st;
        cudaGetDriverEntryPoint("cuTensorMapEncodeTiled", &p, cudaEnableDefault, &st);
        fn = (PFN_encodeTiled)p;
        cudaGetSymbolAddress(&o_ptr, g_o);
        cudaGetSymbolAddress(&scr_ptr, g_scr);
        cudaFuncSetAttribute(fused_kernel, cudaFuncAttributeMaxDynamicSharedMemorySize, SM_TOTAL);
    }
    CUtensorMap tmX, tmW, tmPhi, tmWo, tmO, tmX2, tmOs;
    SideMaps tmS;
    make_2d(fn, &tmX, d_in[0], S_, D_, 256, 64, CU_TENSOR_MAP_SWIZZLE_128B);
    {
        const cuuint64_t gd[3] = {1024, 1024, 3}, gs[2] = {6144, 2048};
        const cuuint32_t bd[3] = {64, 64, 3};
        make_map(fn, &tmW, d_in[1], 3, gd, gs, bd, CU_TENSOR_MAP_SWIZZLE_128B);
    }
    make_2d(fn, &tmS.wc, d_in[1], D_, 3 * D_, 32, 64, CU_TENSOR_MAP_SWIZZLE_NONE);
    make_2d(fn, &tmPhi, d_in[2], 1024, 32, 64, 32, CU_TENSOR_MAP_SWIZZLE_64B);
    make_2d(fn, &tmS.wg, d_in[6], D_, F_, 32, 32, CU_TENSOR_MAP_SWIZZLE_NONE);
    make_2d(fn, &tmS.wu, d_in[7], D_, F_, 32, 32, CU_TENSOR_MAP_SWIZZLE_NONE);
    {
        const cuuint64_t gd[3] = {64, F_, 16}, gs[2] = {2048, 128};
        const cuuint32_t bd[3] = {64, 32, 8};
        make_map(fn, &tmS.wd8, d_in[8], 3, gd, gs, bd, CU_TENSOR_MAP_SWIZZLE_128B);
    }
    {
        const cuuint64_t gd[4] = {64, 64, 16, 16}, gs[3] = {2048, 64 * 2048, 128};
        const cuuint32_t bd[4] = {64, 32, 2, 2};
        make_map(fn, &tmWo, d_in[3], 4, gd, gs, bd, CU_TENSOR_MAP_SWIZZLE_128B);
    }
    make_2d(fn, &tmO, o_ptr, S_, D_, 128, 64, CU_TENSOR_MAP_SWIZZLE_128B);
    make_2d(fn, &tmOs, o_ptr, S_, D_, 256, 32, CU_TENSOR_MAP_SWIZZLE_NONE);
    make_2d(fn, &tmX2, d_in[0], S_, D_, 128, 64, CU_TENSOR_MAP_SWIZZLE_128B);
    Params P;
    P.x = (const __nv_bfloat16*)d_in[0];
    P.wr = (const __nv_bfloat16*)d_in[5];
    P.wqkv = (const __nv_bfloat16*)d_in[1];
    P.wg = (const __nv_bfloat16*)d_in[6];
    P.wu = (const __nv_bfloat16*)d_in[7];
    P.wd = (const __nv_bfloat16*)d_in[8];
    P.wo = (const __nv_bfloat16*)d_in[3];
    P.out = (__nv_bfloat16*)d_out;
    P.scr = (Scratch*)scr_ptr;
    P.tl = (unsigned long long*)tl_ptr;
    cudaLaunchConfig_t cfg = {};
    cfg.gridDim = dim3(NCTA); cfg.blockDim = dim3(NTHREADS); cfg.dynamicSmemBytes = SM_TOTAL; cfg.stream = cudaStreamPerThread;
    cudaLaunchAttribute at[1];
    at[0].id = cudaLaunchAttributeCooperative; at[0].val.cooperative = 1;
    cfg.attrs = at; cfg.numAttrs = 1;
    cudaLaunchKernelEx(&cfg, fused_kernel, P, tmX, tmW, tmX2, tmS, tmPhi, tmWo, tmO, tmOs);
}
```

```cpp
#include <cuda_runtime.h>
#include <cuda_bf16.h>
#include <cuda.h>
#include <stdint.h>

namespace {

constexpr int S_ = 2048, D_ = 1024, F_ = 3584;
constexpr int NCTA = 128, NTHREADS = 384;
#define OREL 2
#define OSTAG 12
#define OARR 3
#define NC0 3
#define NC2 4
#define NG0 12
#define NG1 12
#define GSPLIT 1
#define GSPLIT2 2
#define GST 3
#define SARR 3
#define PFENCE 1
#define JWO 12

constexpr int STAGE = 57344;
constexpr int SM_PHI = 0;
constexpr int SM_V = 131072;
constexpr int SM_AX = 172032;
constexpr int SM_BX = 176128;
constexpr int SM_SP = 172032;
constexpr int SM_FB = 180224;
constexpr int SM_OS = 196608;
constexpr int SM_XS = 221184;
constexpr int SM_KVOP = 172032;
constexpr int SM_MD = 223232;
constexpr int SM_RS = 224256;
constexpr int SM_Y = 225280;
constexpr int SM_GU = 225536;
constexpr int SM_MISC = 226688;
constexpr int SM_H = 179200;
constexpr int SM_BARS = 226816;
constexpr int SM_WPHI = 227840;
constexpr int SM_TOTAL = 232448;

constexpr int B_FULL = 0, B_EMPTY = 3, B_OF = 6, B_SD = 22, B_O = 33, B_PHI = 35, B_T = 37, B_WPHI = 38, B_Y = 39, B_KV = 40, B_LN = 42, B_S1 = 43, B_FF = 44, B_X = 54, B_C1 = 55, B_DN = 56, B_XS = 58, B_COUNT = 59, B_XR = 59, B_OS = 60, B_OW = 62;
constexpr int NB_KV = 1, NB_FFN = 2, NB_AUX = 3, NB_LEAD = 4, NB_STAG = 5;
__device__ __forceinline__ int o_slot(int i) { const int r = i % 5; return r == 4 ? 10 : r; }
__device__ __forceinline__ int wo_slot(int i) { const int r = i % 7; return r == 6 ? 11 : 4 + r; }

struct __align__(128) Acc {
    float4 cs[48 * 8 * 3];
    float4 y[4 * 4 * 3 * 32];
};
constexpr int ACC_VEC_PER_CTA = (int)(sizeof(Acc) / 16 / NCTA);
static_assert(sizeof(Acc) == ACC_VEC_PER_CTA * 16 * NCTA && ACC_VEC_PER_CTA <= 32, "");
struct __align__(128) Scratch {
    Acc acc[2];
    uint4 kv[32 * 4 * 3 * 32];
    unsigned cnt_o[8 * 128];
    uint2 rows[S_];
    uint4 best[NCTA];
    unsigned epoch;
};
__device__ Scratch g_scr;
__device__ __align__(1024) __nv_bfloat16 g_o[S_ * D_];

#define TL(e) do {} while (0)
#define TLP(c, e) do {} while (0)
#define TLG(c, e) do {} while (0)
#define TL_DUMP() do {} while (0)

struct SideMaps { CUtensorMap wc, wg, wu, wd8; };
struct Params {
    const __nv_bfloat16* x;
    const __nv_bfloat16* wr;
    const __nv_bfloat16* wqkv;
    const __nv_bfloat16* wg;
    const __nv_bfloat16* wu;
    const __nv_bfloat16* wd;
    const __nv_bfloat16* wo;
    __nv_bfloat16* out;
        Scratch* scr;
    unsigned long long* tl;
};

__device__ __forceinline__ bool elect_one() {
    uint32_t p; asm volatile("{\n.reg .pred q;\nelect.sync _|q, 0xffffffff;\nselp.u32 %0, 1, 0, q;\n}" : "=r"(p)); return p;
}
__device__ __forceinline__ uint32_t smem_u32(const void* p) { return (uint32_t)__cvta_generic_to_shared(p); }
__device__ __forceinline__ void mbar_init(uint32_t bar, uint32_t cnt) { asm volatile("mbarrier.init.shared::cta.b64 [%0], %1;" :: "r"(bar), "r"(cnt) : "memory"); }
__device__ __forceinline__ void mbar_expect_tx(uint32_t bar, uint32_t bytes) { asm volatile("mbarrier.arrive.expect_tx.shared::cta.b64 _, [%0], %1;" :: "r"(bar), "r"(bytes) : "memory"); }
__device__ __forceinline__ void mbar_arrive_if(bool p, uint32_t bar) {
    asm volatile("{\n.reg .pred q;\nsetp.ne.b32 q, %1, 0;\n@q mbarrier.arrive.shared::cta.b64 _, [%0];\n}" :: "r"(bar), "r"((int)p) : "memory");
}
__device__ __forceinline__ void mbar_wait(uint32_t bar, uint32_t parity) {
    asm volatile("{\n.reg .pred p;\n.reg .u32 n;\nmov.u32 n, 0;\n"
                 "WAIT_LOOP:\nmbarrier.try_wait.parity.shared::cta.b64 p, [%0], %1;\n@p bra WAIT_DONE;\n"
                 "add.u32 n, n, 1;\nsetp.lt.u32 p, n, 0x40000;\n@p bra WAIT_LOOP;\nWAIT_DONE:\n}" :: "r"(bar), "r"(parity) : "memory");
}
__device__ __forceinline__ void tma_2d(uint32_t dst, const CUtensorMap* tm, uint32_t bar, int c0, int c1) {
    asm volatile("cp.async.bulk.tensor.2d.shared::cluster.global.mbarrier::complete_tx::bytes [%0], [%1, {%3, %4}], [%2];"
        :: "r"(dst), "l"(tm), "r"(bar), "r"(c0), "r"(c1) : "memory");
}
__device__ __forceinline__ void tma_3d(uint32_t dst, const CUtensorMap* tm, uint32_t bar, int c0, int c1, int c2) {
    asm volatile("cp.async.bulk.tensor.3d.shared::cluster.global.mbarrier::complete_tx::bytes [%0], [%1, {%3, %4, %5}], [%2];"
        :: "r"(dst), "l"(tm), "r"(bar), "r"(c0), "r"(c1), "r"(c2) : "memory");
}
__device__ __forceinline__ void tma_4d(uint32_t dst, const CUtensorMap* tm, uint32_t bar, int c0, int c1, int c2, int c3) {
    asm volatile("cp.async.bulk.tensor.4d.shared::cluster.global.mbarrier::complete_tx::bytes [%0], [%1, {%3, %4, %5, %6}], [%2];"
        :: "r"(dst), "l"(tm), "r"(bar), "r"(c0), "r"(c1), "r"(c2), "r"(c3) : "memory");
}
__device__ __forceinline__ void prefetch_l2(const void* p, uint32_t bytes) { asm volatile("cp.async.bulk.prefetch.L2.global [%0], %1;" :: "l"(p), "r"(bytes) : "memory"); }
__device__ __forceinline__ void wgmma_fence() { asm volatile("wgmma.fence.sync.aligned;" ::: "memory"); }
__device__ __forceinline__ void wgmma_commit() { asm volatile("wgmma.commit_group.sync.aligned;" ::: "memory"); }
template <int N> __device__ __forceinline__ void wgmma_wait() { asm volatile("wgmma.wait_group.sync.aligned %0;" :: "n"(N) : "memory"); }
template <int N> __device__ __forceinline__ void fence_regs(float (&a)[N]) {
#pragma unroll
    for (int i = 0; i < N; i++) asm volatile("" : "+f"(a[i]) :: "memory");
}
template <int N> __device__ __forceinline__ void fence_regs(uint32_t (&a)[N]) {
#pragma unroll
    for (int i = 0; i < N; i++) asm volatile("" : "+r"(a[i]) :: "memory");
}
__device__ __forceinline__ uint64_t desc_from(uint32_t lo, uint32_t hi) { uint64_t d; asm("mov.b64 %0, {%1, %2};" : "=l"(d) : "r"(lo), "r"(hi)); return d; }
__device__ __forceinline__ uint32_t dlo(uint32_t addr, uint32_t lbo) { return ((addr & 0x3FFFF) >> 4) | ((lbo >> 4) << 16); }
__device__ __forceinline__ void nb_sync(int id, int cnt) { asm volatile("bar.sync %0, %1;" :: "r"(id), "r"(cnt) : "memory"); }
__device__ __forceinline__ void nb_arrive(int id, int cnt) { asm volatile("bar.arrive %0, %1;" :: "r"(id), "r"(cnt) : "memory"); }
__device__ __forceinline__ void fence_async_smem() { asm volatile("fence.proxy.async.shared::cta;" ::: "memory"); }
__device__ __forceinline__ void red_v4(float4* p, float a, float b, float c, float d) {
    asm volatile("red.relaxed.gpu.global.add.v4.f32 [%0], {%1, %2, %3, %4};" :: "l"(p), "f"(a), "f"(b), "f"(c), "f"(d) : "memory");
}
__device__ __forceinline__ float4 ld_gpu(const float4* p) {
    float4 v; asm volatile("ld.relaxed.gpu.global.v4.f32 {%0, %1, %2, %3}, [%4];" : "=f"(v.x), "=f"(v.y), "=f"(v.z), "=f"(v.w) : "l"(p) : "memory"); return v;
}
__device__ __forceinline__ uint4 ld_gpu(const uint4* p) {
    uint4 v; asm volatile("ld.relaxed.gpu.global.v4.u32 {%0, %1, %2, %3}, [%4];" : "=r"(v.x), "=r"(v.y), "=r"(v.z), "=r"(v.w) : "l"(p) : "memory"); return v;
}
__device__ __forceinline__ uint32_t pack_bf16(float lo, float hi) { uint32_t r; asm("cvt.rn.bf16x2.f32 %0, %1, %2;" : "=r"(r) : "f"(hi), "f"(lo)); return r; }
__device__ __forceinline__ uint32_t pack_f16(float lo, float hi) { uint32_t r; asm("cvt.rn.f16x2.f32 %0, %1, %2;" : "=r"(r) : "f"(hi), "f"(lo)); return r; }
__device__ __forceinline__ float2 unpack_f16(uint32_t v) { float2 r; asm("{\n.reg .f16 l, h;\nmov.b32 {l, h}, %2;\ncvt.f32.f16 %0, l;\ncvt.f32.f16 %1, h;\n}" : "=f"(r.x), "=f"(r.y) : "r"(v)); return r; }
__device__ __forceinline__ float bf_lo(uint32_t v) { return __uint_as_float(v << 16); }
__device__ __forceinline__ float bf_hi(uint32_t v) { return __uint_as_float(v & 0xFFFF0000u); }
__device__ __forceinline__ float round_bf16(float v) { return bf_lo(pack_bf16(v, 0.f)); }
__device__ __forceinline__ float ex2(float v) { float r; asm("ex2.approx.ftz.f32 %0, %1;" : "=f"(r) : "f"(v)); return r; }
__device__ __forceinline__ float rcp(float v) { float r; asm("rcp.approx.ftz.f32 %0, %1;" : "=f"(r) : "f"(v)); return r; }
__device__ __forceinline__ float sqrt_a(float v) { float r; asm("sqrt.approx.f32 %0, %1;" : "=f"(r) : "f"(v)); return r; }
__device__ __forceinline__ void stsm(uint32_t addr, uint32_t r0, uint32_t r1, uint32_t r2, uint32_t r3) {
    asm volatile("stmatrix.sync.aligned.m8n8.x4.shared.b16 [%0], {%1, %2, %3, %4};" :: "r"(addr), "r"(r0), "r"(r1), "r"(r2), "r"(r3) : "memory");
}
__device__ __forceinline__ void stsm_t(uint32_t addr, uint32_t r0, uint32_t r1, uint32_t r2, uint32_t r3) {
    asm volatile("stmatrix.sync.aligned.m8n8.x4.trans.shared.b16 [%0], {%1, %2, %3, %4};" :: "r"(addr), "r"(r0), "r"(r1), "r"(r2), "r"(r3) : "memory");
}
__device__ __forceinline__ uint4 lds128(uint32_t addr) {
    uint4 v; asm volatile("ld.shared.v4.u32 {%0, %1, %2, %3}, [%4];" : "=r"(v.x), "=r"(v.y), "=r"(v.z), "=r"(v.w) : "r"(addr) : "memory"); return v;
}
__device__ __forceinline__ void sts128(uint32_t addr, uint32_t a, uint32_t b, uint32_t c, uint32_t d) {
    asm volatile("st.shared.v4.u32 [%0], {%1, %2, %3, %4};" :: "r"(addr), "r"(a), "r"(b), "r"(c), "r"(d) : "memory");
}
__device__ __forceinline__ void sts64(uint32_t addr, uint32_t a, uint32_t b) { asm volatile("st.shared.v2.u32 [%0], {%1, %2};" :: "r"(addr), "r"(a), "r"(b) : "memory"); }
__device__ __forceinline__ uint32_t lds32(uint32_t addr) { uint32_t v; asm volatile("ld.shared.u32 %0, [%1];" : "=r"(v) : "r"(addr) : "memory"); return v; }
__device__ __forceinline__ float ldsf(uint32_t addr) { return __uint_as_float(lds32(addr)); }
__device__ __forceinline__ void sts32(uint32_t addr, uint32_t v) { asm volatile("st.shared.u32 [%0], %1;" :: "r"(addr), "r"(v) : "memory"); }
__device__ __forceinline__ uint32_t hmul2(uint32_t a, uint32_t b) { uint32_t r; asm("mul.rn.bf16x2 %0, %1, %2;" : "=r"(r) : "r"(a), "r"(b)); return r; }
__device__ __forceinline__ uint32_t hadd2(uint32_t a, uint32_t b) { uint32_t r; asm("add.rn.bf16x2 %0, %1, %2;" : "=r"(r) : "r"(a), "r"(b)); return r; }
__device__ __forceinline__ uint32_t hsub2(uint32_t a, uint32_t b) { uint32_t r; asm("sub.rn.bf16x2 %0, %1, %2;" : "=r"(r) : "r"(a), "r"(b)); return r; }

__device__ __forceinline__ void wgmma_ss_n192_tb(float (&d)[96], uint64_t da, uint64_t db, int scale_d) {
    asm volatile(
        "{\n.reg .pred p;\nsetp.ne.b32 p, %98, 0;\n"
        "wgmma.mma_async.sync.aligned.m64n192k16.f32.bf16.bf16 "
        "{%0, %1, %2, %3, %4, %5, %6, %7, %8, %9, %10, %11, %12, %13, %14, %15, %16, %17, %18, %19, %20, %21, %22, %23, %24, %25, %26, %27, %28, %29, %30, %31, %32, %33, %34, %35, %36, %37, %38, %39, %40, %41, %42, %43, %44, %45, %46, %47, %48, %49, %50, %51, %52, %53, %54, %55, %56, %57, %58, %59, %60, %61, %62, %63, %64, %65, %66, %67, %68, %69, %70, %71, %72, %73, %74, %75, %76, %77, %78, %79, %80, %81, %82, %83, %84, %85, %86, %87, %88, %89, %90, %91, %92, %93, %94, %95}, %96, %97, p, 1, 1, 0, 1;\n}\n"
        : "+f"(d[0]), "+f"(d[1]), "+f"(d[2]), "+f"(d[3]), "+f"(d[4]), "+f"(d[5]), "+f"(d[6]), "+f"(d[7]), "+f"(d[8]), "+f"(d[9]), "+f"(d[10]), "+f"(d[11]), "+f"(d[12]), "+f"(d[13]), "+f"(d[14]), "+f"(d[15]), "+f"(d[16]), "+f"(d[17]), "+f"(d[18]), "+f"(d[19]), "+f"(d[20]), "+f"(d[21]), "+f"(d[22]), "+f"(d[23]), "+f"(d[24]), "+f"(d[25]), "+f"(d[26]), "+f"(d[27]), "+f"(d[28]), "+f"(d[29]), "+f"(d[30]), "+f"(d[31]), "+f"(d[32]), "+f"(d[33]), "+f"(d[34]), "+f"(d[35]), "+f"(d[36]), "+f"(d[37]), "+f"(d[38]), "+f"(d[39]), "+f"(d[40]), "+f"(d[41]), "+f"(d[42]), "+f"(d[43]), "+f"(d[44]), "+f"(d[45]), "+f"(d[46]), "+f"(d[47]), "+f"(d[48]), "+f"(d[49]), "+f"(d[50]), "+f"(d[51]), "+f"(d[52]), "+f"(d[53]), "+f"(d[54]), "+f"(d[55]), "+f"(d[56]), "+f"(d[57]), "+f"(d[58]), "+f"(d[59]), "+f"(d[60]), "+f"(d[61]), "+f"(d[62]), "+f"(d[63]), "+f"(d[64]), "+f"(d[65]), "+f"(d[66]), "+f"(d[67]), "+f"(d[68]), "+f"(d[69]), "+f"(d[70]), "+f"(d[71]), "+f"(d[72]), "+f"(d[73]), "+f"(d[74]), "+f"(d[75]), "+f"(d[76]), "+f"(d[77]), "+f"(d[78]), "+f"(d[79]), "+f"(d[80]), "+f"(d[81]), "+f"(d[82]), "+f"(d[83]), "+f"(d[84]), "+f"(d[85]), "+f"(d[86]), "+f"(d[87]), "+f"(d[88]), "+f"(d[89]), "+f"(d[90]), "+f"(d[91]), "+f"(d[92]), "+f"(d[93]), "+f"(d[94]), "+f"(d[95])
        : "l"(da), "l"(db), "r"(scale_d));
}
__device__ __forceinline__ void wgmma_ss_n128_tb(float (&d)[64], uint64_t da, uint64_t db, int scale_d) {
    asm volatile(
        "{\n.reg .pred p;\nsetp.ne.b32 p, %66, 0;\n"
        "wgmma.mma_async.sync.aligned.m64n128k16.f32.bf16.bf16 "
        "{%0, %1, %2, %3, %4, %5, %6, %7, %8, %9, %10, %11, %12, %13, %14, %15, %16, %17, %18, %19, %20, %21, %22, %23, %24, %25, %26, %27, %28, %29, %30, %31, %32, %33, %34, %35, %36, %37, %38, %39, %40, %41, %42, %43, %44, %45, %46, %47, %48, %49, %50, %51, %52, %53, %54, %55, %56, %57, %58, %59, %60, %61, %62, %63}, %64, %65, p, 1, 1, 0, 1;\n}\n"
        : "+f"(d[0]), "+f"(d[1]), "+f"(d[2]), "+f"(d[3]), "+f"(d[4]), "+f"(d[5]), "+f"(d[6]), "+f"(d[7]), "+f"(d[8]), "+f"(d[9]), "+f"(d[10]), "+f"(d[11]), "+f"(d[12]), "+f"(d[13]), "+f"(d[14]), "+f"(d[15]), "+f"(d[16]), "+f"(d[17]), "+f"(d[18]), "+f"(d[19]), "+f"(d[20]), "+f"(d[21]), "+f"(d[22]), "+f"(d[23]), "+f"(d[24]), "+f"(d[25]), "+f"(d[26]), "+f"(d[27]), "+f"(d[28]), "+f"(d[29]), "+f"(d[30]), "+f"(d[31]), "+f"(d[32]), "+f"(d[33]), "+f"(d[34]), "+f"(d[35]), "+f"(d[36]), "+f"(d[37]), "+f"(d[38]), "+f"(d[39]), "+f"(d[40]), "+f"(d[41]), "+f"(d[42]), "+f"(d[43]), "+f"(d[44]), "+f"(d[45]), "+f"(d[46]), "+f"(d[47]), "+f"(d[48]), "+f"(d[49]), "+f"(d[50]), "+f"(d[51]), "+f"(d[52]), "+f"(d[53]), "+f"(d[54]), "+f"(d[55]), "+f"(d[56]), "+f"(d[57]), "+f"(d[58]), "+f"(d[59]), "+f"(d[60]), "+f"(d[61]), "+f"(d[62]), "+f"(d[63])
        : "l"(da), "l"(db), "r"(scale_d));
}
__device__ __forceinline__ void wgmma_ss_n40(float (&d)[20], uint64_t da, uint64_t db, int scale_d) {
    asm volatile(
        "{\n.reg .pred p;\nsetp.ne.b32 p, %22, 0;\n"
        "wgmma.mma_async.sync.aligned.m64n40k16.f32.bf16.bf16 "
        "{%0, %1, %2, %3, %4, %5, %6, %7, %8, %9, %10, %11, %12, %13, %14, %15, %16, %17, %18, %19}, %20, %21, p, 1, 1, 0, 0;\n}\n"
        : "+f"(d[0]), "+f"(d[1]), "+f"(d[2]), "+f"(d[3]), "+f"(d[4]), "+f"(d[5]), "+f"(d[6]), "+f"(d[7]), "+f"(d[8]), "+f"(d[9]), "+f"(d[10]), "+f"(d[11]), "+f"(d[12]), "+f"(d[13]), "+f"(d[14]), "+f"(d[15]), "+f"(d[16]), "+f"(d[17]), "+f"(d[18]), "+f"(d[19])
        : "l"(da), "l"(db), "r"(scale_d));
}
__device__ __forceinline__ void wgmma_ss_n8_ta(float (&d)[4], uint64_t da, uint64_t db, int scale_d) {
    asm volatile(
        "{\n.reg .pred p;\nsetp.ne.b32 p, %6, 0;\n"
        "wgmma.mma_async.sync.aligned.m64n8k16.f32.bf16.bf16 "
        "{%0, %1, %2, %3}, %4, %5, p, 1, 1, 1, 0;\n}\n"
        : "+f"(d[0]), "+f"(d[1]), "+f"(d[2]), "+f"(d[3])
        : "l"(da), "l"(db), "r"(scale_d));
}
__device__ __forceinline__ void wgmma_rs_n32_tb(float (&d)[16], uint32_t a0, uint32_t a1, uint32_t a2, uint32_t a3, uint64_t db, int scale_d) {
    asm volatile(
        "{\n.reg .pred p;\nsetp.ne.b32 p, %21, 0;\n"
        "wgmma.mma_async.sync.aligned.m64n32k16.f32.bf16.bf16 "
        "{%0, %1, %2, %3, %4, %5, %6, %7, %8, %9, %10, %11, %12, %13, %14, %15}, {%16, %17, %18, %19}, %20, p, 1, 1, 1;\n}\n"
        : "+f"(d[0]), "+f"(d[1]), "+f"(d[2]), "+f"(d[3]), "+f"(d[4]), "+f"(d[5]), "+f"(d[6]), "+f"(d[7]), "+f"(d[8]), "+f"(d[9]), "+f"(d[10]), "+f"(d[11]), "+f"(d[12]), "+f"(d[13]), "+f"(d[14]), "+f"(d[15])
        : "r"(a0), "r"(a1), "r"(a2), "r"(a3), "l"(db), "r"(scale_d));
}
__device__ __forceinline__ void wgmma_rs_n40_tb(float (&d)[20], uint32_t a0, uint32_t a1, uint32_t a2, uint32_t a3, uint64_t db, int scale_d) {
    asm volatile(
        "{\n.reg .pred p;\nsetp.ne.b32 p, %25, 0;\n"
        "wgmma.mma_async.sync.aligned.m64n40k16.f32.bf16.bf16 "
        "{%0, %1, %2, %3, %4, %5, %6, %7, %8, %9, %10, %11, %12, %13, %14, %15, %16, %17, %18, %19}, {%20, %21, %22, %23}, %24, p, 1, 1, 1;\n}\n"
        : "+f"(d[0]), "+f"(d[1]), "+f"(d[2]), "+f"(d[3]), "+f"(d[4]), "+f"(d[5]), "+f"(d[6]), "+f"(d[7]), "+f"(d[8]), "+f"(d[9]), "+f"(d[10]), "+f"(d[11]), "+f"(d[12]), "+f"(d[13]), "+f"(d[14]), "+f"(d[15]), "+f"(d[16]), "+f"(d[17]), "+f"(d[18]), "+f"(d[19])
        : "r"(a0), "r"(a1), "r"(a2), "r"(a3), "l"(db), "r"(scale_d));
}

constexpr float LOG2E = 1.4426950408889634f;
constexpr uint32_t DH128 = (1024u >> 4) | (1u << 30);

__device__ __forceinline__ float silu_f(float v) { return v * rcp(1.0f + ex2(-v * LOG2E)); }
__device__ __forceinline__ float silu_t(float v) { const float h = 0.5f * v; float th; asm("tanh.approx.f32 %0, %1;" : "=f"(th) : "f"(h)); return fmaf(h, th, h); }
__device__ __forceinline__ uint32_t ln_pair(uint32_t xv, uint32_t m2, float rs) { const uint32_t a = hsub2(xv, m2); return pack_bf16(bf_lo(a) * rs, bf_hi(a) * rs); }
__device__ __forceinline__ uint32_t silu_pair(uint32_t v) { return pack_bf16(silu_t(bf_lo(v)), silu_t(bf_hi(v))); }
__device__ __forceinline__ uint32_t gate_pair(uint32_t v, float hr, float hm) {
    const float a = fmaf(bf_lo(v), hr, hm), b = fmaf(bf_hi(v), hr, hm);
    float ta, tb;
    asm("tanh.approx.f32 %0, %1;" : "=f"(ta) : "f"(a)); asm("tanh.approx.f32 %0, %1;" : "=f"(tb) : "f"(b));
    return pack_bf16(fmaf(a, ta, a), fmaf(b, tb, b));
}
__device__ __forceinline__ void gate_item(uint4& v, uint32_t sb, int row) {
    const float hr = 0.5f * ldsf(sb + SM_RS + row * 4), hm = -bf_lo(lds32(sb + SM_MD + row * 4)) * hr;
    v.x = gate_pair(v.x, hr, hm); v.y = gate_pair(v.y, hr, hm); v.z = gate_pair(v.z, hr, hm); v.w = gate_pair(v.w, hr, hm);
    asm volatile("" : "+r"(v.x), "+r"(v.y), "+r"(v.z), "+r"(v.w) :: "memory");
}
__device__ __forceinline__ uint32_t hfma2(uint32_t a, uint32_t b, uint32_t c) { uint32_t r; asm("fma.rn.bf16x2 %0, %1, %2, %3;" : "=r"(r) : "r"(a), "r"(b), "r"(c)); return r; }
__device__ __forceinline__ uint32_t dup_lo(uint32_t v) { uint32_t r; asm("{\n.reg .b16 l, h;\nmov.b32 {l, h}, %1;\nmov.b32 %0, {l, l};\n}" : "=r"(r) : "r"(v)); return r; }
__device__ __forceinline__ uint32_t dup_hi(uint32_t v) { uint32_t r; asm("{\n.reg .b16 l, h;\nmov.b32 {l, h}, %1;\nmov.b32 %0, {h, h};\n}" : "=r"(r) : "r"(v)); return r; }
template <bool SQ> __device__ __forceinline__ void colsum8(float (&a)[8], float& sq, const uint4 (&v)[8]) {
    uint32_t q = 0;
#pragma unroll
    for (int i = 0; i < 8; i++) {
        a[0] += bf_lo(v[i].x); a[1] += bf_hi(v[i].x); a[2] += bf_lo(v[i].y); a[3] += bf_hi(v[i].y);
        a[4] += bf_lo(v[i].z); a[5] += bf_hi(v[i].z); a[6] += bf_lo(v[i].w); a[7] += bf_hi(v[i].w);
        if (SQ) q = hfma2(v[i].x, v[i].x, hfma2(v[i].y, v[i].y, hfma2(v[i].z, v[i].z, hfma2(v[i].w, v[i].w, q))));
    }
    if (SQ) sq += bf_lo(q) + bf_hi(q);
}
__device__ __forceinline__ void hfma8(uint4& h, uint32_t w, const uint4& v) { h.x = hfma2(v.x, w, h.x); h.y = hfma2(v.y, w, h.y); h.z = hfma2(v.z, w, h.z); h.w = hfma2(v.w, w, h.w); }
template <int ST, class F>
__device__ __forceinline__ void gemv_run(float (&a)[8], int cnt, int b, uint32_t ph, uint32_t lo, uint32_t wa, uint32_t ws, uint32_t bar0, uint32_t pin, F done) {
    uint32_t rdy = 0;
#pragma unroll 1
    for (int m = 0; m < cnt; m++) {
        if (!rdy) mbar_wait(bar0 + b * 8, ph);
        uint4 A[8];
        const uint4 w = lds128(wa);
#pragma unroll
        for (int i = 0; i < 8; i++) A[i] = lds128(lo + b * 4096 + i * ST);
        const int bc = b;
        if (++b == 3) { b = 0; ph ^= 1; }
        asm volatile("{\n.reg .pred p;\nmbarrier.test_wait.parity.shared::cta.b64 p, [%1], %2;\nselp.u32 %0, 1, 0, p;\n}" : "=r"(rdy) : "r"(bar0 + b * 8), "r"(ph) : "memory");
        sts32(pin, 0u);
        wa += ws;
        uint4 h = make_uint4(0, 0, 0, 0);
        hfma8(h, dup_lo(w.x), A[0]); hfma8(h, dup_hi(w.x), A[1]); hfma8(h, dup_lo(w.y), A[2]); hfma8(h, dup_hi(w.y), A[3]);
        hfma8(h, dup_lo(w.z), A[4]); hfma8(h, dup_hi(w.z), A[5]); hfma8(h, dup_lo(w.w), A[6]); hfma8(h, dup_hi(w.w), A[7]);
        a[0] += bf_lo(h.x); a[1] += bf_hi(h.x); a[2] += bf_lo(h.y); a[3] += bf_hi(h.y);
        a[4] += bf_lo(h.z); a[5] += bf_hi(h.z); a[6] += bf_lo(h.w); a[7] += bf_hi(h.w);
        fence_regs(a);
        done(m, bc);
    }
}
template <int OFF> __device__ __forceinline__ void pack_head(const float (&acc)[96], uint32_t (&f)[8]) {
#pragma unroll
    for (int i = 0; i < 8; i++) f[i] = pack_bf16(acc[OFF + 2 * i], acc[OFF + 2 * i + 1]);
}
__device__ __forceinline__ void feat_mma(float (&p)[16], const uint32_t (&f)[8], uint32_t wlo) {
    constexpr uint32_t DH = (512u >> 4) | (2u << 30);
    wgmma_rs_n32_tb(p, f[0], f[1], f[2], f[3], desc_from(wlo, DH), 0);
    wgmma_rs_n32_tb(p, f[4], f[5], f[6], f[7], desc_from(wlo + 64, DH), 1);
}
template <int S> __device__ __forceinline__ void row_ext(const float (&p)[16], float& a, float& b) {
    auto op = [](float x, float y) { return S > 0 ? fmaxf(x, y) : fminf(x, y); };
    a = op(op(op(p[0], p[1]), op(p[4], p[5])), op(op(p[8], p[9]), op(p[12], p[13])));
    b = op(op(op(p[2], p[3]), op(p[6], p[7])), op(op(p[10], p[11]), op(p[14], p[15])));
#pragma unroll
    for (int o = 1; o <= 2; o <<= 1) { a = op(a, __shfl_xor_sync(0xffffffffu, a, o)); b = op(b, __shfl_xor_sync(0xffffffffu, b, o)); }
}
__device__ __forceinline__ void dual_exp(const float (&p)[16], float scA, float scB, uint32_t (&pos)[8], uint32_t (&neg)[8], uint32_t& chk) {
#pragma unroll
    for (int j = 0; j < 8; j += 2) {
        const float a0 = ex2(p[2 * j] * scA), a1 = ex2(p[2 * j + 1] * scA);
        const float b0 = ex2(p[2 * j + 2] * scB), b1 = ex2(p[2 * j + 3] * scB);
        const float pa = a0 * a1, pb = b0 * b1, R = rcp(pa * pb);
        const uint32_t r = pack_bf16(R * pb, R * pa);
        pos[j] = pack_bf16(a0, a1); pos[j + 1] = pack_bf16(b0, b1);
        neg[j] = hmul2(pos[j], dup_lo(r)); neg[j + 1] = hmul2(pos[j + 1], dup_hi(r));
        chk = hadd2(chk, hadd2(hadd2(pos[j], neg[j]), hadd2(pos[j + 1], neg[j + 1])));
    }
}
template <int S> __device__ __forceinline__ void exact_exp(const float (&p)[16], float scA, float scB, uint32_t (&o)[8]) {
    float mA, mB;
    row_ext<S>(p, mA, mB);
#pragma unroll
    for (int j = 0; j < 8; j++) {
        const float sc = S * ((j & 1) ? scB : scA), m = (j & 1) ? mB : mA;
        const float u = ex2((p[2 * j] - m) * sc), v = ex2((p[2 * j + 1] - m) * sc);
        o[j] = S > 0 ? pack_bf16(u, v) : pack_bf16(v, u);
    }
}
__device__ __forceinline__ void features(const float (&p0)[16], const float (&p1)[16], const float (&rs)[4],
                                         uint32_t (&pa)[8], uint32_t (&na)[8], uint32_t (&pb)[8], uint32_t (&nb)[8]) {
    uint32_t chk = 0;
    dual_exp(p0, rs[0] * LOG2E, rs[1] * LOG2E, pa, na, chk);
    dual_exp(p1, rs[2] * LOG2E, rs[3] * LOG2E, pb, nb, chk);
    if (__builtin_expect(!__all_sync(0xffffffffu, bf_lo(chk) + bf_hi(chk) < 1.0e9f), 0)) {
        exact_exp<1>(p0, rs[0] * LOG2E, rs[1] * LOG2E, pa); exact_exp<-1>(p0, rs[0] * LOG2E, rs[1] * LOG2E, na);
        exact_exp<1>(p1, rs[2] * LOG2E, rs[3] * LOG2E, pb); exact_exp<-1>(p1, rs[2] * LOG2E, rs[3] * LOG2E, nb);
    }
}
__device__ __forceinline__ float quad_sum(float v) { v += __shfl_xor_sync(0xffffffffu, v, 1); return v + __shfl_xor_sync(0xffffffffu, v, 2); }
__device__ __forceinline__ float key_block(const float (&p)[16], float rsA, float rsB, uint32_t d0, uint32_t d1, uint32_t off) {
    float r[8], sp[2], sn[2];
    uint32_t pos[8], neg[8];
    const float scA = rsA * LOG2E, scB = rsB * LOG2E;
#pragma unroll
    for (int j = 0; j < 8; j += 2) {
        const float a0 = ex2(p[2 * j] * scA), a1 = ex2(p[2 * j + 1] * scA);
        const float b0 = ex2(p[2 * j + 2] * scB), b1 = ex2(p[2 * j + 3] * scB);
        const float pa = a0 * a1, pb = b0 * b1, R = rcp(pa * pb), ta = a0 + a1, tb = b0 + b1;
        r[j] = R * pb; r[j + 1] = R * pa;
        if (j == 0) { sp[0] = ta; sp[1] = tb; sn[0] = r[0] * ta; sn[1] = r[1] * tb; }
        else { sp[0] += ta; sp[1] += tb; sn[0] = fmaf(r[j], ta, sn[0]); sn[1] = fmaf(r[j + 1], tb, sn[1]); }
        pos[j] = pack_bf16(a0, a1); pos[j + 1] = pack_bf16(b0, b1);
    }
    const float qa = quad_sum(sp[0]), qb = quad_sum(sp[1]), na = quad_sum(sn[0]), nb = quad_sum(sn[1]);
    const float iq = rcp(qa * qb), nA = rsA * rcp(na), nB = rsB * rcp(nb);
    const uint32_t fp = pack_bf16(rsA * qb * iq, rsB * qa * iq);
#pragma unroll
    for (int j = 0; j < 8; j += 2) {
        const uint32_t rn = pack_bf16(r[j] * nA, r[j + 1] * nB);
        neg[j] = hmul2(pos[j], dup_lo(rn)); neg[j + 1] = hmul2(pos[j + 1], dup_hi(rn));
        pos[j] = hmul2(pos[j], dup_lo(fp)); pos[j + 1] = hmul2(pos[j + 1], dup_hi(fp));
    }
    stsm_t(d0 + 4096, neg[0], neg[2], neg[4], neg[6]); stsm_t(d1 + 4096, neg[1], neg[3], neg[5], neg[7]);
    stsm_t(d0 + off, pos[0], pos[2], pos[4], pos[6]); stsm_t(d1 + off, pos[1], pos[3], pos[5], pos[7]);
    return (qa + qb) + (na + nb);
}
__device__ __forceinline__ void shift_max(float (&p)[16]) {
    float mA, mB;
    row_ext<1>(p, mA, mB);
#pragma unroll
    for (int j = 0; j < 16; j++) p[j] -= (j & 2) ? mB : mA;
}
__device__ __forceinline__ void key_head(float (&p0)[16], float (&p1)[16], const float (&rs)[4], uint32_t d0, uint32_t d1) {
    uint32_t st;
    asm volatile("mov.u32 %0, 0;" : "=r"(st));
    bool again;
#pragma unroll 1
    do {
        const uint32_t off = (st & 2u) << 11;
        const float chk = key_block(p0, rs[0], rs[1], d0, d1, off) + key_block(p1, rs[2], rs[3], d0 + 8192, d1 + 8192, off);
        again = st == 1u || (st == 0u && !__all_sync(0xffffffffu, chk < 1.0e9f));
        if (__builtin_expect(again, 0)) {
            if (st) {
#pragma unroll
                for (int j = 0; j < 16; j += 2) {
                    float t = p0[j]; p0[j] = -p0[j + 1]; p0[j + 1] = -t;
                    t = p1[j]; p1[j] = -p1[j + 1]; p1[j + 1] = -t;
                }
            }
            shift_max(p0); shift_max(p1);
            st++;
        }
        asm volatile("" ::: "memory");
    } while (again);
}
__device__ __forceinline__ void o_mma(float (&d)[20], float (&e)[20], const uint32_t (&pos)[8], const uint32_t (&neg)[8], uint32_t klo) {
    wgmma_rs_n40_tb(d, pos[0], pos[1], pos[2], pos[3], desc_from(klo, 1024u >> 4), 0);
    wgmma_rs_n40_tb(e, neg[0], neg[1], neg[2], neg[3], desc_from(klo + 32, 1024u >> 4), 0);
    wgmma_rs_n40_tb(d, pos[4], pos[5], pos[6], pos[7], desc_from(klo + 16, 1024u >> 4), 1);
    wgmma_rs_n40_tb(e, neg[4], neg[5], neg[6], neg[7], desc_from(klo + 48, 1024u >> 4), 1);
}
__device__ __forceinline__ void o_store(const float (&d)[20], const float (&e)[20], uint32_t dst) {
    const float iA = rcp(fmaf(d[16], e[17], fmaf(e[16], d[17], 1e-6f * d[17] * e[17])));
    const float iB = rcp(fmaf(d[18], e[19], fmaf(e[18], d[19], 1e-6f * d[19] * e[19])));
    const float pA = e[17] * iA, nA = d[17] * iA, pB = e[19] * iB, nB = d[19] * iB;
    uint32_t oa[4], ob[4];
#pragma unroll
    for (int j = 0; j < 4; j++) {
        oa[j] = pack_bf16(fmaf(d[j * 4], pA, e[j * 4] * nA), fmaf(d[j * 4 + 1], pA, e[j * 4 + 1] * nA));
        ob[j] = pack_bf16(fmaf(d[j * 4 + 2], pB, e[j * 4 + 2] * nB), fmaf(d[j * 4 + 3], pB, e[j * 4 + 3] * nB));
    }
    sts128(dst, oa[0], oa[1], oa[2], oa[3]);
    sts128(dst + 512, ob[0], ob[1], ob[2], ob[3]);
}

template <int N> __device__ __forceinline__ void kv_gather(uint4 (&v)[3 * N], const uint4* src, uint32_t dst, int lane, float us) {
    unsigned it = 0;
#pragma unroll 1
    while (++it < (1u << 20)) {
        bool ok = true;
#pragma unroll
        for (int j = 0; j < 3 * N; j++) ok = ok && (v[j].w >> 16) == 0x4800u;
        if (__all_sync(0xffffffffu, ok)) break;
#pragma unroll
        for (int j = 0; j < 3 * N; j++) v[j] = ld_gpu(src + j * 32);
    }
    dst += (lane >> 2) * 16;
    auto cv = [&](uint32_t w) { const float2 f = unpack_f16(w); return pack_bf16(f.x * us, f.y * us); };
#pragma unroll
    for (int n = 0; n < N; n++) {
        sts128(dst + (lane & 3) * 1024 + n * 256, cv(v[3 * n].x), cv(v[3 * n].y), cv(v[3 * n].z), cv(v[3 * n + 2].x));
        sts128(dst + (lane & 3) * 1024 + n * 256 + 128, cv(v[3 * n + 1].x), cv(v[3 * n + 1].y), cv(v[3 * n + 1].z), cv(v[3 * n + 2].y));
        sts32(dst + 4096 + n * 256 + (lane & 3) * 4, pack_bf16(unpack_f16(v[3 * n].w).x, 1.0f));
        sts32(dst + 4096 + n * 256 + 128 + (lane & 3) * 4, pack_bf16(unpack_f16(v[3 * n + 1].w).x, 1.0f));
    }
    fence_async_smem();
    __syncwarp();
}

__global__ void __launch_bounds__(NTHREADS, 1)
fused_kernel(const Params P, const __grid_constant__ CUtensorMap tmX, const __grid_constant__ CUtensorMap tmW, const __grid_constant__ CUtensorMap tmX2,
             const __grid_constant__ SideMaps tmS, const __grid_constant__ CUtensorMap tmPhi,
             const __grid_constant__ CUtensorMap tmWo, const __grid_constant__ CUtensorMap tmO, const __grid_constant__ CUtensorMap tmOs) {
    extern __shared__ __align__(1024) uint8_t smem_raw[];
    constexpr uint32_t sb = 1024;
    if (smem_u32(smem_raw) != sb) return;
    constexpr uint32_t bars = sb + SM_BARS;
    const int rb = blockIdx.x >> 4, hp = blockIdx.x & 15;
    TLP(threadIdx.x == 32, 0); TLG(threadIdx.x == 32, 48);
    auto load_stage = [&](int s, int ks) {
        mbar_expect_tx(bars + 8 * (B_FULL + s), STAGE);
        tma_2d(sb + s * STAGE, &tmX, bars + 8 * (B_FULL + s), ks * 64, rb * 256);
        tma_3d(sb + s * STAGE + 32768, &tmW, bars + 8 * (B_FULL + s), hp * 64, ks * 64, 0);
    };
    if (threadIdx.x < 256) {
        const uint32_t t = threadIdx.x, r = t >> 3, sw = ((t ^ r) & 7) * 16;
        const __nv_bfloat16* wp = P.wqkv + (size_t)r * 3 * D_ + hp * 64 + (t & 7) * 8;
        const __nv_bfloat16* xp = P.x + (size_t)(rb * 256 + (t >> 7) * 128 + (r & 15)) * D_ + (t & 7) * 8;
#pragma unroll
        for (int i = 0; i < 3; i++) asm volatile("cp.async.cg.shared.global [%0], [%1], 16;" :: "r"(sb + 32768 + i * 8192 + r * 128 + sw), "l"(wp + i * D_) : "memory");
#pragma unroll
        for (int i = 0; i < 8; i++) asm volatile("cp.async.cg.shared.global [%0], [%1], 16;" :: "r"(sb + (t >> 7) * 16384 + ((r & 15) + i * 16) * 128 + sw), "l"(xp + i * 16 * D_) : "memory");
        asm volatile("cp.async.commit_group;" ::: "memory");
#pragma unroll
        for (int i = 0; i < 3; i++) asm volatile("cp.async.cg.shared.global [%0], [%1], 16;" :: "r"(sb + 36864 + i * 8192 + r * 128 + sw), "l"(wp + 96 * D_ + i * D_) : "memory");
        asm volatile("cp.async.commit_group;" ::: "memory");
    }
    const int tid = threadIdx.x, warp = __shfl_sync(0xffffffffu, tid >> 5, 0), lane = tid & 31;
    const bool elect = lane == 0;

    if (warp >= 8) {
        const int aw = warp - 9;
        auto load_o = [&](int i) {
            mbar_expect_tx(bars + 8 * (B_OF + i), 16384);
            tma_2d(sb + o_slot(i) * 16384, &tmO, bars + 8 * (B_OF + i), i * 64, rb * 256 + (hp & 1) * 128);
        };
        auto load_wo = [&](int i) {
            mbar_expect_tx(bars + 8 * (B_OF + i), 16384);
            tma_4d(sb + wo_slot(i) * 16384, &tmWo, bars + 8 * (B_OF + i), 0, (i >> 3) * 32, (i & 7) * 2, hp & 14);
        };
        if (warp == 9) {
            if (elect_one()) {
#pragma unroll
                for (int i = B_OF; i < B_COUNT; i++)
                    mbar_init(bars + 8 * i, i < B_SD ? 2 : (i < B_WPHI ? 8 : ((i < B_KV || i >= B_FF || i == B_LN) ? 1 : 4)));
                mbar_init(bars + 8 * B_OS, 1); mbar_init(bars + 8 * B_OS + 8, 1);
#pragma unroll
                for (int i = 0; i < 4; i++) mbar_init(bars + 8 * (B_OW + i), 4);
                asm volatile("fence.mbarrier_init.release.cluster;" ::: "memory");
            }
        }
        if (warp == 8) {
            if (elect_one()) {
#pragma unroll
                for (int i = 0; i < 3; i++) { mbar_init(bars + 8 * (B_FULL + i), 1); mbar_init(bars + 8 * (B_EMPTY + i), 8); }
                mbar_init(bars + 8 * B_XR, 1);
                asm volatile("fence.mbarrier_init.release.cluster;" ::: "memory");
                asm volatile("mbarrier.arrive.shared::cta.b64 _, [%0];" :: "r"(bars + 8 * B_FULL) : "memory");
            }
            __syncwarp();
            nb_arrive(0, NTHREADS);
        } else {
            __syncwarp();
            nb_sync(0, NTHREADS);
        }
        asm volatile("setmaxnreg.dec.sync.aligned.u32 56;");
        if (warp == 8 && elect_one()) {
            load_stage(1, 1); load_stage(2, 2);
            mbar_expect_tx(bars + 8 * B_XR, 32768);
            asm volatile("cp.async.bulk.shared::cluster.global.mbarrier::complete_tx::bytes [%0], [%1], 32768, [%2];"
                         :: "r"(sb + SM_FB + 4096), "l"(P.x + (size_t)blockIdx.x * 16 * D_), "r"(bars + 8 * B_XR) : "memory");
        }
        __syncwarp();
        nb_sync(NB_KV, 128);
        unsigned epoch;
        asm volatile("ld.relaxed.gpu.global.u32 %0, [%1];" : "=r"(epoch) : "l"(&P.scr->epoch) : "memory");
        auto get_acc = [&]() { return &P.scr->acc[epoch & 1u]; };
        if (warp == 8) {
            epoch = __shfl_sync(0xffffffffu, epoch, 0);
            int s = 0, ph = 0;
#pragma unroll 1
            for (int j = 0; j < 15; j++) {
                mbar_wait(bars + 8 * (B_EMPTY + s), ph);
                if (elect_one()) {
                    if (j < 13) load_stage(s, j + 3);
                    if (j < 2) {
                        prefetch_l2(P.wqkv + (size_t)(256 + j * 384 + blockIdx.x * 3) * 3 * D_, 18432);
                    } else if (j < 10) {
                        if (j == 2) asm volatile("mbarrier.arrive.shared::cta.b64 _, [%0];" :: "r"(bars + 8 * B_FF) : "memory");
                        const size_t o = (size_t)((j - 2) * 128 + blockIdx.x) * F_;
                        prefetch_l2(P.wg + o, F_ * 2); prefetch_l2(P.wu + o, F_ * 2);
                    }
                    if (j == JWO) prefetch_l2(P.wo + (size_t)blockIdx.x * 8 * D_, 16384);
                    if (j == 12) {
                        asm volatile("prefetch.tensormap [%0];" :: "l"(&tmO) : "memory");
                        asm volatile("prefetch.tensormap [%0];" :: "l"(&tmOs) : "memory");
                        asm volatile("prefetch.tensormap [%0];" :: "l"(&tmS.wd8) : "memory");
                        asm volatile("prefetch.tensormap [%0];" :: "l"(&tmWo) : "memory");
                        mbar_expect_tx(bars + 8 * B_WPHI, 4096);
                        tma_2d(sb + SM_WPHI, &tmPhi, bars + 8 * B_WPHI, 0, hp * 64);
                    }
                    if (j >= 13) {
                        if (blockIdx.x >= 112 || j == 13) { load_wo(2 * j - 26); load_wo(2 * j - 25); }
                        else {
                            mbar_expect_tx(bars + 8 * (B_DN + 1), 32768);
                            tma_3d(sb + 6 * 16384, &tmS.wd8, bars + 8 * (B_DN + 1), 0, blockIdx.x * 32, 8);
                        }
                    }
                }
                __syncwarp();
                if (++s == 3) { s = 0; ph ^= 1; }
                if (j == 3 && lane < ACC_VEC_PER_CTA) reinterpret_cast<uint4*>(&P.scr->acc[~epoch & 1u])[blockIdx.x * ACC_VEC_PER_CTA + lane] = make_uint4(0, 0, 0, 0);
            }
            TLP(elect, 20);
        } else {
            const bool ffn = blockIdx.x < 112;
            const uint32_t fbuf = sb + SM_FB + 4096 + aw * 12288, fbar = bars + 8 * (B_FF + 1 + aw * 3);
        const int nc = aw == 0 ? NC0 : (aw == 1 ? 12 - NC0 - NC2 : NC2), c0 = aw == 0 ? 0 : (aw == 1 ? NC0 : 12 - NC2);
        const int ng = !ffn ? 0 : (aw == 0 ? NG0 : (aw == 1 ? NG1 : 32 - NG0 - NG1)), g0 = aw == 0 ? 0 : (aw == 1 ? NG0 : NG0 + NG1);
        auto issue = [&](int i, int b) {
            __syncwarp();
            if (i < nc + ng && elect_one()) {
                mbar_expect_tx(fbar + b * 8, 4096);
                if (i < nc) {
                    tma_2d(fbuf + b * 4096, &tmS.wc, fbar + b * 8, ((c0 + i) >> 2) * 1024 + hp * 64, rb * 128 + ((c0 + i) & 3) * 32);
                } else {
                    tma_2d(fbuf + b * 4096, &tmS.wg, fbar + b * 8, blockIdx.x * 32, (g0 + i - nc) * 32);
                    tma_2d(fbuf + b * 4096 + 2048, &tmS.wu, fbar + b * 8, blockIdx.x * 32, (g0 + i - nc) * 32);
                }
            }
            __syncwarp();
        };
            {
                uint4 wv[4];
#pragma unroll
                for (int i = 0; i < 4; i++) wv[i] = __ldg(reinterpret_cast<const uint4*>(P.wr) + i * 32 + lane);
                const uint32_t* ww = reinterpret_cast<const uint32_t*>(wv);
                float sw = 0.f;
#pragma unroll
                for (int i = 0; i < 16; i++) sw += bf_lo(ww[i]) + bf_hi(ww[i]);
#pragma unroll 1
                for (int o = 16; o > 0; o >>= 1) sw += __shfl_xor_sync(0xffffffffu, sw, o);
                sts32(sb + SM_MISC + 20, __float_as_uint(sw));
                if (aw == 2) {
#pragma unroll
                    for (int i = 0; i < 3; i++) P.scr->kv[(hp * 8 + rb) * 96 + i * 32 + lane] = make_uint4(0, 0, 0, 0);
                    if (hp == 0) reinterpret_cast<uint4*>(&P.scr->cnt_o[rb * 128])[lane] = make_uint4(0, 0, 0, 0);
                    asm volatile("fence.acq_rel.gpu;" ::: "memory");
                    __syncwarp();
                }
                mbar_wait(bars + 8 * B_XR, 0);
#pragma unroll 1
                for (int r = aw * 6; r < min(aw * 6 + 6, 16); r++) {
                    const uint32_t buf = sb + SM_FB + 4096 + r * 2048;
                    uint4 xv[4];
                    uint32_t c2 = lds32(buf);
#pragma unroll
                    for (int i = 0; i < 4; i++) xv[i] = lds128(buf + i * 512 + lane * 16);
                    sts32(sb + SM_MISC + 12, 0u);
                    c2 = fabsf(bf_lo(c2) - bf_hi(c2)) < 0.25f * fabsf(bf_lo(c2)) ? dup_lo(c2) : 0u;
                    const uint32_t* xw = reinterpret_cast<const uint32_t*>(xv);
                    uint32_t d2[2] = {0u, 0u};
                    float s0 = 0.f, s1 = 0.f, q0 = 0.f, q1 = 0.f;
#pragma unroll
                    for (int i = 0; i < 16; i++) {
                        const uint32_t a = hsub2(xw[i], c2);
                        s0 += bf_lo(a); s1 += bf_hi(a);
                        d2[i & 1] = hfma2(a, ww[i], d2[i & 1]);
                        q0 = fmaf(bf_lo(a), bf_lo(a), q0); q1 = fmaf(bf_hi(a), bf_hi(a), q1);
                    }
                    sts128(sb + SM_SP + r * 512 + lane * 16, __float_as_uint(s0 + s1), __float_as_uint(q0 + q1),
                           __float_as_uint((bf_lo(d2[0]) + bf_hi(d2[0])) + (bf_lo(d2[1]) + bf_hi(d2[1]))), c2 << 16);
                }
                epoch = __shfl_sync(0xffffffffu, epoch, 0);
                if (aw < 2) nb_arrive(NB_FFN, 96);
                mbar_wait(bars + 8 * B_FF, 0);
#pragma unroll 1
                for (int i = 0; i < 3; i++) issue(i, i);
                const unsigned tag = epoch + 1u;
                if (aw == 2) {
                    nb_sync(NB_FFN, 96);
                    TLP(elect, 23);
                    float s = 0.f, q = 0.f, dt = 0.f, x0;
#pragma unroll 8
                    for (int j = 0; j < 16; j++) {
                        const uint4 e = lds128(sb + SM_SP + lane * 256 + ((j + lane) & 15) * 16);
                        s += __uint_as_float(e.x); q += __uint_as_float(e.y); dt += __uint_as_float(e.z); x0 = __uint_as_float(e.w);
                    }
                    s += __shfl_xor_sync(0xffffffffu, s, 1); q += __shfl_xor_sync(0xffffffffu, q, 1); dt += __shfl_xor_sync(0xffffffffu, dt, 1);
                    const float ms = s * (1.0f / D_);
                    const float vb = round_bf16(fmaxf(q - s * ms, 0.f) * (1.0f / D_));
                    const uint32_t md = pack_bf16(x0 + ms, sqrt_a(round_bf16(vb + 1e-5f)));
                    const uint32_t rbits = pack_bf16((dt - (bf_lo(md) - x0) * ldsf(sb + SM_MISC + 20)) * rcp(bf_hi(md)), 0.f);
                    const int row = blockIdx.x * 16 + (lane >> 1);
                    const uint32_t key = ((((rbits & 0x8000u) ? (~rbits & 0xFFFFu) : (rbits | 0x8000u)) + 1u) << 11) | (uint32_t)(2047 - row);
                    asm volatile("st.relaxed.gpu.global.v2.u32 [%0], {%1, %2};" :: "l"(&P.scr->rows[row]), "r"(md), "r"(tag) : "memory");
                    if (key == __reduce_max_sync(0xffffffffu, key))
                        asm volatile("st.relaxed.gpu.global.v4.u32 [%0], {%1, %2, %3, %3};" :: "l"(&P.scr->best[blockIdx.x]), "r"(key), "r"(md), "r"(tag) : "memory");
                    TLP(elect, 24);
                }
                {
                    float a[8], sq = 0.f, wt = 0.f;
#pragma unroll
                    for (int i = 0; i < 8; i++) a[i] = 0.f;
#pragma unroll 1
                    for (int m = 0; m < nc; m++) {
                        const int b = m % 3, c = c0 + m;
                        mbar_wait(fbar + b * 8, (m / 3) & 1);
                        uint4 v[8];
#pragma unroll
                        for (int i = 0; i < 8; i++) v[i] = lds128(fbuf + b * 4096 + i * 512 + lane * 16);
                        sts32(sb + SM_MISC + 12, 0u);
                        colsum8<true>(a, sq, v);
                        fence_regs(a);
                        wt += 1.0f;
                        issue(m + 3, b);
                        if ((c & 3) == 3 || m == nc - 1) {
#pragma unroll 1
                            for (int o = 8; o <= 16; o <<= 1) {
#pragma unroll
                                for (int i = 0; i < 8; i++) a[i] += __shfl_xor_sync(0xffffffffu, a[i], o);
                                sq += __shfl_xor_sync(0xffffffffu, sq, o);
                            }
                            float4* dst = &get_acc()->cs[((c >> 2) * 16 + hp) * 24 + lane];
                            if (lane < 8) { red_v4(dst, a[0], a[1], a[2], wt); red_v4(dst + 8, a[3], a[4], a[5], wt); red_v4(dst + 16, a[6], a[7], sq, wt); }
#pragma unroll
                            for (int i = 0; i < 8; i++) a[i] = 0.f;
                            wt = 0.f;
                        }
                    }
                    TLP(tid == 288, 26); TLP(tid == 320, 15); TLP(tid == 352, 22);
                }
                if (aw == 0) {
                    uint4 v[4];
                    unsigned it = 0;
                    bool ok = true;
#pragma unroll 1
                    do {
                        if (!ok) __nanosleep(200);
#pragma unroll
                        for (int i = 0; i < 4; i++) v[i] = ld_gpu(&P.scr->best[i * 32 + lane]);
                        ok = v[0].z == tag && v[1].z == tag && v[2].z == tag && v[3].z == tag;
                    } while (!__all_sync(0xffffffffu, ok) && ++it < (1u << 20));
#pragma unroll
                    for (int i = 1; i < 4; i++) if (v[i].x > v[0].x) v[0] = v[i];
                    const uint32_t key = __reduce_max_sync(0xffffffffu, v[0].x);
                    const uint32_t md = __reduce_or_sync(0xffffffffu, v[0].x == key ? v[0].y : 0u);
                    const int sel = 2047 - (int)(key & 2047u);
                    const uint4* xp = reinterpret_cast<const uint4*>(P.x + (size_t)sel * D_) + lane;
#pragma unroll
                    for (int i = 0; i < 4; i++) v[i] = __ldg(xp + i * 32);
                    const uint32_t m2 = __byte_perm(md, 0, 0x1010);
                    const float rs = rcp(bf_hi(md));
                    const uint32_t ord = (key >> 11) - 1u;
                    const float r = __uint_as_float(((ord & 0x8000u) ? (ord & 0x7FFFu) : (~ord & 0xFFFFu)) << 16);
                    sts128(sb + SM_MISC, (uint32_t)sel, __float_as_uint(round_bf16(rcp(1.0f + ex2(-r * LOG2E)))), epoch, 0u);
#pragma unroll
                    for (int i = 0; i < 4; i++) {
                        const uint32_t e0 = ln_pair(v[i].x, m2, rs), e1 = ln_pair(v[i].y, m2, rs), e2 = ln_pair(v[i].z, m2, rs), e3 = ln_pair(v[i].w, m2, rs);
                        const uint32_t xa = sb + SM_XS + i * 512 + (lane >> 2) * 64 + (lane & 3) * 4;
                        sts32(xa, __byte_perm(e0, e2, 0x5410)); sts32(xa + 16, __byte_perm(e0, e2, 0x7632));
                        sts32(xa + 32, __byte_perm(e1, e3, 0x5410)); sts32(xa + 48, __byte_perm(e1, e3, 0x7632));
                    }
                    TLP(elect, 25);
                    __syncwarp();
                    mbar_arrive_if(elect, bars + 8 * B_XS);
                }
            }
            if (aw == 2) {
                    const int l = lane < 24 ? lane : 0;
                    const float4* src = &get_acc()->cs[((l >> 3) * 16 + hp) * 24 + (l & 7)];
                    float4 v0, v1, v2;
                    uint4 v[4];
                    unsigned it = 0;
                    bool ok;
#pragma unroll 1
                    do {
                        v0 = ld_gpu(src); v1 = ld_gpu(src + 8); v2 = ld_gpu(src + 16);
                        ok = v0.w == 32.0f && v1.w == 32.0f && v2.w == 32.0f;
#pragma unroll
                        for (int i = 0; i < 4; i++) v[i] = ld_gpu(reinterpret_cast<const uint4*>(&P.scr->rows[rb * 256]) + i * 32 + lane);
#pragma unroll
                        for (int i = 0; i < 4; i++) ok = ok && v[i].y == epoch + 1u && v[i].w == epoch + 1u;
                    } while (!__all_sync(0xffffffffu, ok) && ++it < (1u << 20));
#pragma unroll
                    for (int i = 0; i < 4; i++) {
                        const uint32_t o = i * 256 + lane * 8;
                        sts64(sb + SM_MD + o, v[i].x, v[i].z);
                        sts64(sb + SM_RS + o, __float_as_uint(rcp(bf_hi(v[i].x))), __float_as_uint(rcp(bf_hi(v[i].z))));
                        const uint32_t h0 = hmul2(dup_lo(v[i].x), 0xBF00BF00u), h1 = hmul2(dup_lo(v[i].z), 0xBF00BF00u);
                        sts128(sb + SM_AX + o * 4, h0, h0 & 0xFFFFu, 0u, 0u);
                        sts128(sb + SM_AX + o * 4 + 16, h1, h1 & 0xFFFFu, 0u, 0u);
                    }
                    sts128(sb + SM_H + lane * 16, 0u, 0u, 0u, 0u); sts128(sb + SM_H + 512 + lane * 16, 0u, 0u, 0u, 0u);
                    const uint32_t e2 = __reduce_max_sync(0xffffffffu, l >= 16 ? __float_as_uint(v2.z) : 0u) >> 23;
                    sts32(sb + SM_MISC + 16, (uint32_t)min(max(187 - (int)((e2 + 1) >> 1), 1), 180) << 23);
                    float cc[8] = {v0.x, v0.y, v0.z, v1.x, v1.y, v1.z, v2.x, v2.y};
                    const uint32_t bx = sb + SM_BX + (l >> 3) * 1024;
#pragma unroll 1
                    for (int k = 0; k < 8; k++) {
                        uint32_t w[4];
#pragma unroll
                        for (int i = 0; i < 4; i++) {
                            w[i] = pack_bf16(cc[2 * i], cc[2 * i + 1]);
                            cc[2 * i] -= bf_lo(w[i]); cc[2 * i + 1] -= bf_hi(w[i]);
                        }
                        sts128(bx + k * 128 + (((l & 7) ^ k) * 16), w[0], w[1], w[2], w[3]);
                    }
                    fence_async_smem();
                    __syncwarp();
                    mbar_arrive_if(elect, bars + 8 * B_LN);
                    TLP(elect, 28);
                }
            mbar_wait(bars + 8 * B_XS, 0);
            if (ffn) {
                float a[8];
#pragma unroll
                for (int i = 0; i < 8; i++) a[i] = 0.f;
                TLP(elect, 40 + aw);
                gemv_run<256>(a, ng, nc % 3, (nc / 3) & 1, fbuf + (lane >> 4) * 2048 + (lane & 15) * 16, sb + SM_XS + g0 * 64 + (lane & 12) * 4, 64, fbar, sb + SM_MISC + 12,
                              [&](int m, int b) { issue(nc + m + 3, b); });
                TLP(elect, 44 + aw);
#pragma unroll 1
                for (int o = 4; o <= 8; o <<= 1) {
#pragma unroll
                    for (int i = 0; i < 8; i++) a[i] += __shfl_xor_sync(0xffffffffu, a[i], o);
                }
                if ((lane & 12) == 0) {
                    const uint32_t ga = sb + SM_GU + aw * 256 + (lane >> 4) * 128 + (lane & 3) * 32;
                    sts128(ga, __float_as_uint(a[0]), __float_as_uint(a[1]), __float_as_uint(a[2]), __float_as_uint(a[3]));
                    sts128(ga + 16, __float_as_uint(a[4]), __float_as_uint(a[5]), __float_as_uint(a[6]), __float_as_uint(a[7]));
                }
                nb_sync(NB_AUX, 96);
                if (warp == 9) {
                    if (elect_one()) {
                        mbar_expect_tx(bars + 8 * B_DN, 32768);
                        tma_3d(sb + SM_FB + 8192, &tmS.wd8, bars + 8 * B_DN, 0, blockIdx.x * 32, 0);
                    }
                    const uint32_t ga = sb + SM_GU + lane * 4;
                    const float gg = round_bf16((ldsf(ga) + ldsf(ga + 256)) + ldsf(ga + 512));
                    const float uu = round_bf16((ldsf(ga + 128) + ldsf(ga + 384)) + ldsf(ga + 640));
                    asm volatile("st.shared.u16 [%0], %1;" :: "r"(sb + SM_H + (lane >> 3) * 256 + 112 + (lane & 7) * 2), "h"((uint16_t)pack_bf16(round_bf16(silu_f(gg)) * uu, 0.f)) : "memory");
                    fence_async_smem();
                }
                __syncwarp();
                TLP(tid == 288, 27);
            }
        }
        {
            TLP(tid == 288, 38);
            const int w4 = warp & 3;
            const uint32_t sp = sb + SM_FB + w4 * 1536;
            auto send = [&](int h) {
                if (elect_one()) {
                    asm volatile("cp.reduce.async.bulk.global.shared::cta.bulk_group.add.noftz.f16 [%0], [%1], 1536;"
                                 :: "l"(&P.scr->kv[(hp * 8 + h * 4 + w4) * 96]), "r"(sp) : "memory");
                    asm volatile("cp.async.bulk.commit_group;" ::: "memory");
                }
            };
            float ya[4] = {0.f, 0.f, 0.f, 0.f}, yb[4] = {0.f, 0.f, 0.f, 0.f};
            uint4 g0[3];
#pragma unroll 1
            for (int h = 0; h < 2; h++) {
                {
                    float d[20];
                    const uint32_t alo = dlo(sb + SM_PHI + h * 32768, 16), vlo = dlo(sb + SM_V + h * 20480, 16);
                    mbar_wait(bars + 8 * (B_PHI + h), 0);
                    wgmma_fence();
#pragma unroll
                    for (int k = 0; k < 16; k++)
                        wgmma_ss_n40(d, desc_from(alo + (k >> 2) * 512 + (k & 3) * 2, DH128), desc_from(vlo + (k >> 2) * 320 + (k & 3) * 2, DH128), k);
                    wgmma_commit();
#pragma unroll
                    for (int j = 0; j < 3; j++) g0[j] = ld_gpu(&P.scr->kv[(hp * 8 + w4) * 96 + j * 32 + lane]);
                    asm volatile("cp.async.bulk.wait_group.read 0;" ::: "memory");
                    __syncwarp();
                    const float ksc = ldsf(sb + SM_MISC + 16);
                    wgmma_wait<0>();
                    fence_regs(d);
#define U(x) pack_f16(d[x] * ksc, d[x + 1] * ksc)
                    sts128(sp + lane * 16, U(0), U(4), U(8), pack_f16(d[16], 1.0f));
                    sts128(sp + 512 + lane * 16, U(2), U(6), U(10), pack_f16(d[18], 1.0f));
                    sts128(sp + 1024 + lane * 16, U(12), U(14), 0u, 0x3C000000u);
#undef U
                    fence_async_smem();
                    __syncwarp();
                    send(h);
                    TLP(tid == 256, 30 + h);
                    nb_sync(NB_KV, 128);
                    if (h) break;
                    if (warp == 8 && elect_one()) {
                        mbar_expect_tx(bars + 8 * B_X, 32768);
                        tma_2d(sb, &tmX2, bars + 8 * B_X, (hp >> 1) * 128, rb * 256 + (hp & 1) * 128);
                        tma_2d(sb + 16384, &tmX2, bars + 8 * B_X, (hp >> 1) * 128 + 64, rb * 256 + (hp & 1) * 128);
                        load_wo(4);
                    }
                    __syncwarp();
                }
                if (blockIdx.x < 112) {
                    const uint32_t hlo = dlo(sb + SM_H, 256);
                    mbar_wait(bars + 8 * B_DN, 0);
                    mbar_wait(bars + 8 * (B_DN + 1), 0);
                    wgmma_fence();
#pragma unroll 2
                    for (int k = 0; k < 16; k++) {
                        wgmma_ss_n8_ta(yb, desc_from(dlo(sb + 6 * 16384, 16) + k * 128, DH128), desc_from(hlo + (k & 1) * 32 + 7 - (k >> 1), 8), k);
                        wgmma_ss_n8_ta(ya, desc_from(dlo(sb + SM_FB + 8192, 16) + k * 128, DH128), desc_from(hlo + (k & 1) * 32 + 7 - (k >> 1), 8), k);
                    }
                    wgmma_commit();
                    wgmma_wait<0>();
                    fence_regs(ya); fence_regs(yb);
                    if (warp == 8) {
                        nb_sync(NB_KV, 128);
                        if (elect_one()) { load_wo(2); load_wo(3); }
                        __syncwarp();
                    } else {
                        nb_arrive(NB_KV, 128);
                    }
                    TLP(tid == 288, 29);
                }
            }
            const float kus = __uint_as_float((254u << 23) - lds32(sb + SM_MISC + 16));
            kv_gather<1>(g0, &P.scr->kv[(hp * 8 + w4) * 96 + lane], sb + SM_KVOP + w4 * 256, lane, kus);
            mbar_arrive_if(elect, bars + 8 * B_KV);
            asm volatile("cp.async.bulk.wait_group.read 0;" ::: "memory");
            __syncwarp();
            if (blockIdx.x < 112) {
#define U(x) __float_as_uint(x)
                sts128(sp + lane * 16, U(ya[0]), U(ya[1]), U(ya[2]), U(1.0f));
                sts128(sp + 512 + lane * 16, U(ya[3]), U(yb[0]), U(yb[1]), U(1.0f));
                sts128(sp + 1024 + lane * 16, U(yb[2]), U(yb[3]), 0u, U(1.0f));
#undef U
                fence_async_smem();
                __syncwarp();
                if (elect_one()) {
                    asm volatile("cp.reduce.async.bulk.global.shared::cta.bulk_group.add.f32 [%0], [%1], 1536;"
                                 :: "l"(&get_acc()->y[((blockIdx.x & 3) * 4 + w4) * 96]), "r"(sp) : "memory");
                    asm volatile("cp.async.bulk.commit_group;" ::: "memory");
                }
                __syncwarp();
            }
            if (w4 >= 2) {
                uint4 g1[6];
#pragma unroll
                for (int j = 0; j < 6; j++) g1[j] = make_uint4(0, 0, 0, 0);
                kv_gather<2>(g1, &P.scr->kv[(hp * 8 + 2 * w4) * 96 + lane], sb + SM_KVOP - 5120 + (w4 - 2) * 512, lane, kus);
                mbar_arrive_if(lane < 2, bars + 8 * (B_KV + 1));
            }
            asm volatile("cp.async.bulk.wait_group.read 0;" ::: "memory");
            __syncwarp();
            mbar_arrive_if(elect, bars + 8 * B_S1);
        }
        if (warp == 8) {
            if (elect_one()) {
                uint4 cnt;
                mbar_wait(bars + 8 * B_O, 0);
#pragma unroll
                for (int i = 0; i < 16; i++) {
                    if (!(i & 3)) cnt = make_uint4(0, 0, 0, 0);
                    unsigned it = 0;
#pragma unroll 1
                    while (((i & 3) == 0 ? cnt.x : ((i & 3) == 1 ? cnt.y : ((i & 3) == 2 ? cnt.z : cnt.w))) < 2u && ++it < (1u << 20))
                        cnt = ld_gpu(reinterpret_cast<const uint4*>(&P.scr->cnt_o[rb * 128 + (hp & 1) * 64 + (i >> 3) * 32 + (i & 4)]));
                    if (PFENCE) asm volatile("fence.proxy.async.global;" ::: "memory");
                    if ((i & 3) == 0 && i < 12) TL(i == 0 ? 21 : (i == 4 ? 34 : 36));
                    if (i == 4 || i > 5) mbar_wait(bars + 8 * (B_SD + max(i - 5, 0)), 0);
                    load_o(i);
                    if (i == 3) { load_wo(5); mbar_wait(bars + 8 * B_S1, 0); load_wo(6); }
                    if (i >= 5 && i < 14) load_wo(i + 2);
                }
            }
        } else if (warp < 11) {
            if (elect_one()) {
#pragma unroll
                for (int w = 0; w < 2; w++) {
                    mbar_wait(bars + 8 * (B_OW + 2 * aw + w), 0);
                    asm volatile("cp.async.bulk.tensor.2d.global.shared::cta.bulk_group [%0, {%2, %3}], [%1];"
                                 :: "l"(&tmOs), "r"(sb + SM_OS + w * 8192), "r"(aw * 512 + hp * 32), "r"(rb * 256 + w * 128) : "memory");
                    asm volatile("cp.async.bulk.commit_group;" ::: "memory");
                }
#pragma unroll
                for (int w = 0; w < 2; w++) {
                    if (w) asm volatile("cp.async.bulk.wait_group 0;" ::: "memory"); else asm volatile("cp.async.bulk.wait_group 1;" ::: "memory");
                    asm volatile("fence.proxy.async.global;" ::: "memory");
                    asm volatile("red.relaxed.gpu.global.add.u32 [%0], 1;" :: "l"(&P.scr->cnt_o[rb * 128 + w * 64 + aw * 32 + (hp >> 1)]) : "memory");
                }
                asm volatile("mbarrier.arrive.shared::cta.b64 _, [%0];" :: "r"(bars + 8 * B_OS) : "memory");
            }
        } else if (warp == 11) {
            const uint4 misc = lds128(sb + SM_MISC);
            if ((int)(misc.x >> 7) == rb * 2 + (hp & 1)) {
                float y[4] = {0.f, 0.f, 0.f, 0.f};
#pragma unroll 1
                for (int rep = 0; rep < 4; rep++) {
                    const float4* yp = &get_acc()->y[(rep * 4 + (lane >> 3)) * 96 + (hp >> 3) * 32 + (lane & 7) * 4 + ((hp >> 1) & 3)];
                    float4 u, v;
                    unsigned it = 0;
#pragma unroll 1
                    do { u = ld_gpu(yp); v = ld_gpu(yp + 32); } while (!__all_sync(0xffffffffu, u.w == 28.0f && v.w == 28.0f) && ++it < (1u << 20));
                    if (hp & 8) { y[0] += u.y; y[1] += v.x; y[2] += u.z; y[3] += v.y; } else { y[0] += u.x; y[1] += u.z; y[2] += u.y; y[3] += v.x; }
                }
                const uint32_t sg = __byte_perm(misc.y, 0, 0x3232), ya = sb + SM_Y + ((lane >> 3) * 16 + (lane & 7)) * 2;
                const uint32_t w0 = hmul2(pack_bf16(y[0], y[1]), sg), w1 = hmul2(pack_bf16(y[2], y[3]), sg);
                asm volatile("st.shared.u16 [%0], %1;" :: "r"(ya), "h"((uint16_t)w0) : "memory");
                asm volatile("st.shared.u16 [%0], %1;" :: "r"(ya + 16), "h"((uint16_t)(w0 >> 16)) : "memory");
                asm volatile("st.shared.u16 [%0], %1;" :: "r"(ya + 128), "h"((uint16_t)w1) : "memory");
                asm volatile("st.shared.u16 [%0], %1;" :: "r"(ya + 144), "h"((uint16_t)(w1 >> 16)) : "memory");
                __syncwarp();
                if (lane < 16) {
                    const uint4 xc = __ldg(reinterpret_cast<const uint4*>(P.x + (size_t)misc.x * D_ + (hp >> 1) * 128) + lane);
                    const uint32_t m2 = __byte_perm(lds32(sb + SM_MD + (misc.x & 255u) * 4), 0, 0x1010);
                    const float r = ldsf(sb + SM_RS + (misc.x & 255u) * 4);
                    const uint4 yv = lds128(sb + SM_Y + lane * 16);
                    sts128(sb + SM_Y + lane * 16, silu_pair(hadd2(ln_pair(xc.x, m2, r), yv.x)), silu_pair(hadd2(ln_pair(xc.y, m2, r), yv.y)),
                           silu_pair(hadd2(ln_pair(xc.z, m2, r), yv.z)), silu_pair(hadd2(ln_pair(xc.w, m2, r), yv.w)));
                    sts128(sb + SM_Y + 256 + lane * 16, xc.x, xc.y, xc.z, xc.w);
                }
                __syncwarp();
                mbar_arrive_if(elect, bars + 8 * B_Y);
                TLP(elect, 39);
            }
        }
    } else {
        const int wg = warp >> 2, w4 = warp & 3, g = lane >> 2;
        nb_sync(0, NTHREADS);
        asm volatile("setmaxnreg.inc.sync.aligned.u32 224;");
        TLP(tid == 0, 1);
        const int row0 = wg * 128 + w4 * 16 + g;
        float pq0[16], pq1[16];
        float rs[4];
        uint32_t f2[8], f3[8], q0[8], q1[8], q2[8], q3[8];
        float qa[16], qb[16];
        const uint32_t wlo = dlo(sb + SM_WPHI, 16);
        const uint32_t sw0 = (uint32_t)(((w4 * 2) ^ (lane & 7)) * 16), sw1 = sw0 ^ 16u;
        {
            float acc0[96], acc1[96];
            {
                const uint32_t alo0 = dlo(sb + wg * 16384, 16), blo0 = dlo(sb + 32768, 8192);
                {
#pragma unroll
                    for (int k = 0; k < 4; k++) {
                        if (k == 0) asm volatile("cp.async.wait_group 1;" ::: "memory");
                        if (k == 2) { wgmma_commit(); asm volatile("cp.async.wait_group 0;" ::: "memory"); }
                        if (!(k & 1)) { fence_async_smem(); nb_sync(NB_STAG, 256); wgmma_fence(); }
                        if (k == 0) { TLP(tid == 0, 2); TLG(tid == 0, 49); }
                        wgmma_ss_n192_tb(acc0, desc_from(alo0 + k * 2, DH128), desc_from(blo0 + k * 128, DH128), k);
                        wgmma_ss_n192_tb(acc1, desc_from(alo0 + 512 + k * 2, DH128), desc_from(blo0 + k * 128, DH128), k);
                    }
                    wgmma_commit();
                }
                int s = 1, ph = 0, ps = 0;
#pragma unroll 1
                for (int ks = 1; ks < 16; ks++) {
                    const bool hold = wg && ks == 15;
                    if (hold) {
                        wgmma_wait<0>();
                        mbar_arrive_if(elect, bars + 8 * (B_EMPTY + ps));
                        nb_sync(NB_LEAD, 256);
                    }
                    mbar_wait(bars + 8 * (B_FULL + s), ph);
                    const uint32_t alo = alo0 + s * (STAGE >> 4), blo = blo0 + s * (STAGE >> 4);
                    wgmma_fence();
#pragma unroll
                    for (int k = 0; k < 4; k++) {
                        if (k == SARR && !wg && ks == 15) nb_arrive(NB_LEAD, 256);
                        wgmma_ss_n192_tb(acc0, desc_from(alo + k * 2, DH128), desc_from(blo + k * 128, DH128), 1);
                        wgmma_ss_n192_tb(acc1, desc_from(alo + 512 + k * 2, DH128), desc_from(blo + k * 128, DH128), 1);
                        if (k == 0) {
                            wgmma_commit();
                            wgmma_wait<1>();
                            mbar_arrive_if(elect && !hold, bars + 8 * (B_EMPTY + ps));
                        }
                    }
                    wgmma_commit();
                    ps = s;
                    if (++s == 3) { s = 0; ph ^= 1; }
                }
            }
            mbar_wait(bars + 8 * B_LN, 0);
            wgmma_fence();
            wgmma_ss_n192_tb(acc0, desc_from(dlo(sb + SM_AX + wg * 2048, 0), 128u >> 4), desc_from(dlo(sb + SM_BX, 1024), 1u << 30), 1);
            wgmma_ss_n192_tb(acc1, desc_from(dlo(sb + SM_AX + wg * 2048 + 1024, 0), 128u >> 4), desc_from(dlo(sb + SM_BX, 1024), 1u << 30), 1);
            wgmma_commit();
            mbar_wait(bars + 8 * (B_EMPTY + 2), 0);
            mbar_wait(bars + 8 * B_WPHI, 0);
            {
                uint32_t md[4];
#pragma unroll
                for (int i = 0; i < 4; i++) {
                    const int r = row0 + (i >> 1) * 64 + (i & 1) * 8;
                    md[i] = __byte_perm(lds32(sb + SM_MD + r * 4), 0, 0x3232);
                    rs[i] = ldsf(sb + SM_RS + r * 4);
                }
                const uint32_t zb = sb + SM_V + wg * 10240 + (lane >> 4) * 5120 + 4096 + (lane & 7) * 128 + (sw0 ^ ((lane & 8) * 2));
                stsm_t(zb, md[0], md[1], md[2], md[3]);
                stsm_t(zb + 20480, md[0], md[1], md[2], md[3]);
            }
            wgmma_wait<0>();
            fence_regs(acc0); fence_regs(acc1);
            TLP(tid == 0, 3); TLG(tid == 0, 50);
            const uint32_t vb = sb + SM_V + wg * 10240 + lane * 128;
            uint32_t f0[8], f1[8], v[8];
            pack_head<64>(acc0, v); stsm_t(vb + sw0, v[0], v[2], v[4], v[6]); stsm_t(vb + sw1, v[1], v[3], v[5], v[7]);
            pack_head<64>(acc1, v); stsm_t(vb + 5120 + sw0, v[0], v[2], v[4], v[6]); stsm_t(vb + 5120 + sw1, v[1], v[3], v[5], v[7]);
#pragma unroll
            for (int i = 32; i < 48; i++) { asm volatile("" : "+f"(acc0[i]) :: "memory"); asm volatile("" : "+f"(acc1[i]) :: "memory"); }
            pack_head<32>(acc0, f0); pack_head<32>(acc1, f1);
            wgmma_fence();
            feat_mma(pq0, f0, wlo); feat_mma(pq1, f1, wlo);
            wgmma_commit();
            pack_head<80>(acc0, v); stsm_t(vb + 20480 + sw0, v[0], v[2], v[4], v[6]); stsm_t(vb + 20480 + sw1, v[1], v[3], v[5], v[7]);
            pack_head<80>(acc1, v); stsm_t(vb + 25600 + sw0, v[0], v[2], v[4], v[6]); stsm_t(vb + 25600 + sw1, v[1], v[3], v[5], v[7]);
            pack_head<48>(acc0, f2); pack_head<48>(acc1, f3);
            pack_head<0>(acc0, q0); pack_head<0>(acc1, q1);
#pragma unroll
            for (int i = 0; i < 16; i++) { qa[i] = acc0[16 + i]; qb[i] = acc1[16 + i]; }
            fence_regs(f2); fence_regs(f3); fence_regs(q0); fence_regs(q1);
            wgmma_wait<0>();
            fence_regs(pq0); fence_regs(pq1); fence_regs(f0); fence_regs(f1);
            mbar_arrive_if(elect, bars + 8 * B_T);
            TLP(tid == 0, 4);
        }
#pragma unroll 1
        for (int h = 0; h < 2; h++) {
            const uint32_t pb = sb + SM_PHI + wg * 16384 + lane * 128 + h * 32768;
            key_head(pq0, pq1, rs, pb + sw0, pb + sw1);
            wgmma_fence();
            feat_mma(pq0, f2, wlo + 128 - h * 128); feat_mma(pq1, f3, wlo + 128 - h * 128);
            wgmma_commit();
            fence_async_smem();
            __syncwarp();
            mbar_arrive_if(elect, bars + 8 * (B_PHI + h));
            TLP(tid == 0, 6 + 2 * h);
            mbar_wait(bars + 8 * B_T, 0);
            wgmma_wait<0>();
            fence_regs(pq0); fence_regs(pq1); fence_regs(f2); fence_regs(f3);
#pragma unroll
            for (int j = 0; j < 8; j++) { f2[j] = q0[j]; f3[j] = q1[j]; }
            fence_regs(f2); fence_regs(f3);
        }
#pragma unroll
        for (int j = 0; j < 8; j++) { q2[j] = pack_bf16(qa[2 * j], qa[2 * j + 1]); q3[j] = pack_bf16(qb[2 * j], qb[2 * j + 1]); }
        const int orow = (hp & 1) * 128 + wg * 64 + w4 * 16 + (lane >> 4);
        const size_t goff = (size_t)(rb * 256 + orow) * D_ + (hp >> 1) * 128 + (lane & 15) * 8;
        uint4 gv[8], xv[8];
#pragma unroll
        for (int i = 0; i < 8; i++) xv[i] = make_uint4(0, 0, 0, 0);
#pragma unroll
        for (int i = 0; i < GSPLIT2; i++) gv[i] = make_uint4(0, 0, 0, 0);
        const uint32_t rowc = sb + ((lane >> 3) & 1) * 16384 + (wg * 64 + w4 * 16 + (lane >> 4)) * 128;
        {
            const uint32_t od = sb + SM_OS + (wg * 128 + w4 * 16) * 64 + lane * 16;
#pragma unroll 1
            for (int h = 0; h < 2; h++) {
                uint32_t pa[8], na[8], pb[8], nb[8];
                features(pq0, pq1, rs, pa, na, pb, nb);
                TLP(tid == 0, 16 + h);
                if (h == 0) {
                    wgmma_fence();
                    feat_mma(pq0, q2, wlo + 128); feat_mma(pq1, q3, wlo + 128);
                    wgmma_commit();
                    mbar_wait(bars + 8 * B_X, 0);
#pragma unroll
                    for (int i = 0; i < 8; i++) xv[i] = lds128(rowc + i * 256 + (((lane & 7) ^ ((2 * i + (lane >> 4)) & 7)) * 16));
#pragma unroll
                    for (int i = 0; i < GSPLIT; i++) { gv[i] = xv[i]; gate_item(gv[i], sb, orow + 2 * i); }
                    wgmma_wait<0>();
                    fence_regs(pq0); fence_regs(pq1); fence_regs(q2); fence_regs(q3);
                    TLP(tid == 0, 18);
                } else {
#pragma unroll
                    for (int i = GSPLIT; i < GSPLIT2; i++) { gv[i] = xv[i]; gate_item(gv[i], sb, orow + 2 * i); }
                    TLP(tid == 0, 10);
                }
                {
                    float d0[20], e0[20], d1[20], e1[20];
                    const uint32_t klo = dlo(sb + SM_KVOP - h * 5120, 128);
                    fence_regs(pa); fence_regs(na); fence_regs(pb); fence_regs(nb);
                    mbar_wait(bars + 8 * (B_KV + h), 0);
                    TLP(tid == 0, 32 + h);
                    wgmma_fence();
                    o_mma(d0, e0, pa, na, klo);
                    wgmma_commit();
                    o_mma(d1, e1, pb, nb, klo);
                    wgmma_commit();
                    if (h) mbar_wait(bars + 8 * B_OS, 0);
                    wgmma_wait<1>();
                    fence_regs(d0); fence_regs(e0); fence_regs(pa); fence_regs(na);
                    o_store(d0, e0, od);
                    wgmma_wait<0>();
                    fence_regs(d1); fence_regs(e1); fence_regs(pb); fence_regs(nb);
                    o_store(d1, e1, od + 4096);
                    fence_async_smem();
                    __syncwarp();
                    mbar_arrive_if(elect, bars + 8 * (B_OW + 2 * h + wg));
                    mbar_arrive_if(elect, bars + 8 * (B_O + h));
                }
                TLP(tid == 0, 9 + 2 * h);
            }
        }
        float ghr[8], ghm[8];
        float acc[64];
        {
            const uint32_t alo0 = dlo(sb + wg * 8192, 16), blo0 = dlo(sb, 8192);
#pragma unroll
            for (int i = 0; i < 16; i++) {
                const uint32_t alo = alo0 + o_slot(i) * 1024, blo = blo0 + wo_slot(i) * 1024;
                mbar_wait(bars + 8 * (B_OF + i), 0);
                if (i == OSTAG && wg == 0) nb_sync(NB_STAG, 256);
                wgmma_fence();
#pragma unroll
                for (int k = 0; k < 4; k++) {
                    if (i == 15 && k == OARR && wg) nb_arrive(NB_STAG, 256);
                    wgmma_ss_n128_tb(acc, desc_from(alo + k * 2, DH128), desc_from(blo + k * 128, DH128), k | i);
                    if (k == OREL) {
                        if (i > 0 && i < 12) {
                            wgmma_commit();
                            wgmma_wait<1>();
                            mbar_arrive_if(elect, bars + 8 * (B_SD + i - 1));
                        }
                    }
                }
                wgmma_commit();
                if (i == 0) { TLP(tid == 0, 12); TLG(tid == 0, 51); }
                if (i == 0) {
#pragma unroll
                    for (int q = GSPLIT2; q < 8; q++) { ghr[q] = 0.5f * ldsf(sb + SM_RS + (orow + 2 * q) * 4); ghm[q] = -bf_lo(lds32(sb + SM_MD + (orow + 2 * q) * 4)) * ghr[q]; }
                }
                static_assert(2 * (8 - GSPLIT2) <= 16 - GST, "");
                if (i >= GST && GSPLIT2 + (i - GST) / 2 < 8) {
                    const int q = GSPLIT2 + (i - GST) / 2;
                    if ((i - GST) & 1) { gv[q].z = gate_pair(xv[q].z, ghr[q], ghm[q]); gv[q].w = gate_pair(xv[q].w, ghr[q], ghm[q]); asm volatile("" : "+r"(gv[q].z), "+r"(gv[q].w) :: "memory"); }
                    else { gv[q].x = gate_pair(xv[q].x, ghr[q], ghm[q]); gv[q].y = gate_pair(xv[q].y, ghr[q], ghm[q]); asm volatile("" : "+r"(gv[q].x), "+r"(gv[q].y) :: "memory"); }
                }
            }
        }
        wgmma_wait<0>();
        fence_regs(acc);
        TLP(tid == 0, 13); TLG(tid == 0, 52);
        {
            const uint32_t stg = sb + (wg * 64 + w4 * 16) * 128;
            const int rr = lane & 7;
#pragma unroll
            for (int c = 0; c < 4; c++) {
                const uint32_t a0 = stg + (c >> 1) * 16384 + rr * 128 + ((((c & 1) * 4 + (lane >> 3)) ^ rr) * 16);
                stsm(a0, pack_bf16(acc[c * 16 + 0], acc[c * 16 + 1]), pack_bf16(acc[c * 16 + 4], acc[c * 16 + 5]),
                     pack_bf16(acc[c * 16 + 8], acc[c * 16 + 9]), pack_bf16(acc[c * 16 + 12], acc[c * 16 + 13]));
                stsm(a0 + 1024, pack_bf16(acc[c * 16 + 2], acc[c * 16 + 3]), pack_bf16(acc[c * 16 + 6], acc[c * 16 + 7]),
                     pack_bf16(acc[c * 16 + 10], acc[c * 16 + 11]), pack_bf16(acc[c * 16 + 14], acc[c * 16 + 15]));
            }
            __syncwarp();
#pragma unroll
            for (int i = 0; i < 8; i++) {
                const uint4 sv = lds128(rowc + i * 256 + (((lane & 7) ^ ((2 * i + (lane >> 4)) & 7)) * 16));
                uint4 o;
                o.x = hadd2(xv[i].x, hmul2(sv.x, gv[i].x)); o.y = hadd2(xv[i].y, hmul2(sv.y, gv[i].y));
                o.z = hadd2(xv[i].z, hmul2(sv.z, gv[i].z)); o.w = hadd2(xv[i].w, hmul2(sv.w, gv[i].w));
                *reinterpret_cast<uint4*>(P.out + goff + (size_t)i * 2 * D_) = o;
            }
            const uint32_t sel = lds32(sb + SM_MISC);
            if ((int)(sel >> 4) == rb * 16 + (orow >> 4)) {
                mbar_wait(bars + 8 * B_Y, 0);
                if ((sel & 1u) == (uint32_t)(lane >> 4)) {
                    const int i = (sel & 15u) >> 1;
                    const uint4 sv = lds128(rowc + i * 256 + (((lane & 7) ^ (sel & 7u)) * 16));
                    const uint4 gq = lds128(sb + SM_Y + (lane & 15) * 16), xq = lds128(sb + SM_Y + 256 + (lane & 15) * 16);
                    *reinterpret_cast<uint4*>(P.out + goff + (size_t)i * 2 * D_) = make_uint4(hadd2(xq.x, hmul2(sv.x, gq.x)), hadd2(xq.y, hmul2(sv.y, gq.y)), hadd2(xq.z, hmul2(sv.z, gq.z)), hadd2(xq.w, hmul2(sv.w, gq.w)));
                }
            }
        }
        TLG(tid == 0, 53);
        if (tid == 0) { TL(14); TL_DUMP(); }
        if (blockIdx.x == 0 && tid == 0) asm volatile("st.relaxed.gpu.global.u32 [%0], %1;" :: "l"(&P.scr->epoch), "r"(lds32(sb + SM_MISC + 8) + 1u) : "memory");
    }
}

typedef CUresult (*PFN_encodeTiled)(CUtensorMap*, CUtensorMapDataType, cuuint32_t, void*, const cuuint64_t*, const cuuint64_t*,
                                    const cuuint32_t*, const cuuint32_t*, CUtensorMapInterleave, CUtensorMapSwizzle,
                                    CUtensorMapL2promotion, CUtensorMapFloatOOBfill);

void make_map(PFN_encodeTiled fn, CUtensorMap* m, const void* ptr, int rank, const cuuint64_t* dims, const cuuint64_t* strides, const cuuint32_t* box, CUtensorMapSwizzle sw) {
    const cuuint32_t es[5] = {1, 1, 1, 1, 1};
    fn(m, CU_TENSOR_MAP_DATA_TYPE_BFLOAT16, rank, const_cast<void*>(ptr), dims, strides, box, es, CU_TENSOR_MAP_INTERLEAVE_NONE,
       sw, CU_TENSOR_MAP_L2_PROMOTION_L2_256B, CU_TENSOR_MAP_FLOAT_OOB_FILL_NONE);
}
void make_2d(PFN_encodeTiled fn, CUtensorMap* m, const void* ptr, uint64_t rows, uint64_t cols, uint32_t box_rows, uint32_t box_cols, CUtensorMapSwizzle sw) {
    const cuuint64_t gd[2] = {cols, rows}, gs[1] = {cols * 2};
    const cuuint32_t bd[2] = {box_cols, box_rows};
    make_map(fn, m, ptr, 2, gd, gs, bd, sw);
}

}

extern "C" void kernel_launch(void* const* d_in, const int* in_sizes, int n_in, void* d_out, int out_size) {
    (void)in_sizes; (void)n_in; (void)out_size;
    static PFN_encodeTiled fn = nullptr;
    static void* o_ptr = nullptr;
    static void* scr_ptr = nullptr;
    static void* tl_ptr = nullptr;
    if (!fn) {
        void* p = nullptr;
        cudaDriverEntryPointQueryResult st;
        cudaGetDriverEntryPoint("cuTensorMapEncodeTiled", &p, cudaEnableDefault, &st);
        fn = (PFN_encodeTiled)p;
        cudaGetSymbolAddress(&o_ptr, g_o);
        cudaGetSymbolAddress(&scr_ptr, g_scr);
        cudaFuncSetAttribute(fused_kernel, cudaFuncAttributeMaxDynamicSharedMemorySize, SM_TOTAL);
    }
    CUtensorMap tmX, tmW, tmPhi, tmWo, tmO, tmX2, tmOs;
    SideMaps tmS;
    make_2d(fn, &tmX, d_in[0], S_, D_, 256, 64, CU_TENSOR_MAP_SWIZZLE_128B);
    {
        const cuuint64_t gd[3] = {1024, 1024, 3}, gs[2] = {6144, 2048};
        const cuuint32_t bd[3] = {64, 64, 3};
        make_map(fn, &tmW, d_in[1], 3, gd, gs, bd, CU_TENSOR_MAP_SWIZZLE_128B);
    }
    make_2d(fn, &tmS.wc, d_in[1], D_, 3 * D_, 32, 64, CU_TENSOR_MAP_SWIZZLE_NONE);
    make_2d(fn, &tmPhi, d_in[2], 1024, 32, 64, 32, CU_TENSOR_MAP_SWIZZLE_64B);
    make_2d(fn, &tmS.wg, d_in[6], D_, F_, 32, 32, CU_TENSOR_MAP_SWIZZLE_NONE);
    make_2d(fn, &tmS.wu, d_in[7], D_, F_, 32, 32, CU_TENSOR_MAP_SWIZZLE_NONE);
    {
        const cuuint64_t gd[3] = {64, F_, 16}, gs[2] = {2048, 128};
        const cuuint32_t bd[3] = {64, 32, 8};
        make_map(fn, &tmS.wd8, d_in[8], 3, gd, gs, bd, CU_TENSOR_MAP_SWIZZLE_128B);
    }
    {
        const cuuint64_t gd[4] = {64, 64, 16, 16}, gs[3] = {2048, 64 * 2048, 128};
        const cuuint32_t bd[4] = {64, 32, 2, 2};
        make_map(fn, &tmWo, d_in[3], 4, gd, gs, bd, CU_TENSOR_MAP_SWIZZLE_128B);
    }
    make_2d(fn, &tmO, o_ptr, S_, D_, 128, 64, CU_TENSOR_MAP_SWIZZLE_128B);
    make_2d(fn, &tmOs, o_ptr, S_, D_, 128, 32, CU_TENSOR_MAP_SWIZZLE_NONE);
    make_2d(fn, &tmX2, d_in[0], S_, D_, 128, 64, CU_TENSOR_MAP_SWIZZLE_128B);
    Params P;
    P.x = (const __nv_bfloat16*)d_in[0];
    P.wr = (const __nv_bfloat16*)d_in[5];
    P.wqkv = (const __nv_bfloat16*)d_in[1];
    P.wg = (const __nv_bfloat16*)d_in[6];
    P.wu = (const __nv_bfloat16*)d_in[7];
    P.wd = (const __nv_bfloat16*)d_in[8];
    P.wo = (const __nv_bfloat16*)d_in[3];
    P.out = (__nv_bfloat16*)d_out;
    P.scr = (Scratch*)scr_ptr;
    P.tl = (unsigned long long*)tl_ptr;
    cudaLaunchConfig_t cfg = {};
    cfg.gridDim = dim3(NCTA); cfg.blockDim = dim3(NTHREADS); cfg.dynamicSmemBytes = SM_TOTAL; cfg.stream = cudaStreamPerThread;
    cudaLaunchAttribute at[1];
    at[0].id = cudaLaunchAttributeCooperative; at[0].val.cooperative = 1;
    cfg.attrs = at; cfg.numAttrs = 1;
    cudaLaunchKernelEx(&cfg, fused_kernel, P, tmX, tmW, tmX2, tmS, tmPhi, tmWo, tmO, tmOs);
}
```

```cpp
#include <cuda_runtime.h>
#include <cuda_bf16.h>
#include <cuda.h>
#include <stdint.h>

namespace {

constexpr int S_ = 2048, D_ = 1024, F_ = 3584;
constexpr int NCTA = 128, NTHREADS = 384;
#define OREL 2
#define OSTAG 12
#define OARR 3
#define NC0 3
#define NC2 4
#define NG0 12
#define NG1 12
#define GSPLIT 0
#define GSPLIT2 2
#define GST 3
#define SARR 3
#define PFENCE 1
#define JWO 10

constexpr int STAGE = 57344;
constexpr int SM_PHI = 0;
constexpr int SM_V = 131072;
constexpr int SM_AX = 172032;
constexpr int SM_BX = 176128;
constexpr int SM_SP = 172032;
constexpr int SM_FB = 180224;
constexpr int SM_OS = 196608;
constexpr int SM_XS = 221184;
constexpr int SM_KVOP = 172032;
constexpr int SM_MD = 223232;
constexpr int SM_RS = 224256;
constexpr int SM_Y = 225280;
constexpr int SM_GU = 225536;
constexpr int SM_MISC = 226688;
constexpr int SM_H = 179200;
constexpr int SM_BARS = 226816;
constexpr int SM_WPHI = 227840;
constexpr int SM_TOTAL = 232448;

constexpr int B_FULL = 0, B_EMPTY = 3, B_OF = 6, B_SD = 22, B_O = 33, B_PHI = 35, B_T = 37, B_WPHI = 38, B_Y = 39, B_KV = 40, B_LN = 42, B_S1 = 43, B_FF = 44, B_X = 54, B_C1 = 55, B_DN = 56, B_XS = 58, B_COUNT = 59, B_XR = 59, B_OS = 60, B_OW = 62;
constexpr int NB_KV = 1, NB_FFN = 2, NB_AUX = 3, NB_LEAD = 4, NB_STAG = 5;
__device__ __forceinline__ int o_slot(int i) { const int r = i % 5; return r == 4 ? 10 : r; }
__device__ __forceinline__ int wo_slot(int i) { const int r = i % 7; return r == 0 ? 11 : r < 4 ? 3 + r : r == 4 ? 8 : r == 5 ? 7 : 9; }

struct __align__(128) Acc {
    float4 cs[48 * 8 * 3];
    float4 y[4 * 4 * 3 * 32];
};
constexpr int ACC_VEC_PER_CTA = (int)(sizeof(Acc) / 16 / NCTA);
static_assert(sizeof(Acc) == ACC_VEC_PER_CTA * 16 * NCTA && ACC_VEC_PER_CTA <= 32, "");
struct __align__(128) Scratch {
    Acc acc[2];
    uint4 kv[32 * 4 * 3 * 32];
    unsigned cnt_o[8 * 128];
    uint2 rows[S_];
    uint4 best[NCTA];
    unsigned epoch;
};
__device__ Scratch g_scr;
__device__ __align__(1024) __nv_bfloat16 g_o[S_ * D_];

#define TL(e) do {} while (0)
#define TLP(c, e) do {} while (0)
#define TLG(c, e) do {} while (0)
#define TL_DUMP() do {} while (0)

struct SideMaps { CUtensorMap wc, wg, wu, wd8; };
struct Params {
    const __nv_bfloat16* x;
    const __nv_bfloat16* wr;
    const __nv_bfloat16* wqkv;
    const __nv_bfloat16* wg;
    const __nv_bfloat16* wu;
    const __nv_bfloat16* wd;
    const __nv_bfloat16* wo;
    __nv_bfloat16* out;
        Scratch* scr;
    unsigned long long* tl;
};

__device__ __forceinline__ bool elect_one() {
    uint32_t p; asm volatile("{\n.reg .pred q;\nelect.sync _|q, 0xffffffff;\nselp.u32 %0, 1, 0, q;\n}" : "=r"(p)); return p;
}
__device__ __forceinline__ uint32_t smem_u32(const void* p) { return (uint32_t)__cvta_generic_to_shared(p); }
__device__ __forceinline__ void mbar_init(uint32_t bar, uint32_t cnt) { asm volatile("mbarrier.init.shared::cta.b64 [%0], %1;" :: "r"(bar), "r"(cnt) : "memory"); }
__device__ __forceinline__ void mbar_expect_tx(uint32_t bar, uint32_t bytes) { asm volatile("mbarrier.arrive.expect_tx.shared::cta.b64 _, [%0], %1;" :: "r"(bar), "r"(bytes) : "memory"); }
__device__ __forceinline__ void mbar_arrive_if(bool p, uint32_t bar) {
    asm volatile("{\n.reg .pred q;\nsetp.ne.b32 q, %1, 0;\n@q mbarrier.arrive.shared::cta.b64 _, [%0];\n}" :: "r"(bar), "r"((int)p) : "memory");
}
__device__ __forceinline__ void mbar_wait(uint32_t bar, uint32_t parity) {
    asm volatile("{\n.reg .pred p;\n.reg .u32 n;\nmov.u32 n, 0;\n"
                 "WAIT_LOOP:\nmbarrier.try_wait.parity.shared::cta.b64 p, [%0], %1;\n@p bra WAIT_DONE;\n"
                 "add.u32 n, n, 1;\nsetp.lt.u32 p, n, 0x40000;\n@p bra WAIT_LOOP;\nWAIT_DONE:\n}" :: "r"(bar), "r"(parity) : "memory");
}
__device__ __forceinline__ void tma_2d(uint32_t dst, const CUtensorMap* tm, uint32_t bar, int c0, int c1) {
    asm volatile("cp.async.bulk.tensor.2d.shared::cluster.global.mbarrier::complete_tx::bytes [%0], [%1, {%3, %4}], [%2];"
        :: "r"(dst), "l"(tm), "r"(bar), "r"(c0), "r"(c1) : "memory");
}
__device__ __forceinline__ void tma_3d(uint32_t dst, const CUtensorMap* tm, uint32_t bar, int c0, int c1, int c2) {
    asm volatile("cp.async.bulk.tensor.3d.shared::cluster.global.mbarrier::complete_tx::bytes [%0], [%1, {%3, %4, %5}], [%2];"
        :: "r"(dst), "l"(tm), "r"(bar), "r"(c0), "r"(c1), "r"(c2) : "memory");
}
__device__ __forceinline__ void tma_4d(uint32_t dst, const CUtensorMap* tm, uint32_t bar, int c0, int c1, int c2, int c3) {
    asm volatile("cp.async.bulk.tensor.4d.shared::cluster.global.mbarrier::complete_tx::bytes [%0], [%1, {%3, %4, %5, %6}], [%2];"
        :: "r"(dst), "l"(tm), "r"(bar), "r"(c0), "r"(c1), "r"(c2), "r"(c3) : "memory");
}
__device__ __forceinline__ void prefetch_l2(const void* p, uint32_t bytes) { asm volatile("cp.async.bulk.prefetch.L2.global [%0], %1;" :: "l"(p), "r"(bytes) : "memory"); }
__device__ __forceinline__ void wgmma_fence() { asm volatile("wgmma.fence.sync.aligned;" ::: "memory"); }
__device__ __forceinline__ void wgmma_commit() { asm volatile("wgmma.commit_group.sync.aligned;" ::: "memory"); }
template <int N> __device__ __forceinline__ void wgmma_wait() { asm volatile("wgmma.wait_group.sync.aligned %0;" :: "n"(N) : "memory"); }
template <int N> __device__ __forceinline__ void fence_regs(float (&a)[N]) {
#pragma unroll
    for (int i = 0; i < N; i++) asm volatile("" : "+f"(a[i]) :: "memory");
}
template <int N> __device__ __forceinline__ void fence_regs(uint32_t (&a)[N]) {
#pragma unroll
    for (int i = 0; i < N; i++) asm volatile("" : "+r"(a[i]) :: "memory");
}
__device__ __forceinline__ uint64_t desc_from(uint32_t lo, uint32_t hi) { uint64_t d; asm("mov.b64 %0, {%1, %2};" : "=l"(d) : "r"(lo), "r"(hi)); return d; }
__device__ __forceinline__ uint32_t dlo(uint32_t addr, uint32_t lbo) { return ((addr & 0x3FFFF) >> 4) | ((lbo >> 4) << 16); }
__device__ __forceinline__ void nb_sync(int id, int cnt) { asm volatile("bar.sync %0, %1;" :: "r"(id), "r"(cnt) : "memory"); }
__device__ __forceinline__ void nb_arrive(int id, int cnt) { asm volatile("bar.arrive %0, %1;" :: "r"(id), "r"(cnt) : "memory"); }
__device__ __forceinline__ void fence_async_smem() { asm volatile("fence.proxy.async.shared::cta;" ::: "memory"); }
__device__ __forceinline__ void red_v4(float4* p, float a, float b, float c, float d) {
    asm volatile("red.relaxed.gpu.global.add.v4.f32 [%0], {%1, %2, %3, %4};" :: "l"(p), "f"(a), "f"(b), "f"(c), "f"(d) : "memory");
}
__device__ __forceinline__ float4 ld_gpu(const float4* p) {
    float4 v; asm volatile("ld.relaxed.gpu.global.v4.f32 {%0, %1, %2, %3}, [%4];" : "=f"(v.x), "=f"(v.y), "=f"(v.z), "=f"(v.w) : "l"(p) : "memory"); return v;
}
__device__ __forceinline__ uint4 ld_gpu(const uint4* p) {
    uint4 v; asm volatile("ld.relaxed.gpu.global.v4.u32 {%0, %1, %2, %3}, [%4];" : "=r"(v.x), "=r"(v.y), "=r"(v.z), "=r"(v.w) : "l"(p) : "memory"); return v;
}
__device__ __forceinline__ uint32_t pack_bf16(float lo, float hi) { uint32_t r; asm("cvt.rn.bf16x2.f32 %0, %1, %2;" : "=r"(r) : "f"(hi), "f"(lo)); return r; }
__device__ __forceinline__ uint32_t pack_f16(float lo, float hi) { uint32_t r; asm("cvt.rn.f16x2.f32 %0, %1, %2;" : "=r"(r) : "f"(hi), "f"(lo)); return r; }
__device__ __forceinline__ float2 unpack_f16(uint32_t v) { float2 r; asm("{\n.reg .f16 l, h;\nmov.b32 {l, h}, %2;\ncvt.f32.f16 %0, l;\ncvt.f32.f16 %1, h;\n}" : "=f"(r.x), "=f"(r.y) : "r"(v)); return r; }
__device__ __forceinline__ float bf_lo(uint32_t v) { return __uint_as_float(v << 16); }
__device__ __forceinline__ float bf_hi(uint32_t v) { return __uint_as_float(v & 0xFFFF0000u); }
__device__ __forceinline__ float round_bf16(float v) { return bf_lo(pack_bf16(v, 0.f)); }
__device__ __forceinline__ float ex2(float v) { float r; asm("ex2.approx.ftz.f32 %0, %1;" : "=f"(r) : "f"(v)); return r; }
__device__ __forceinline__ float rcp(float v) { float r; asm("rcp.approx.ftz.f32 %0, %1;" : "=f"(r) : "f"(v)); return r; }
__device__ __forceinline__ float sqrt_a(float v) { float r; asm("sqrt.approx.f32 %0, %1;" : "=f"(r) : "f"(v)); return r; }
__device__ __forceinline__ void stsm(uint32_t addr, uint32_t r0, uint32_t r1, uint32_t r2, uint32_t r3) {
    asm volatile("stmatrix.sync.aligned.m8n8.x4.shared.b16 [%0], {%1, %2, %3, %4};" :: "r"(addr), "r"(r0), "r"(r1), "r"(r2), "r"(r3) : "memory");
}
__device__ __forceinline__ void stsm_t(uint32_t addr, uint32_t r0, uint32_t r1, uint32_t r2, uint32_t r3) {
    asm volatile("stmatrix.sync.aligned.m8n8.x4.trans.shared.b16 [%0], {%1, %2, %3, %4};" :: "r"(addr), "r"(r0), "r"(r1), "r"(r2), "r"(r3) : "memory");
}
__device__ __forceinline__ uint4 lds128(uint32_t addr) {
    uint4 v; asm volatile("ld.shared.v4.u32 {%0, %1, %2, %3}, [%4];" : "=r"(v.x), "=r"(v.y), "=r"(v.z), "=r"(v.w) : "r"(addr) : "memory"); return v;
}
__device__ __forceinline__ void sts128(uint32_t addr, uint32_t a, uint32_t b, uint32_t c, uint32_t d) {
    asm volatile("st.shared.v4.u32 [%0], {%1, %2, %3, %4};" :: "r"(addr), "r"(a), "r"(b), "r"(c), "r"(d) : "memory");
}
__device__ __forceinline__ void sts64(uint32_t addr, uint32_t a, uint32_t b) { asm volatile("st.shared.v2.u32 [%0], {%1, %2};" :: "r"(addr), "r"(a), "r"(b) : "memory"); }
__device__ __forceinline__ uint32_t lds32(uint32_t addr) { uint32_t v; asm volatile("ld.shared.u32 %0, [%1];" : "=r"(v) : "r"(addr) : "memory"); return v; }
__device__ __forceinline__ float ldsf(uint32_t addr) { return __uint_as_float(lds32(addr)); }
__device__ __forceinline__ void sts32(uint32_t addr, uint32_t v) { asm volatile("st.shared.u32 [%0], %1;" :: "r"(addr), "r"(v) : "memory"); }
__device__ __forceinline__ uint32_t hmul2(uint32_t a, uint32_t b) { uint32_t r; asm("mul.rn.bf16x2 %0, %1, %2;" : "=r"(r) : "r"(a), "r"(b)); return r; }
__device__ __forceinline__ uint32_t hadd2(uint32_t a, uint32_t b) { uint32_t r; asm("add.rn.bf16x2 %0, %1, %2;" : "=r"(r) : "r"(a), "r"(b)); return r; }
__device__ __forceinline__ uint32_t hsub2(uint32_t a, uint32_t b) { uint32_t r; asm("sub.rn.bf16x2 %0, %1, %2;" : "=r"(r) : "r"(a), "r"(b)); return r; }

__device__ __forceinline__ void wgmma_ss_n192_tb(float (&d)[96], uint64_t da, uint64_t db, int scale_d) {
    asm volatile(
        "{\n.reg .pred p;\nsetp.ne.b32 p, %98, 0;\n"
        "wgmma.mma_async.sync.aligned.m64n192k16.f32.bf16.bf16 "
        "{%0, %1, %2, %3, %4, %5, %6, %7, %8, %9, %10, %11, %12, %13, %14, %15, %16, %17, %18, %19, %20, %21, %22, %23, %24, %25, %26, %27, %28, %29, %30, %31, %32, %33, %34, %35, %36, %37, %38, %39, %40, %41, %42, %43, %44, %45, %46, %47, %48, %49, %50, %51, %52, %53, %54, %55, %56, %57, %58, %59, %60, %61, %62, %63, %64, %65, %66, %67, %68, %69, %70, %71, %72, %73, %74, %75, %76, %77, %78, %79, %80, %81, %82, %83, %84, %85, %86, %87, %88, %89, %90, %91, %92, %93, %94, %95}, %96, %97, p, 1, 1, 0, 1;\n}\n"
        : "+f"(d[0]), "+f"(d[1]), "+f"(d[2]), "+f"(d[3]), "+f"(d[4]), "+f"(d[5]), "+f"(d[6]), "+f"(d[7]), "+f"(d[8]), "+f"(d[9]), "+f"(d[10]), "+f"(d[11]), "+f"(d[12]), "+f"(d[13]), "+f"(d[14]), "+f"(d[15]), "+f"(d[16]), "+f"(d[17]), "+f"(d[18]), "+f"(d[19]), "+f"(d[20]), "+f"(d[21]), "+f"(d[22]), "+f"(d[23]), "+f"(d[24]), "+f"(d[25]), "+f"(d[26]), "+f"(d[27]), "+f"(d[28]), "+f"(d[29]), "+f"(d[30]), "+f"(d[31]), "+f"(d[32]), "+f"(d[33]), "+f"(d[34]), "+f"(d[35]), "+f"(d[36]), "+f"(d[37]), "+f"(d[38]), "+f"(d[39]), "+f"(d[40]), "+f"(d[41]), "+f"(d[42]), "+f"(d[43]), "+f"(d[44]), "+f"(d[45]), "+f"(d[46]), "+f"(d[47]), "+f"(d[48]), "+f"(d[49]), "+f"(d[50]), "+f"(d[51]), "+f"(d[52]), "+f"(d[53]), "+f"(d[54]), "+f"(d[55]), "+f"(d[56]), "+f"(d[57]), "+f"(d[58]), "+f"(d[59]), "+f"(d[60]), "+f"(d[61]), "+f"(d[62]), "+f"(d[63]), "+f"(d[64]), "+f"(d[65]), "+f"(d[66]), "+f"(d[67]), "+f"(d[68]), "+f"(d[69]), "+f"(d[70]), "+f"(d[71]), "+f"(d[72]), "+f"(d[73]), "+f"(d[74]), "+f"(d[75]), "+f"(d[76]), "+f"(d[77]), "+f"(d[78]), "+f"(d[79]), "+f"(d[80]), "+f"(d[81]), "+f"(d[82]), "+f"(d[83]), "+f"(d[84]), "+f"(d[85]), "+f"(d[86]), "+f"(d[87]), "+f"(d[88]), "+f"(d[89]), "+f"(d[90]), "+f"(d[91]), "+f"(d[92]), "+f"(d[93]), "+f"(d[94]), "+f"(d[95])
        : "l"(da), "l"(db), "r"(scale_d));
}
__device__ __forceinline__ void wgmma_ss_n128_tb(float (&d)[64], uint64_t da, uint64_t db, int scale_d) {
    asm volatile(
        "{\n.reg .pred p;\nsetp.ne.b32 p, %66, 0;\n"
        "wgmma.mma_async.sync.aligned.m64n128k16.f32.bf16.bf16 "
        "{%0, %1, %2, %3, %4, %5, %6, %7, %8, %9, %10, %11, %12, %13, %14, %15, %16, %17, %18, %19, %20, %21, %22, %23, %24, %25, %26, %27, %28, %29, %30, %31, %32, %33, %34, %35, %36, %37, %38, %39, %40, %41, %42, %43, %44, %45, %46, %47, %48, %49, %50, %51, %52, %53, %54, %55, %56, %57, %58, %59, %60, %61, %62, %63}, %64, %65, p, 1, 1, 0, 1;\n}\n"
        : "+f"(d[0]), "+f"(d[1]), "+f"(d[2]), "+f"(d[3]), "+f"(d[4]), "+f"(d[5]), "+f"(d[6]), "+f"(d[7]), "+f"(d[8]), "+f"(d[9]), "+f"(d[10]), "+f"(d[11]), "+f"(d[12]), "+f"(d[13]), "+f"(d[14]), "+f"(d[15]), "+f"(d[16]), "+f"(d[17]), "+f"(d[18]), "+f"(d[19]), "+f"(d[20]), "+f"(d[21]), "+f"(d[22]), "+f"(d[23]), "+f"(d[24]), "+f"(d[25]), "+f"(d[26]), "+f"(d[27]), "+f"(d[28]), "+f"(d[29]), "+f"(d[30]), "+f"(d[31]), "+f"(d[32]), "+f"(d[33]), "+f"(d[34]), "+f"(d[35]), "+f"(d[36]), "+f"(d[37]), "+f"(d[38]), "+f"(d[39]), "+f"(d[40]), "+f"(d[41]), "+f"(d[42]), "+f"(d[43]), "+f"(d[44]), "+f"(d[45]), "+f"(d[46]), "+f"(d[47]), "+f"(d[48]), "+f"(d[49]), "+f"(d[50]), "+f"(d[51]), "+f"(d[52]), "+f"(d[53]), "+f"(d[54]), "+f"(d[55]), "+f"(d[56]), "+f"(d[57]), "+f"(d[58]), "+f"(d[59]), "+f"(d[60]), "+f"(d[61]), "+f"(d[62]), "+f"(d[63])
        : "l"(da), "l"(db), "r"(scale_d));
}
__device__ __forceinline__ void wgmma_ss_n40(float (&d)[20], uint64_t da, uint64_t db, int scale_d) {
    asm volatile(
        "{\n.reg .pred p;\nsetp.ne.b32 p, %22, 0;\n"
        "wgmma.mma_async.sync.aligned.m64n40k16.f32.bf16.bf16 "
        "{%0, %1, %2, %3, %4, %5, %6, %7, %8, %9, %10, %11, %12, %13, %14, %15, %16, %17, %18, %19}, %20, %21, p, 1, 1, 0, 0;\n}\n"
        : "+f"(d[0]), "+f"(d[1]), "+f"(d[2]), "+f"(d[3]), "+f"(d[4]), "+f"(d[5]), "+f"(d[6]), "+f"(d[7]), "+f"(d[8]), "+f"(d[9]), "+f"(d[10]), "+f"(d[11]), "+f"(d[12]), "+f"(d[13]), "+f"(d[14]), "+f"(d[15]), "+f"(d[16]), "+f"(d[17]), "+f"(d[18]), "+f"(d[19])
        : "l"(da), "l"(db), "r"(scale_d));
}
__device__ __forceinline__ void wgmma_ss_n8_ta(float (&d)[4], uint64_t da, uint64_t db, int scale_d) {
    asm volatile(
        "{\n.reg .pred p;\nsetp.ne.b32 p, %6, 0;\n"
        "wgmma.mma_async.sync.aligned.m64n8k16.f32.bf16.bf16 "
        "{%0, %1, %2, %3}, %4, %5, p, 1, 1, 1, 0;\n}\n"
        : "+f"(d[0]), "+f"(d[1]), "+f"(d[2]), "+f"(d[3])
        : "l"(da), "l"(db), "r"(scale_d));
}
__device__ __forceinline__ void wgmma_rs_n32_tb(float (&d)[16], uint32_t a0, uint32_t a1, uint32_t a2, uint32_t a3, uint64_t db, int scale_d) {
    asm volatile(
        "{\n.reg .pred p;\nsetp.ne.b32 p, %21, 0;\n"
        "wgmma.mma_async.sync.aligned.m64n32k16.f32.bf16.bf16 "
        "{%0, %1, %2, %3, %4, %5, %6, %7, %8, %9, %10, %11, %12, %13, %14, %15}, {%16, %17, %18, %19}, %20, p, 1, 1, 1;\n}\n"
        : "+f"(d[0]), "+f"(d[1]), "+f"(d[2]), "+f"(d[3]), "+f"(d[4]), "+f"(d[5]), "+f"(d[6]), "+f"(d[7]), "+f"(d[8]), "+f"(d[9]), "+f"(d[10]), "+f"(d[11]), "+f"(d[12]), "+f"(d[13]), "+f"(d[14]), "+f"(d[15])
        : "r"(a0), "r"(a1), "r"(a2), "r"(a3), "l"(db), "r"(scale_d));
}
__device__ __forceinline__ void wgmma_rs_n40_tb(float (&d)[20], uint32_t a0, uint32_t a1, uint32_t a2, uint32_t a3, uint64_t db, int scale_d) {
    asm volatile(
        "{\n.reg .pred p;\nsetp.ne.b32 p, %25, 0;\n"
        "wgmma.mma_async.sync.aligned.m64n40k16.f32.bf16.bf16 "
        "{%0, %1, %2, %3, %4, %5, %6, %7, %8, %9, %10, %11, %12, %13, %14, %15, %16, %17, %18, %19}, {%20, %21, %22, %23}, %24, p, 1, 1, 1;\n}\n"
        : "+f"(d[0]), "+f"(d[1]), "+f"(d[2]), "+f"(d[3]), "+f"(d[4]), "+f"(d[5]), "+f"(d[6]), "+f"(d[7]), "+f"(d[8]), "+f"(d[9]), "+f"(d[10]), "+f"(d[11]), "+f"(d[12]), "+f"(d[13]), "+f"(d[14]), "+f"(d[15]), "+f"(d[16]), "+f"(d[17]), "+f"(d[18]), "+f"(d[19])
        : "r"(a0), "r"(a1), "r"(a2), "r"(a3), "l"(db), "r"(scale_d));
}

constexpr float LOG2E = 1.4426950408889634f;
constexpr uint32_t DH128 = (1024u >> 4) | (1u << 30);

__device__ __forceinline__ float silu_f(float v) { return v * rcp(1.0f + ex2(-v * LOG2E)); }
__device__ __forceinline__ float silu_t(float v) { const float h = 0.5f * v; float th; asm("tanh.approx.f32 %0, %1;" : "=f"(th) : "f"(h)); return fmaf(h, th, h); }
__device__ __forceinline__ uint32_t ln_pair(uint32_t xv, uint32_t m2, float rs) { const uint32_t a = hsub2(xv, m2); return pack_bf16(bf_lo(a) * rs, bf_hi(a) * rs); }
__device__ __forceinline__ uint32_t silu_pair(uint32_t v) { return pack_bf16(silu_t(bf_lo(v)), silu_t(bf_hi(v))); }
__device__ __forceinline__ uint32_t gate_pair(uint32_t v, float hr, float hm) {
    const float a = fmaf(bf_lo(v), hr, hm), b = fmaf(bf_hi(v), hr, hm);
    float ta, tb;
    asm("tanh.approx.f32 %0, %1;" : "=f"(ta) : "f"(a)); asm("tanh.approx.f32 %0, %1;" : "=f"(tb) : "f"(b));
    return pack_bf16(fmaf(a, ta, a), fmaf(b, tb, b));
}
__device__ __forceinline__ void gate_item(uint4& v, uint32_t sb, int row) {
    const float hr = 0.5f * ldsf(sb + SM_RS + row * 4), hm = -bf_lo(lds32(sb + SM_MD + row * 4)) * hr;
    v.x = gate_pair(v.x, hr, hm); v.y = gate_pair(v.y, hr, hm); v.z = gate_pair(v.z, hr, hm); v.w = gate_pair(v.w, hr, hm);
    asm volatile("" : "+r"(v.x), "+r"(v.y), "+r"(v.z), "+r"(v.w) :: "memory");
}
__device__ __forceinline__ uint32_t hfma2(uint32_t a, uint32_t b, uint32_t c) { uint32_t r; asm("fma.rn.bf16x2 %0, %1, %2, %3;" : "=r"(r) : "r"(a), "r"(b), "r"(c)); return r; }
__device__ __forceinline__ uint32_t dup_lo(uint32_t v) { uint32_t r; asm("{\n.reg .b16 l, h;\nmov.b32 {l, h}, %1;\nmov.b32 %0, {l, l};\n}" : "=r"(r) : "r"(v)); return r; }
__device__ __forceinline__ uint32_t dup_hi(uint32_t v) { uint32_t r; asm("{\n.reg .b16 l, h;\nmov.b32 {l, h}, %1;\nmov.b32 %0, {h, h};\n}" : "=r"(r) : "r"(v)); return r; }
template <bool SQ> __device__ __forceinline__ void colsum8(float (&a)[8], float& sq, const uint4 (&v)[8]) {
    uint32_t q = 0;
#pragma unroll
    for (int i = 0; i < 8; i++) {
        a[0] += bf_lo(v[i].x); a[1] += bf_hi(v[i].x); a[2] += bf_lo(v[i].y); a[3] += bf_hi(v[i].y);
        a[4] += bf_lo(v[i].z); a[5] += bf_hi(v[i].z); a[6] += bf_lo(v[i].w); a[7] += bf_hi(v[i].w);
        if (SQ) q = hfma2(v[i].x, v[i].x, hfma2(v[i].y, v[i].y, hfma2(v[i].z, v[i].z, hfma2(v[i].w, v[i].w, q))));
    }
    if (SQ) sq += bf_lo(q) + bf_hi(q);
}
__device__ __forceinline__ void hfma8(uint4& h, uint32_t w, const uint4& v) { h.x = hfma2(v.x, w, h.x); h.y = hfma2(v.y, w, h.y); h.z = hfma2(v.z, w, h.z); h.w = hfma2(v.w, w, h.w); }
template <int ST, class F>
__device__ __forceinline__ void gemv_run(float (&a)[8], int cnt, int b, uint32_t ph, uint32_t lo, uint32_t wa, uint32_t ws, uint32_t bar0, uint32_t pin, F done) {
    uint32_t rdy = 0;
#pragma unroll 1
    for (int m = 0; m < cnt; m++) {
        if (!rdy) mbar_wait(bar0 + b * 8, ph);
        uint4 A[8];
        const uint4 w = lds128(wa);
#pragma unroll
        for (int i = 0; i < 8; i++) A[i] = lds128(lo + b * 4096 + i * ST);
        const int bc = b;
        if (++b == 3) { b = 0; ph ^= 1; }
        asm volatile("{\n.reg .pred p;\nmbarrier.test_wait.parity.shared::cta.b64 p, [%1], %2;\nselp.u32 %0, 1, 0, p;\n}" : "=r"(rdy) : "r"(bar0 + b * 8), "r"(ph) : "memory");
        sts32(pin, 0u);
        wa += ws;
        uint4 h = make_uint4(0, 0, 0, 0);
        hfma8(h, dup_lo(w.x), A[0]); hfma8(h, dup_hi(w.x), A[1]); hfma8(h, dup_lo(w.y), A[2]); hfma8(h, dup_hi(w.y), A[3]);
        hfma8(h, dup_lo(w.z), A[4]); hfma8(h, dup_hi(w.z), A[5]); hfma8(h, dup_lo(w.w), A[6]); hfma8(h, dup_hi(w.w), A[7]);
        a[0] += bf_lo(h.x); a[1] += bf_hi(h.x); a[2] += bf_lo(h.y); a[3] += bf_hi(h.y);
        a[4] += bf_lo(h.z); a[5] += bf_hi(h.z); a[6] += bf_lo(h.w); a[7] += bf_hi(h.w);
        fence_regs(a);
        done(m, bc);
    }
}
template <int OFF> __device__ __forceinline__ void pack_head(const float (&acc)[96], uint32_t (&f)[8]) {
#pragma unroll
    for (int i = 0; i < 8; i++) f[i] = pack_bf16(acc[OFF + 2 * i], acc[OFF + 2 * i + 1]);
}
__device__ __forceinline__ void feat_mma(float (&p)[16], const uint32_t (&f)[8], uint32_t wlo) {
    constexpr uint32_t DH = (512u >> 4) | (2u << 30);
    wgmma_rs_n32_tb(p, f[0], f[1], f[2], f[3], desc_from(wlo, DH), 0);
    wgmma_rs_n32_tb(p, f[4], f[5], f[6], f[7], desc_from(wlo + 64, DH), 1);
}
template <int S> __device__ __forceinline__ void row_ext(const float (&p)[16], float& a, float& b) {
    auto op = [](float x, float y) { return S > 0 ? fmaxf(x, y) : fminf(x, y); };
    a = op(op(op(p[0], p[1]), op(p[4], p[5])), op(op(p[8], p[9]), op(p[12], p[13])));
    b = op(op(op(p[2], p[3]), op(p[6], p[7])), op(op(p[10], p[11]), op(p[14], p[15])));
#pragma unroll
    for (int o = 1; o <= 2; o <<= 1) { a = op(a, __shfl_xor_sync(0xffffffffu, a, o)); b = op(b, __shfl_xor_sync(0xffffffffu, b, o)); }
}
__device__ __forceinline__ void dual_exp(const float (&p)[16], float scA, float scB, uint32_t (&pos)[8], uint32_t (&neg)[8], uint32_t& chk) {
#pragma unroll
    for (int j = 0; j < 8; j += 2) {
        const float a0 = ex2(p[2 * j] * scA), a1 = ex2(p[2 * j + 1] * scA);
        const float b0 = ex2(p[2 * j + 2] * scB), b1 = ex2(p[2 * j + 3] * scB);
        const float pa = a0 * a1, pb = b0 * b1, R = rcp(pa * pb);
        const uint32_t r = pack_bf16(R * pb, R * pa);
        pos[j] = pack_bf16(a0, a1); pos[j + 1] = pack_bf16(b0, b1);
        neg[j] = hmul2(pos[j], dup_lo(r)); neg[j + 1] = hmul2(pos[j + 1], dup_hi(r));
        chk = hadd2(chk, hadd2(hadd2(pos[j], neg[j]), hadd2(pos[j + 1], neg[j + 1])));
    }
}
template <int S> __device__ __forceinline__ void exact_exp(const float (&p)[16], float scA, float scB, uint32_t (&o)[8]) {
    float mA, mB;
    row_ext<S>(p, mA, mB);
#pragma unroll
    for (int j = 0; j < 8; j++) {
        const float sc = S * ((j & 1) ? scB : scA), m = (j & 1) ? mB : mA;
        const float u = ex2((p[2 * j] - m) * sc), v = ex2((p[2 * j + 1] - m) * sc);
        o[j] = S > 0 ? pack_bf16(u, v) : pack_bf16(v, u);
    }
}
__device__ __forceinline__ void features(const float (&p0)[16], const float (&p1)[16], const float (&rs)[4],
                                         uint32_t (&pa)[8], uint32_t (&na)[8], uint32_t (&pb)[8], uint32_t (&nb)[8]) {
    uint32_t chk = 0;
    dual_exp(p0, rs[0] * LOG2E, rs[1] * LOG2E, pa, na, chk);
    dual_exp(p1, rs[2] * LOG2E, rs[3] * LOG2E, pb, nb, chk);
    if (__builtin_expect(!__all_sync(0xffffffffu, bf_lo(chk) + bf_hi(chk) < 1.0e9f), 0)) {
        exact_exp<1>(p0, rs[0] * LOG2E, rs[1] * LOG2E, pa); exact_exp<-1>(p0, rs[0] * LOG2E, rs[1] * LOG2E, na);
        exact_exp<1>(p1, rs[2] * LOG2E, rs[3] * LOG2E, pb); exact_exp<-1>(p1, rs[2] * LOG2E, rs[3] * LOG2E, nb);
    }
}
__device__ __forceinline__ float quad_sum(float v) { v += __shfl_xor_sync(0xffffffffu, v, 1); return v + __shfl_xor_sync(0xffffffffu, v, 2); }
__device__ __forceinline__ float key_block(const float (&p)[16], float rsA, float rsB, uint32_t d0, uint32_t d1, uint32_t off) {
    float r[8], sp[2], sn[2];
    uint32_t pos[8], neg[8];
    const float scA = rsA * LOG2E, scB = rsB * LOG2E;
#pragma unroll
    for (int j = 0; j < 8; j += 2) {
        const float a0 = ex2(p[2 * j] * scA), a1 = ex2(p[2 * j + 1] * scA);
        const float b0 = ex2(p[2 * j + 2] * scB), b1 = ex2(p[2 * j + 3] * scB);
        const float pa = a0 * a1, pb = b0 * b1, R = rcp(pa * pb), ta = a0 + a1, tb = b0 + b1;
        r[j] = R * pb; r[j + 1] = R * pa;
        if (j == 0) { sp[0] = ta; sp[1] = tb; sn[0] = r[0] * ta; sn[1] = r[1] * tb; }
        else { sp[0] += ta; sp[1] += tb; sn[0] = fmaf(r[j], ta, sn[0]); sn[1] = fmaf(r[j + 1], tb, sn[1]); }
        pos[j] = pack_bf16(a0, a1); pos[j + 1] = pack_bf16(b0, b1);
    }
    const float qa = quad_sum(sp[0]), qb = quad_sum(sp[1]), na = quad_sum(sn[0]), nb = quad_sum(sn[1]);
    const float iq = rcp(qa * qb), nA = rsA * rcp(na), nB = rsB * rcp(nb);
    const uint32_t fp = pack_bf16(rsA * qb * iq, rsB * qa * iq);
#pragma unroll
    for (int j = 0; j < 8; j += 2) {
        const uint32_t rn = pack_bf16(r[j] * nA, r[j + 1] * nB);
        neg[j] = hmul2(pos[j], dup_lo(rn)); neg[j + 1] = hmul2(pos[j + 1], dup_hi(rn));
        pos[j] = hmul2(pos[j], dup_lo(fp)); pos[j + 1] = hmul2(pos[j + 1], dup_hi(fp));
    }
    stsm_t(d0 + 4096, neg[0], neg[2], neg[4], neg[6]); stsm_t(d1 + 4096, neg[1], neg[3], neg[5], neg[7]);
    stsm_t(d0 + off, pos[0], pos[2], pos[4], pos[6]); stsm_t(d1 + off, pos[1], pos[3], pos[5], pos[7]);
    return (qa + qb) + (na + nb);
}
__device__ __forceinline__ void shift_max(float (&p)[16]) {
    float mA, mB;
    row_ext<1>(p, mA, mB);
#pragma unroll
    for (int j = 0; j < 16; j++) p[j] -= (j & 2) ? mB : mA;
}
__device__ __forceinline__ void key_head(float (&p0)[16], float (&p1)[16], const float (&rs)[4], uint32_t d0, uint32_t d1) {
    uint32_t st;
    asm volatile("mov.u32 %0, 0;" : "=r"(st));
    bool again;
#pragma unroll 1
    do {
        const uint32_t off = (st & 2u) << 11;
        const float chk = key_block(p0, rs[0], rs[1], d0, d1, off) + key_block(p1, rs[2], rs[3], d0 + 8192, d1 + 8192, off);
        again = st == 1u || (st == 0u && !__all_sync(0xffffffffu, chk < 1.0e9f));
        if (__builtin_expect(again, 0)) {
            if (st) {
#pragma unroll
                for (int j = 0; j < 16; j += 2) {
                    float t = p0[j]; p0[j] = -p0[j + 1]; p0[j + 1] = -t;
                    t = p1[j]; p1[j] = -p1[j + 1]; p1[j + 1] = -t;
                }
            }
            shift_max(p0); shift_max(p1);
            st++;
        }
        asm volatile("" ::: "memory");
    } while (again);
}
__device__ __forceinline__ void o_mma(float (&d)[20], float (&e)[20], const uint32_t (&pos)[8], const uint32_t (&neg)[8], uint32_t klo) {
    wgmma_rs_n40_tb(d, pos[0], pos[1], pos[2], pos[3], desc_from(klo, 1024u >> 4), 0);
    wgmma_rs_n40_tb(e, neg[0], neg[1], neg[2], neg[3], desc_from(klo + 32, 1024u >> 4), 0);
    wgmma_rs_n40_tb(d, pos[4], pos[5], pos[6], pos[7], desc_from(klo + 16, 1024u >> 4), 1);
    wgmma_rs_n40_tb(e, neg[4], neg[5], neg[6], neg[7], desc_from(klo + 48, 1024u >> 4), 1);
}
__device__ __forceinline__ void o_store(const float (&d)[20], const float (&e)[20], uint32_t dst) {
    const float iA = rcp(fmaf(d[16], e[17], fmaf(e[16], d[17], 1e-6f * d[17] * e[17])));
    const float iB = rcp(fmaf(d[18], e[19], fmaf(e[18], d[19], 1e-6f * d[19] * e[19])));
    const float pA = e[17] * iA, nA = d[17] * iA, pB = e[19] * iB, nB = d[19] * iB;
    uint32_t oa[4], ob[4];
#pragma unroll
    for (int j = 0; j < 4; j++) {
        oa[j] = pack_bf16(fmaf(d[j * 4], pA, e[j * 4] * nA), fmaf(d[j * 4 + 1], pA, e[j * 4 + 1] * nA));
        ob[j] = pack_bf16(fmaf(d[j * 4 + 2], pB, e[j * 4 + 2] * nB), fmaf(d[j * 4 + 3], pB, e[j * 4 + 3] * nB));
    }
    sts128(dst, oa[0], oa[1], oa[2], oa[3]);
    sts128(dst + 512, ob[0], ob[1], ob[2], ob[3]);
}

template <int N> __device__ __forceinline__ void kv_gather(uint4 (&v)[3 * N], const uint4* src, uint32_t dst, int lane, float us) {
    unsigned it = 0;
#pragma unroll 1
    while (++it < (1u << 20)) {
        bool ok = true;
#pragma unroll
        for (int j = 0; j < 3 * N; j++) ok = ok && (v[j].w >> 16) == 0x4800u;
        if (__all_sync(0xffffffffu, ok)) break;
#pragma unroll
        for (int j = 0; j < 3 * N; j++) v[j] = ld_gpu(src + j * 32);
    }
    dst += (lane >> 2) * 16;
    auto cv = [&](uint32_t w) { const float2 f = unpack_f16(w); return pack_bf16(f.x * us, f.y * us); };
#pragma unroll
    for (int n = 0; n < N; n++) {
        sts128(dst + (lane & 3) * 1024 + n * 256, cv(v[3 * n].x), cv(v[3 * n].y), cv(v[3 * n].z), cv(v[3 * n + 2].x));
        sts128(dst + (lane & 3) * 1024 + n * 256 + 128, cv(v[3 * n + 1].x), cv(v[3 * n + 1].y), cv(v[3 * n + 1].z), cv(v[3 * n + 2].y));
        sts32(dst + 4096 + n * 256 + (lane & 3) * 4, pack_bf16(unpack_f16(v[3 * n].w).x, 1.0f));
        sts32(dst + 4096 + n * 256 + 128 + (lane & 3) * 4, pack_bf16(unpack_f16(v[3 * n + 1].w).x, 1.0f));
    }
    fence_async_smem();
    __syncwarp();
}

__global__ void __launch_bounds__(NTHREADS, 1)
fused_kernel(const Params P, const __grid_constant__ CUtensorMap tmX, const __grid_constant__ CUtensorMap tmW, const __grid_constant__ CUtensorMap tmX2,
             const __grid_constant__ SideMaps tmS, const __grid_constant__ CUtensorMap tmPhi,
             const __grid_constant__ CUtensorMap tmWo, const __grid_constant__ CUtensorMap tmO, const __grid_constant__ CUtensorMap tmOs) {
    extern __shared__ __align__(1024) uint8_t smem_raw[];
    constexpr uint32_t sb = 1024;
    if (smem_u32(smem_raw) != sb) return;
    constexpr uint32_t bars = sb + SM_BARS;
    const int rb = blockIdx.x >> 4, hp = blockIdx.x & 15;
    TLP(threadIdx.x == 32, 0); TLG(threadIdx.x == 32, 48);
    auto load_stage = [&](int s, int ks) {
        mbar_expect_tx(bars + 8 * (B_FULL + s), STAGE);
        tma_2d(sb + s * STAGE, &tmX, bars + 8 * (B_FULL + s), ks * 64, rb * 256);
        tma_3d(sb + s * STAGE + 32768, &tmW, bars + 8 * (B_FULL + s), hp * 64, ks * 64, 0);
    };
    if (threadIdx.x < 256) {
        const uint32_t t = threadIdx.x, r = t >> 3, sw = ((t ^ r) & 7) * 16;
        const __nv_bfloat16* wp = P.wqkv + (size_t)r * 3 * D_ + hp * 64 + (t & 7) * 8;
        const __nv_bfloat16* xp = P.x + (size_t)(rb * 256 + (t >> 7) * 128 + (r & 15)) * D_ + (t & 7) * 8;
#pragma unroll
        for (int i = 0; i < 3; i++) asm volatile("cp.async.cg.shared.global [%0], [%1], 16;" :: "r"(sb + 32768 + i * 8192 + r * 128 + sw), "l"(wp + i * D_) : "memory");
#pragma unroll
        for (int i = 0; i < 8; i++) asm volatile("cp.async.cg.shared.global [%0], [%1], 16;" :: "r"(sb + (t >> 7) * 16384 + ((r & 15) + i * 16) * 128 + sw), "l"(xp + i * 16 * D_) : "memory");
        asm volatile("cp.async.commit_group;" ::: "memory");
#pragma unroll
        for (int i = 0; i < 3; i++) asm volatile("cp.async.cg.shared.global [%0], [%1], 16;" :: "r"(sb + 36864 + i * 8192 + r * 128 + sw), "l"(wp + 96 * D_ + i * D_) : "memory");
        asm volatile("cp.async.commit_group;" ::: "memory");
    }
    const int tid = threadIdx.x, warp = __shfl_sync(0xffffffffu, tid >> 5, 0), lane = tid & 31;
    const bool elect = lane == 0;

    if (warp >= 8) {
        const int aw = warp - 9;
        auto load_o = [&](int i) {
            mbar_expect_tx(bars + 8 * (B_OF + i), 16384);
            tma_2d(sb + o_slot(i) * 16384, &tmO, bars + 8 * (B_OF + i), i * 64, rb * 256 + (hp & 1) * 128);
        };
        auto load_wo = [&](int i) {
            mbar_expect_tx(bars + 8 * (B_OF + i), 16384);
            tma_4d(sb + wo_slot(i) * 16384, &tmWo, bars + 8 * (B_OF + i), 0, (i >> 3) * 32, (i & 7) * 2, hp & 14);
        };
        if (warp == 9) {
            if (elect_one()) {
#pragma unroll
                for (int i = B_OF; i < B_COUNT; i++)
                    mbar_init(bars + 8 * i, i < B_SD ? 2 : (i < B_WPHI ? 8 : ((i < B_KV || i >= B_FF || i == B_LN) ? 1 : 4)));
                mbar_init(bars + 8 * B_OS, 1); mbar_init(bars + 8 * B_OS + 8, 1);
#pragma unroll
                for (int i = 0; i < 4; i++) mbar_init(bars + 8 * (B_OW + i), 4);
                asm volatile("fence.mbarrier_init.release.cluster;" ::: "memory");
            }
        }
        if (warp == 8) {
            if (elect_one()) {
#pragma unroll
                for (int i = 0; i < 3; i++) { mbar_init(bars + 8 * (B_FULL + i), 1); mbar_init(bars + 8 * (B_EMPTY + i), 8); }
                mbar_init(bars + 8 * B_XR, 1);
                asm volatile("fence.mbarrier_init.release.cluster;" ::: "memory");
                asm volatile("mbarrier.arrive.shared::cta.b64 _, [%0];" :: "r"(bars + 8 * B_FULL) : "memory");
            }
            __syncwarp();
            nb_arrive(0, NTHREADS);
        } else {
            __syncwarp();
            nb_sync(0, NTHREADS);
        }
        asm volatile("setmaxnreg.dec.sync.aligned.u32 56;");
        if (warp == 8 && elect_one()) {
            load_stage(1, 1); load_stage(2, 2);
            mbar_expect_tx(bars + 8 * B_XR, 32768);
            asm volatile("cp.async.bulk.shared::cluster.global.mbarrier::complete_tx::bytes [%0], [%1], 32768, [%2];"
                         :: "r"(sb + SM_FB + 4096), "l"(P.x + (size_t)blockIdx.x * 16 * D_), "r"(bars + 8 * B_XR) : "memory");
        }
        __syncwarp();
        nb_sync(NB_KV, 128);
        unsigned epoch;
        asm volatile("ld.relaxed.gpu.global.u32 %0, [%1];" : "=r"(epoch) : "l"(&P.scr->epoch) : "memory");
        auto get_acc = [&]() { return &P.scr->acc[epoch & 1u]; };
        if (warp == 8) {
            epoch = __shfl_sync(0xffffffffu, epoch, 0);
            int s = 0, ph = 0;
#pragma unroll 1
            for (int j = 0; j < 15; j++) {
                mbar_wait(bars + 8 * (B_EMPTY + s), ph);
                if (elect_one()) {
                    if (j < 13) load_stage(s, j + 3);
                    if (j < 2) {
                        prefetch_l2(P.wqkv + (size_t)(256 + j * 384 + blockIdx.x * 3) * 3 * D_, 18432);
                    } else if (j < 10) {
                        if (j == 2) asm volatile("mbarrier.arrive.shared::cta.b64 _, [%0];" :: "r"(bars + 8 * B_FF) : "memory");
                        const size_t o = (size_t)((j - 2) * 128 + blockIdx.x) * F_;
                        prefetch_l2(P.wg + o, F_ * 2); prefetch_l2(P.wu + o, F_ * 2);
                    }
                    if (j == JWO) prefetch_l2(P.wo + (size_t)blockIdx.x * 8 * D_, 16384);
                    if (j == 12) {
                        asm volatile("prefetch.tensormap [%0];" :: "l"(&tmO) : "memory");
                        asm volatile("prefetch.tensormap [%0];" :: "l"(&tmOs) : "memory");
                        asm volatile("prefetch.tensormap [%0];" :: "l"(&tmS.wd8) : "memory");
                        asm volatile("prefetch.tensormap [%0];" :: "l"(&tmWo) : "memory");
                        mbar_expect_tx(bars + 8 * B_WPHI, 4096);
                        tma_2d(sb + SM_WPHI, &tmPhi, bars + 8 * B_WPHI, 0, hp * 64);
                    }
                    if (j >= 13) {
                        if (blockIdx.x >= 112) { if (j == 13) { load_wo(1); load_wo(2); } else { load_wo(3); load_wo(5); } }
                        else {
                            mbar_expect_tx(bars + 8 * (B_DN + j - 13), 32768);
                            tma_3d(sb + (2 * j - 22) * 16384, &tmS.wd8, bars + 8 * (B_DN + j - 13), 0, blockIdx.x * 32, (j - 13) * 8);
                        }
                    }
                }
                __syncwarp();
                if (++s == 3) { s = 0; ph ^= 1; }
                if (j == 3 && lane < ACC_VEC_PER_CTA) reinterpret_cast<uint4*>(&P.scr->acc[~epoch & 1u])[blockIdx.x * ACC_VEC_PER_CTA + lane] = make_uint4(0, 0, 0, 0);
            }
            TLP(elect, 20);
        } else {
            const bool ffn = blockIdx.x < 112;
            const uint32_t fbuf = sb + SM_FB + 4096 + aw * 12288, fbar = bars + 8 * (B_FF + 1 + aw * 3);
        const int nc = aw == 0 ? NC0 : (aw == 1 ? 12 - NC0 - NC2 : NC2), c0 = aw == 0 ? 0 : (aw == 1 ? NC0 : 12 - NC2);
        const int ng = !ffn ? 0 : (aw == 0 ? NG0 : (aw == 1 ? NG1 : 32 - NG0 - NG1)), g0 = aw == 0 ? 0 : (aw == 1 ? NG0 : NG0 + NG1);
        auto issue = [&](int i, int b) {
            __syncwarp();
            if (i < nc + ng && elect_one()) {
                mbar_expect_tx(fbar + b * 8, 4096);
                if (i < nc) {
                    tma_2d(fbuf + b * 4096, &tmS.wc, fbar + b * 8, ((c0 + i) >> 2) * 1024 + hp * 64, rb * 128 + ((c0 + i) & 3) * 32);
                } else {
                    tma_2d(fbuf + b * 4096, &tmS.wg, fbar + b * 8, blockIdx.x * 32, (g0 + i - nc) * 32);
                    tma_2d(fbuf + b * 4096 + 2048, &tmS.wu, fbar + b * 8, blockIdx.x * 32, (g0 + i - nc) * 32);
                }
            }
            __syncwarp();
        };
            {
                uint4 wv[4];
#pragma unroll
                for (int i = 0; i < 4; i++) wv[i] = __ldg(reinterpret_cast<const uint4*>(P.wr) + i * 32 + lane);
                const uint32_t* ww = reinterpret_cast<const uint32_t*>(wv);
                float sw = 0.f;
#pragma unroll
                for (int i = 0; i < 16; i++) sw += bf_lo(ww[i]) + bf_hi(ww[i]);
#pragma unroll 1
                for (int o = 16; o > 0; o >>= 1) sw += __shfl_xor_sync(0xffffffffu, sw, o);
                sts32(sb + SM_MISC + 20, __float_as_uint(sw));
                if (aw == 2) {
#pragma unroll
                    for (int i = 0; i < 3; i++) P.scr->kv[(hp * 8 + rb) * 96 + i * 32 + lane] = make_uint4(0, 0, 0, 0);
                    if (hp == 0) reinterpret_cast<uint4*>(&P.scr->cnt_o[rb * 128])[lane] = make_uint4(0, 0, 0, 0);
                    asm volatile("fence.acq_rel.gpu;" ::: "memory");
                    __syncwarp();
                }
                mbar_wait(bars + 8 * B_XR, 0);
#pragma unroll 1
                for (int r = aw * 6; r < min(aw * 6 + 6, 16); r++) {
                    const uint32_t buf = sb + SM_FB + 4096 + r * 2048;
                    uint4 xv[4];
                    uint32_t c2 = lds32(buf);
#pragma unroll
                    for (int i = 0; i < 4; i++) xv[i] = lds128(buf + i * 512 + lane * 16);
                    sts32(sb + SM_MISC + 12, 0u);
                    c2 = fabsf(bf_lo(c2) - bf_hi(c2)) < 0.25f * fabsf(bf_lo(c2)) ? dup_lo(c2) : 0u;
                    const uint32_t* xw = reinterpret_cast<const uint32_t*>(xv);
                    uint32_t d2[2] = {0u, 0u};
                    float s0 = 0.f, s1 = 0.f, q0 = 0.f, q1 = 0.f;
#pragma unroll
                    for (int i = 0; i < 16; i++) {
                        const uint32_t a = hsub2(xw[i], c2);
                        s0 += bf_lo(a); s1 += bf_hi(a);
                        d2[i & 1] = hfma2(a, ww[i], d2[i & 1]);
                        q0 = fmaf(bf_lo(a), bf_lo(a), q0); q1 = fmaf(bf_hi(a), bf_hi(a), q1);
                    }
                    sts128(sb + SM_SP + r * 512 + lane * 16, __float_as_uint(s0 + s1), __float_as_uint(q0 + q1),
                           __float_as_uint((bf_lo(d2[0]) + bf_hi(d2[0])) + (bf_lo(d2[1]) + bf_hi(d2[1]))), c2 << 16);
                }
                epoch = __shfl_sync(0xffffffffu, epoch, 0);
                if (aw < 2) nb_arrive(NB_FFN, 96);
                mbar_wait(bars + 8 * B_FF, 0);
#pragma unroll 1
                for (int i = 0; i < 3; i++) issue(i, i);
                const unsigned tag = epoch + 1u;
                if (aw == 2) {
                    nb_sync(NB_FFN, 96);
                    TLP(elect, 23);
                    float s = 0.f, q = 0.f, dt = 0.f, x0;
#pragma unroll 8
                    for (int j = 0; j < 16; j++) {
                        const uint4 e = lds128(sb + SM_SP + lane * 256 + ((j + lane) & 15) * 16);
                        s += __uint_as_float(e.x); q += __uint_as_float(e.y); dt += __uint_as_float(e.z); x0 = __uint_as_float(e.w);
                    }
                    s += __shfl_xor_sync(0xffffffffu, s, 1); q += __shfl_xor_sync(0xffffffffu, q, 1); dt += __shfl_xor_sync(0xffffffffu, dt, 1);
                    const float ms = s * (1.0f / D_);
                    const float vb = round_bf16(fmaxf(q - s * ms, 0.f) * (1.0f / D_));
                    const uint32_t md = pack_bf16(x0 + ms, sqrt_a(round_bf16(vb + 1e-5f)));
                    const uint32_t rbits = pack_bf16((dt - (bf_lo(md) - x0) * ldsf(sb + SM_MISC + 20)) * rcp(bf_hi(md)), 0.f);
                    const int row = blockIdx.x * 16 + (lane >> 1);
                    const uint32_t key = ((((rbits & 0x8000u) ? (~rbits & 0xFFFFu) : (rbits | 0x8000u)) + 1u) << 11) | (uint32_t)(2047 - row);
                    asm volatile("st.relaxed.gpu.global.v2.u32 [%0], {%1, %2};" :: "l"(&P.scr->rows[row]), "r"(md), "r"(tag) : "memory");
                    if (key == __reduce_max_sync(0xffffffffu, key))
                        asm volatile("st.relaxed.gpu.global.v4.u32 [%0], {%1, %2, %3, %3};" :: "l"(&P.scr->best[blockIdx.x]), "r"(key), "r"(md), "r"(tag) : "memory");
                    TLP(elect, 24);
                }
                {
                    float a[8], sq = 0.f, wt = 0.f;
#pragma unroll
                    for (int i = 0; i < 8; i++) a[i] = 0.f;
#pragma unroll 1
                    for (int m = 0; m < nc; m++) {
                        const int b = m % 3, c = c0 + m;
                        mbar_wait(fbar + b * 8, (m / 3) & 1);
                        uint4 v[8];
#pragma unroll
                        for (int i = 0; i < 8; i++) v[i] = lds128(fbuf + b * 4096 + i * 512 + lane * 16);
                        sts32(sb + SM_MISC + 12, 0u);
                        colsum8<true>(a, sq, v);
                        fence_regs(a);
                        wt += 1.0f;
                        issue(m + 3, b);
                        if ((c & 3) == 3 || m == nc - 1) {
#pragma unroll 1
                            for (int o = 8; o <= 16; o <<= 1) {
#pragma unroll
                                for (int i = 0; i < 8; i++) a[i] += __shfl_xor_sync(0xffffffffu, a[i], o);
                                sq += __shfl_xor_sync(0xffffffffu, sq, o);
                            }
                            float4* dst = &get_acc()->cs[((c >> 2) * 16 + hp) * 24 + lane];
                            if (lane < 8) { red_v4(dst, a[0], a[1], a[2], wt); red_v4(dst + 8, a[3], a[4], a[5], wt); red_v4(dst + 16, a[6], a[7], sq, wt); }
#pragma unroll
                            for (int i = 0; i < 8; i++) a[i] = 0.f;
                            wt = 0.f;
                        }
                    }
                    TLP(tid == 288, 26); TLP(tid == 320, 15); TLP(tid == 352, 22);
                }
                if (aw == 0) {
                    uint4 v[4];
                    unsigned it = 0;
                    bool ok = true;
#pragma unroll 1
                    do {
                        if (!ok) __nanosleep(200);
#pragma unroll
                        for (int i = 0; i < 4; i++) v[i] = ld_gpu(&P.scr->best[i * 32 + lane]);
                        ok = v[0].z == tag && v[1].z == tag && v[2].z == tag && v[3].z == tag;
                    } while (!__all_sync(0xffffffffu, ok) && ++it < (1u << 20));
#pragma unroll
                    for (int i = 1; i < 4; i++) if (v[i].x > v[0].x) v[0] = v[i];
                    const uint32_t key = __reduce_max_sync(0xffffffffu, v[0].x);
                    const uint32_t md = __reduce_or_sync(0xffffffffu, v[0].x == key ? v[0].y : 0u);
                    const int sel = 2047 - (int)(key & 2047u);
                    const uint4* xp = reinterpret_cast<const uint4*>(P.x + (size_t)sel * D_) + lane;
#pragma unroll
                    for (int i = 0; i < 4; i++) v[i] = __ldg(xp + i * 32);
                    const uint32_t m2 = __byte_perm(md, 0, 0x1010);
                    const float rs = rcp(bf_hi(md));
                    const uint32_t ord = (key >> 11) - 1u;
                    const float r = __uint_as_float(((ord & 0x8000u) ? (ord & 0x7FFFu) : (~ord & 0xFFFFu)) << 16);
                    sts128(sb + SM_MISC, (uint32_t)sel, __float_as_uint(round_bf16(rcp(1.0f + ex2(-r * LOG2E)))), epoch, 0u);
#pragma unroll
                    for (int i = 0; i < 4; i++) {
                        const uint32_t e0 = ln_pair(v[i].x, m2, rs), e1 = ln_pair(v[i].y, m2, rs), e2 = ln_pair(v[i].z, m2, rs), e3 = ln_pair(v[i].w, m2, rs);
                        const uint32_t xa = sb + SM_XS + i * 512 + (lane >> 2) * 64 + (lane & 3) * 4;
                        sts32(xa, __byte_perm(e0, e2, 0x5410)); sts32(xa + 16, __byte_perm(e0, e2, 0x7632));
                        sts32(xa + 32, __byte_perm(e1, e3, 0x5410)); sts32(xa + 48, __byte_perm(e1, e3, 0x7632));
                    }
                    TLP(elect, 25);
                    __syncwarp();
                    mbar_arrive_if(elect, bars + 8 * B_XS);
                }
            }
            if (aw == 2) {
                    const int l = lane < 24 ? lane : 0;
                    const float4* src = &get_acc()->cs[((l >> 3) * 16 + hp) * 24 + (l & 7)];
                    float4 v0, v1, v2;
                    uint4 v[4];
                    unsigned it = 0;
                    bool ok;
#pragma unroll 1
                    do {
                        v0 = ld_gpu(src); v1 = ld_gpu(src + 8); v2 = ld_gpu(src + 16);
                        ok = v0.w == 32.0f && v1.w == 32.0f && v2.w == 32.0f;
#pragma unroll
                        for (int i = 0; i < 4; i++) v[i] = ld_gpu(reinterpret_cast<const uint4*>(&P.scr->rows[rb * 256]) + i * 32 + lane);
#pragma unroll
                        for (int i = 0; i < 4; i++) ok = ok && v[i].y == epoch + 1u && v[i].w == epoch + 1u;
                    } while (!__all_sync(0xffffffffu, ok) && ++it < (1u << 20));
#pragma unroll
                    for (int i = 0; i < 4; i++) {
                        const uint32_t o = i * 256 + lane * 8;
                        sts64(sb + SM_MD + o, v[i].x, v[i].z);
                        sts64(sb + SM_RS + o, __float_as_uint(rcp(bf_hi(v[i].x))), __float_as_uint(rcp(bf_hi(v[i].z))));
                        const uint32_t h0 = hmul2(dup_lo(v[i].x), 0xBF00BF00u), h1 = hmul2(dup_lo(v[i].z), 0xBF00BF00u);
                        sts128(sb + SM_AX + o * 4, h0, h0 & 0xFFFFu, 0u, 0u);
                        sts128(sb + SM_AX + o * 4 + 16, h1, h1 & 0xFFFFu, 0u, 0u);
                    }
                    sts128(sb + SM_H + lane * 16, 0u, 0u, 0u, 0u); sts128(sb + SM_H + 512 + lane * 16, 0u, 0u, 0u, 0u);
                    const uint32_t e2 = __reduce_max_sync(0xffffffffu, l >= 16 ? __float_as_uint(v2.z) : 0u) >> 23;
                    sts32(sb + SM_MISC + 16, (uint32_t)min(max(187 - (int)((e2 + 1) >> 1), 1), 180) << 23);
                    float cc[8] = {v0.x, v0.y, v0.z, v1.x, v1.y, v1.z, v2.x, v2.y};
                    const uint32_t bx = sb + SM_BX + (l >> 3) * 1024;
#pragma unroll 1
                    for (int k = 0; k < 8; k++) {
                        uint32_t w[4];
#pragma unroll
                        for (int i = 0; i < 4; i++) {
                            w[i] = pack_bf16(cc[2 * i], cc[2 * i + 1]);
                            cc[2 * i] -= bf_lo(w[i]); cc[2 * i + 1] -= bf_hi(w[i]);
                        }
                        sts128(bx + k * 128 + (((l & 7) ^ k) * 16), w[0], w[1], w[2], w[3]);
                    }
                    fence_async_smem();
                    __syncwarp();
                    mbar_arrive_if(elect, bars + 8 * B_LN);
                    TLP(elect, 28);
                }
            mbar_wait(bars + 8 * B_XS, 0);
            if (ffn) {
                float a[8];
#pragma unroll
                for (int i = 0; i < 8; i++) a[i] = 0.f;
                TLP(elect, 40 + aw);
                gemv_run<256>(a, ng, nc % 3, (nc / 3) & 1, fbuf + (lane >> 4) * 2048 + (lane & 15) * 16, sb + SM_XS + g0 * 64 + (lane & 12) * 4, 64, fbar, sb + SM_MISC + 12,
                              [&](int m, int b) { issue(nc + m + 3, b); });
                TLP(elect, 44 + aw);
#pragma unroll 1
                for (int o = 4; o <= 8; o <<= 1) {
#pragma unroll
                    for (int i = 0; i < 8; i++) a[i] += __shfl_xor_sync(0xffffffffu, a[i], o);
                }
                if ((lane & 12) == 0) {
                    const uint32_t ga = sb + SM_GU + aw * 256 + (lane >> 4) * 128 + (lane & 3) * 32;
                    sts128(ga, __float_as_uint(a[0]), __float_as_uint(a[1]), __float_as_uint(a[2]), __float_as_uint(a[3]));
                    sts128(ga + 16, __float_as_uint(a[4]), __float_as_uint(a[5]), __float_as_uint(a[6]), __float_as_uint(a[7]));
                }
                nb_sync(NB_AUX, 96);
                if (warp == 9) {
                    const uint32_t ga = sb + SM_GU + lane * 4;
                    const float gg = round_bf16((ldsf(ga) + ldsf(ga + 256)) + ldsf(ga + 512));
                    const float uu = round_bf16((ldsf(ga + 128) + ldsf(ga + 384)) + ldsf(ga + 640));
                    asm volatile("st.shared.u16 [%0], %1;" :: "r"(sb + SM_H + (lane >> 3) * 256 + 112 + (lane & 7) * 2), "h"((uint16_t)pack_bf16(round_bf16(silu_f(gg)) * uu, 0.f)) : "memory");
                    fence_async_smem();
                }
                __syncwarp();
                TLP(tid == 288, 27);
            } else {
                nb_sync(NB_AUX, 96);
            }
            if (warp == 10 && elect_one()) load_wo(0);
            __syncwarp();
        }
        {
            TLP(tid == 288, 38);
            const int w4 = warp & 3;
            const uint32_t sp = sb + 212992 + w4 * 1536;
            auto send = [&](int h) {
                if (elect_one()) {
                    asm volatile("cp.reduce.async.bulk.global.shared::cta.bulk_group.add.noftz.f16 [%0], [%1], 1536;"
                                 :: "l"(&P.scr->kv[(hp * 8 + h * 4 + w4) * 96]), "r"(sp) : "memory");
                    asm volatile("cp.async.bulk.commit_group;" ::: "memory");
                }
            };
            float ya[4] = {0.f, 0.f, 0.f, 0.f}, yb[4] = {0.f, 0.f, 0.f, 0.f};
            uint4 g0[3];
#pragma unroll 1
            for (int h = 0; h < 2; h++) {
                {
                    float d[20];
                    const uint32_t alo = dlo(sb + SM_PHI + h * 32768, 16), vlo = dlo(sb + SM_V + h * 20480, 16);
                    mbar_wait(bars + 8 * (B_PHI + h), 0);
                    wgmma_fence();
#pragma unroll
                    for (int k = 0; k < 16; k++)
                        wgmma_ss_n40(d, desc_from(alo + (k >> 2) * 512 + (k & 3) * 2, DH128), desc_from(vlo + (k >> 2) * 320 + (k & 3) * 2, DH128), k);
                    wgmma_commit();
#pragma unroll
                    for (int j = 0; j < 3; j++) g0[j] = ld_gpu(&P.scr->kv[(hp * 8 + w4) * 96 + j * 32 + lane]);
                    asm volatile("cp.async.bulk.wait_group.read 0;" ::: "memory");
                    __syncwarp();
                    const float ksc = ldsf(sb + SM_MISC + 16);
                    wgmma_wait<0>();
                    fence_regs(d);
#define U(x) pack_f16(d[x] * ksc, d[x + 1] * ksc)
                    sts128(sp + lane * 16, U(0), U(4), U(8), pack_f16(d[16], 1.0f));
                    sts128(sp + 512 + lane * 16, U(2), U(6), U(10), pack_f16(d[18], 1.0f));
                    sts128(sp + 1024 + lane * 16, U(12), U(14), 0u, 0x3C000000u);
#undef U
                    fence_async_smem();
                    __syncwarp();
                    send(h);
                    TLP(tid == 256, 30 + h);
                    nb_sync(NB_KV, 128);
                    if (h) break;
                    if (warp == 8 && elect_one()) {
                        mbar_expect_tx(bars + 8 * B_X, 32768);
                        tma_2d(sb, &tmX2, bars + 8 * B_X, (hp >> 1) * 128, rb * 256 + (hp & 1) * 128);
                        tma_2d(sb + 16384, &tmX2, bars + 8 * B_X, (hp >> 1) * 128 + 64, rb * 256 + (hp & 1) * 128);
                    }
                    __syncwarp();
                }
                if (blockIdx.x < 112) {
                    const uint32_t hlo = dlo(sb + SM_H, 256);
                    mbar_wait(bars + 8 * B_DN, 0);
                    mbar_wait(bars + 8 * (B_DN + 1), 0);
                    wgmma_fence();
#pragma unroll 2
                    for (int k = 0; k < 16; k++) {
                        wgmma_ss_n8_ta(yb, desc_from(dlo(sb + 6 * 16384, 16) + k * 128, DH128), desc_from(hlo + (k & 1) * 32 + 7 - (k >> 1), 8), k);
                        wgmma_ss_n8_ta(ya, desc_from(dlo(sb + 4 * 16384, 16) + k * 128, DH128), desc_from(hlo + (k & 1) * 32 + 7 - (k >> 1), 8), k);
                    }
                    wgmma_commit();
                    wgmma_wait<0>();
                    fence_regs(ya); fence_regs(yb);
                    if (warp == 8) {
                        nb_sync(NB_KV, 128);
                        if (elect_one()) { load_wo(1); load_wo(2); }
                        __syncwarp();
                    } else {
                        nb_arrive(NB_KV, 128);
                    }
                    TLP(tid == 288, 29);
                }
            }
            const float kus = __uint_as_float((254u << 23) - lds32(sb + SM_MISC + 16));
            kv_gather<1>(g0, &P.scr->kv[(hp * 8 + w4) * 96 + lane], sb + SM_KVOP + w4 * 256, lane, kus);
            mbar_arrive_if(elect, bars + 8 * B_KV);
            if (warp == 8 && elect_one()) { load_wo(4); if (blockIdx.x < 112) { load_wo(3); load_wo(5); } }
            __syncwarp();
            asm volatile("cp.async.bulk.wait_group.read 0;" ::: "memory");
            __syncwarp();
            if (blockIdx.x < 112) {
#define U(x) __float_as_uint(x)
                sts128(sp + lane * 16, U(ya[0]), U(ya[1]), U(ya[2]), U(1.0f));
                sts128(sp + 512 + lane * 16, U(ya[3]), U(yb[0]), U(yb[1]), U(1.0f));
                sts128(sp + 1024 + lane * 16, U(yb[2]), U(yb[3]), 0u, U(1.0f));
#undef U
                fence_async_smem();
                __syncwarp();
                if (elect_one()) {
                    asm volatile("cp.reduce.async.bulk.global.shared::cta.bulk_group.add.f32 [%0], [%1], 1536;"
                                 :: "l"(&get_acc()->y[((blockIdx.x & 3) * 4 + w4) * 96]), "r"(sp) : "memory");
                    asm volatile("cp.async.bulk.commit_group;" ::: "memory");
                }
                __syncwarp();
            }
            if (w4 >= 2) {
                uint4 g1[6];
#pragma unroll
                for (int j = 0; j < 6; j++) g1[j] = make_uint4(0, 0, 0, 0);
                kv_gather<2>(g1, &P.scr->kv[(hp * 8 + 2 * w4) * 96 + lane], sb + SM_KVOP - 5120 + (w4 - 2) * 512, lane, kus);
                mbar_arrive_if(lane < 2, bars + 8 * (B_KV + 1));
            }
            asm volatile("cp.async.bulk.wait_group.read 0;" ::: "memory");
        }
        if (warp == 8) {
            if (elect_one()) {
                uint4 cnt;
                mbar_wait(bars + 8 * B_O, 0);
#pragma unroll
                for (int i = 0; i < 16; i++) {
                    if (!(i & 3)) cnt = make_uint4(0, 0, 0, 0);
                    unsigned it = 0;
#pragma unroll 1
                    while (((i & 3) == 0 ? cnt.x : ((i & 3) == 1 ? cnt.y : ((i & 3) == 2 ? cnt.z : cnt.w))) < 2u && ++it < (1u << 20))
                        cnt = ld_gpu(reinterpret_cast<const uint4*>(&P.scr->cnt_o[rb * 128 + (hp & 1) * 64 + (i >> 3) * 32 + (i & 4)]));
                    if (PFENCE) asm volatile("fence.proxy.async.global;" ::: "memory");
                    if ((i & 3) == 0 && i < 12) TL(i == 0 ? 21 : (i == 4 ? 34 : 36));
                    if (i == 4 || i > 5) mbar_wait(bars + 8 * (B_SD + max(i - 5, 0)), 0);
                    load_o(i);
                    if (i == 3) load_wo(6);
                    if (i >= 5 && i < 14) load_wo(i + 2);
                }
            }
        } else if (warp < 11) {
            if (elect_one()) {
#pragma unroll
                for (int w = 0; w < 2; w++) {
                    mbar_wait(bars + 8 * (B_OW + 2 * aw + w), 0);
                    asm volatile("cp.async.bulk.tensor.2d.global.shared::cta.bulk_group [%0, {%2, %3}], [%1];"
                                 :: "l"(&tmOs), "r"(sb + SM_OS + w * 8192), "r"(aw * 512 + hp * 32), "r"(rb * 256 + w * 128) : "memory");
                    asm volatile("cp.async.bulk.commit_group;" ::: "memory");
                }
#pragma unroll
                for (int w = 0; w < 2; w++) {
                    if (w) asm volatile("cp.async.bulk.wait_group 0;" ::: "memory"); else asm volatile("cp.async.bulk.wait_group 1;" ::: "memory");
                    asm volatile("fence.proxy.async.global;" ::: "memory");
                    asm volatile("red.relaxed.gpu.global.add.u32 [%0], 1;" :: "l"(&P.scr->cnt_o[rb * 128 + w * 64 + aw * 32 + (hp >> 1)]) : "memory");
                }
                asm volatile("mbarrier.arrive.shared::cta.b64 _, [%0];" :: "r"(bars + 8 * B_OS) : "memory");
            }
        } else if (warp == 11) {
            const uint4 misc = lds128(sb + SM_MISC);
            if ((int)(misc.x >> 7) == rb * 2 + (hp & 1)) {
                float y[4] = {0.f, 0.f, 0.f, 0.f};
#pragma unroll 1
                for (int rep = 0; rep < 4; rep++) {
                    const float4* yp = &get_acc()->y[(rep * 4 + (lane >> 3)) * 96 + (hp >> 3) * 32 + (lane & 7) * 4 + ((hp >> 1) & 3)];
                    float4 u, v;
                    unsigned it = 0;
#pragma unroll 1
                    do { u = ld_gpu(yp); v = ld_gpu(yp + 32); } while (!__all_sync(0xffffffffu, u.w == 28.0f && v.w == 28.0f) && ++it < (1u << 20));
                    if (hp & 8) { y[0] += u.y; y[1] += v.x; y[2] += u.z; y[3] += v.y; } else { y[0] += u.x; y[1] += u.z; y[2] += u.y; y[3] += v.x; }
                }
                const uint32_t sg = __byte_perm(misc.y, 0, 0x3232), ya = sb + SM_Y + ((lane >> 3) * 16 + (lane & 7)) * 2;
                const uint32_t w0 = hmul2(pack_bf16(y[0], y[1]), sg), w1 = hmul2(pack_bf16(y[2], y[3]), sg);
                asm volatile("st.shared.u16 [%0], %1;" :: "r"(ya), "h"((uint16_t)w0) : "memory");
                asm volatile("st.shared.u16 [%0], %1;" :: "r"(ya + 16), "h"((uint16_t)(w0 >> 16)) : "memory");
                asm volatile("st.shared.u16 [%0], %1;" :: "r"(ya + 128), "h"((uint16_t)w1) : "memory");
                asm volatile("st.shared.u16 [%0], %1;" :: "r"(ya + 144), "h"((uint16_t)(w1 >> 16)) : "memory");
                __syncwarp();
                if (lane < 16) {
                    const uint4 xc = __ldg(reinterpret_cast<const uint4*>(P.x + (size_t)misc.x * D_ + (hp >> 1) * 128) + lane);
                    const uint32_t m2 = __byte_perm(lds32(sb + SM_MD + (misc.x & 255u) * 4), 0, 0x1010);
                    const float r = ldsf(sb + SM_RS + (misc.x & 255u) * 4);
                    const uint4 yv = lds128(sb + SM_Y + lane * 16);
                    sts128(sb + SM_Y + lane * 16, silu_pair(hadd2(ln_pair(xc.x, m2, r), yv.x)), silu_pair(hadd2(ln_pair(xc.y, m2, r), yv.y)),
                           silu_pair(hadd2(ln_pair(xc.z, m2, r), yv.z)), silu_pair(hadd2(ln_pair(xc.w, m2, r), yv.w)));
                    sts128(sb + SM_Y + 256 + lane * 16, xc.x, xc.y, xc.z, xc.w);
                }
                __syncwarp();
                mbar_arrive_if(elect, bars + 8 * B_Y);
                TLP(elect, 39);
            }
        }
    } else {
        const int wg = warp >> 2, w4 = warp & 3, g = lane >> 2;
        nb_sync(0, NTHREADS);
        asm volatile("setmaxnreg.inc.sync.aligned.u32 224;");
        TLP(tid == 0, 1);
        const int row0 = wg * 128 + w4 * 16 + g;
        float pq0[16], pq1[16];
        float rs[4];
        uint32_t f2[8], f3[8], q0[8], q1[8], q2[8], q3[8];
        float qa[16], qb[16];
        const uint32_t wlo = dlo(sb + SM_WPHI, 16);
        const uint32_t sw0 = (uint32_t)(((w4 * 2) ^ (lane & 7)) * 16), sw1 = sw0 ^ 16u;
        {
            float acc0[96], acc1[96];
            {
                const uint32_t alo0 = dlo(sb + wg * 16384, 16), blo0 = dlo(sb + 32768, 8192);
                {
#pragma unroll
                    for (int k = 0; k < 4; k++) {
                        if (k == 0) asm volatile("cp.async.wait_group 1;" ::: "memory");
                        if (k == 2) { wgmma_commit(); asm volatile("cp.async.wait_group 0;" ::: "memory"); }
                        if (!(k & 1)) { fence_async_smem(); nb_sync(NB_STAG, 256); wgmma_fence(); }
                        if (k == 0) { TLP(tid == 0, 2); TLG(tid == 0, 49); }
                        wgmma_ss_n192_tb(acc0, desc_from(alo0 + k * 2, DH128), desc_from(blo0 + k * 128, DH128), k);
                        wgmma_ss_n192_tb(acc1, desc_from(alo0 + 512 + k * 2, DH128), desc_from(blo0 + k * 128, DH128), k);
                    }
                    wgmma_commit();
                }
                int s = 1, ph = 0, ps = 0;
#pragma unroll 1
                for (int ks = 1; ks < 16; ks++) {
                    const bool hold = wg && ks == 15;
                    if (hold) {
                        wgmma_wait<0>();
                        mbar_arrive_if(elect, bars + 8 * (B_EMPTY + ps));
                        nb_sync(NB_LEAD, 256);
                    }
                    mbar_wait(bars + 8 * (B_FULL + s), ph);
                    const uint32_t alo = alo0 + s * (STAGE >> 4), blo = blo0 + s * (STAGE >> 4);
                    wgmma_fence();
#pragma unroll
                    for (int k = 0; k < 4; k++) {
                        if (k == SARR && !wg && ks == 15) nb_arrive(NB_LEAD, 256);
                        wgmma_ss_n192_tb(acc0, desc_from(alo + k * 2, DH128), desc_from(blo + k * 128, DH128), 1);
                        wgmma_ss_n192_tb(acc1, desc_from(alo + 512 + k * 2, DH128), desc_from(blo + k * 128, DH128), 1);
                        if (k == 0) {
                            wgmma_commit();
                            wgmma_wait<1>();
                            mbar_arrive_if(elect && !hold, bars + 8 * (B_EMPTY + ps));
                        }
                    }
                    wgmma_commit();
                    ps = s;
                    if (++s == 3) { s = 0; ph ^= 1; }
                }
            }
            mbar_wait(bars + 8 * B_LN, 0);
            wgmma_fence();
            wgmma_ss_n192_tb(acc0, desc_from(dlo(sb + SM_AX + wg * 2048, 0), 128u >> 4), desc_from(dlo(sb + SM_BX, 1024), 1u << 30), 1);
            wgmma_ss_n192_tb(acc1, desc_from(dlo(sb + SM_AX + wg * 2048 + 1024, 0), 128u >> 4), desc_from(dlo(sb + SM_BX, 1024), 1u << 30), 1);
            wgmma_commit();
            mbar_wait(bars + 8 * (B_EMPTY + 2), 0);
            mbar_wait(bars + 8 * B_WPHI, 0);
            {
                uint32_t md[4];
#pragma unroll
                for (int i = 0; i < 4; i++) {
                    const int r = row0 + (i >> 1) * 64 + (i & 1) * 8;
                    md[i] = __byte_perm(lds32(sb + SM_MD + r * 4), 0, 0x3232);
                    rs[i] = ldsf(sb + SM_RS + r * 4);
                }
                const uint32_t zb = sb + SM_V + wg * 10240 + (lane >> 4) * 5120 + 4096 + (lane & 7) * 128 + (sw0 ^ ((lane & 8) * 2));
                stsm_t(zb, md[0], md[1], md[2], md[3]);
                stsm_t(zb + 20480, md[0], md[1], md[2], md[3]);
            }
            wgmma_wait<0>();
            fence_regs(acc0); fence_regs(acc1);
            TLP(tid == 0, 3); TLG(tid == 0, 50);
            const uint32_t vb = sb + SM_V + wg * 10240 + lane * 128;
            uint32_t f0[8], f1[8], v[8];
            pack_head<64>(acc0, v); stsm_t(vb + sw0, v[0], v[2], v[4], v[6]); stsm_t(vb + sw1, v[1], v[3], v[5], v[7]);
            pack_head<64>(acc1, v); stsm_t(vb + 5120 + sw0, v[0], v[2], v[4], v[6]); stsm_t(vb + 5120 + sw1, v[1], v[3], v[5], v[7]);
#pragma unroll
            for (int i = 32; i < 48; i++) { asm volatile("" : "+f"(acc0[i]) :: "memory"); asm volatile("" : "+f"(acc1[i]) :: "memory"); }
            pack_head<32>(acc0, f0); pack_head<32>(acc1, f1);
            wgmma_fence();
            feat_mma(pq0, f0, wlo); feat_mma(pq1, f1, wlo);
            wgmma_commit();
            pack_head<80>(acc0, v); stsm_t(vb + 20480 + sw0, v[0], v[2], v[4], v[6]); stsm_t(vb + 20480 + sw1, v[1], v[3], v[5], v[7]);
            pack_head<80>(acc1, v); stsm_t(vb + 25600 + sw0, v[0], v[2], v[4], v[6]); stsm_t(vb + 25600 + sw1, v[1], v[3], v[5], v[7]);
            pack_head<48>(acc0, f2); pack_head<48>(acc1, f3);
            pack_head<0>(acc0, q0); pack_head<0>(acc1, q1);
#pragma unroll
            for (int i = 0; i < 16; i++) { qa[i] = acc0[16 + i]; qb[i] = acc1[16 + i]; }
            fence_regs(f2); fence_regs(f3); fence_regs(q0); fence_regs(q1);
            wgmma_wait<0>();
            fence_regs(pq0); fence_regs(pq1); fence_regs(f0); fence_regs(f1);
            mbar_arrive_if(elect, bars + 8 * B_T);
            TLP(tid == 0, 4);
        }
#pragma unroll 1
        for (int h = 0; h < 2; h++) {
            const uint32_t pb = sb + SM_PHI + wg * 16384 + lane * 128 + h * 32768;
            key_head(pq0, pq1, rs, pb + sw0, pb + sw1);
            wgmma_fence();
            feat_mma(pq0, f2, wlo + 128 - h * 128); feat_mma(pq1, f3, wlo + 128 - h * 128);
            wgmma_commit();
            fence_async_smem();
            __syncwarp();
            mbar_arrive_if(elect, bars + 8 * (B_PHI + h));
            TLP(tid == 0, 6 + 2 * h);
            mbar_wait(bars + 8 * B_T, 0);
            wgmma_wait<0>();
            fence_regs(pq0); fence_regs(pq1); fence_regs(f2); fence_regs(f3);
#pragma unroll
            for (int j = 0; j < 8; j++) { f2[j] = q0[j]; f3[j] = q1[j]; }
            fence_regs(f2); fence_regs(f3);
        }
#pragma unroll
        for (int j = 0; j < 8; j++) { q2[j] = pack_bf16(qa[2 * j], qa[2 * j + 1]); q3[j] = pack_bf16(qb[2 * j], qb[2 * j + 1]); }
        const int orow = (hp & 1) * 128 + wg * 64 + w4 * 16 + (lane >> 4);
        const size_t goff = (size_t)(rb * 256 + orow) * D_ + (hp >> 1) * 128 + (lane & 15) * 8;
        uint4 gv[8], xv[8];
#pragma unroll
        for (int i = 0; i < 8; i++) xv[i] = make_uint4(0, 0, 0, 0);
#pragma unroll
        for (int i = 0; i < GSPLIT2; i++) gv[i] = make_uint4(0, 0, 0, 0);
        const uint32_t rowc = sb + ((lane >> 3) & 1) * 16384 + (wg * 64 + w4 * 16 + (lane >> 4)) * 128;
        {
            const uint32_t od = sb + SM_OS + (wg * 128 + w4 * 16) * 64 + lane * 16;
#pragma unroll 1
            for (int h = 0; h < 2; h++) {
                uint32_t pa[8], na[8], pb[8], nb[8];
                features(pq0, pq1, rs, pa, na, pb, nb);
                TLP(tid == 0, 16 + h);
                if (h == 0) {
                    wgmma_fence();
                    feat_mma(pq0, q2, wlo + 128); feat_mma(pq1, q3, wlo + 128);
                    wgmma_commit();
                    wgmma_wait<0>();
                    fence_regs(pq0); fence_regs(pq1); fence_regs(q2); fence_regs(q3);
                    TLP(tid == 0, 18);
                } else {
#pragma unroll
                    for (int i = GSPLIT; i < GSPLIT2; i++) { gv[i] = xv[i]; gate_item(gv[i], sb, orow + 2 * i); }
                    TLP(tid == 0, 10);
                }
                {
                    float d0[20], e0[20], d1[20], e1[20];
                    const uint32_t klo = dlo(sb + SM_KVOP - h * 5120, 128);
                    fence_regs(pa); fence_regs(na); fence_regs(pb); fence_regs(nb);
                    mbar_wait(bars + 8 * (B_KV + h), 0);
                    TLP(tid == 0, 32 + h);
                    wgmma_fence();
                    o_mma(d0, e0, pa, na, klo);
                    wgmma_commit();
                    o_mma(d1, e1, pb, nb, klo);
                    wgmma_commit();
                    if (h) mbar_wait(bars + 8 * B_OS, 0);
                    wgmma_wait<1>();
                    fence_regs(d0); fence_regs(e0); fence_regs(pa); fence_regs(na);
                    o_store(d0, e0, od);
                    wgmma_wait<0>();
                    fence_regs(d1); fence_regs(e1); fence_regs(pb); fence_regs(nb);
                    o_store(d1, e1, od + 4096);
                    fence_async_smem();
                    __syncwarp();
                    mbar_arrive_if(elect, bars + 8 * (B_OW + 2 * h + wg));
                    if (!h) {
                    mbar_wait(bars + 8 * B_X, 0);
#pragma unroll
                    for (int i = 0; i < 8; i++) xv[i] = lds128(rowc + i * 256 + (((lane & 7) ^ ((2 * i + (lane >> 4)) & 7)) * 16));
#pragma unroll
                    for (int i = 0; i < GSPLIT; i++) { gv[i] = xv[i]; gate_item(gv[i], sb, orow + 2 * i); }
                    __syncwarp();
                    }
                    mbar_arrive_if(elect, bars + 8 * (B_O + h));
                }
                TLP(tid == 0, 9 + 2 * h);
            }
        }
        float ghr[8], ghm[8];
        float acc[64];
        {
            const uint32_t alo0 = dlo(sb + wg * 8192, 16), blo0 = dlo(sb, 8192);
#pragma unroll
            for (int i = 0; i < 16; i++) {
                const uint32_t alo = alo0 + o_slot(i) * 1024, blo = blo0 + wo_slot(i) * 1024;
                mbar_wait(bars + 8 * (B_OF + i), 0);
                if (i == OSTAG && wg == 0) nb_sync(NB_STAG, 256);
                wgmma_fence();
#pragma unroll
                for (int k = 0; k < 4; k++) {
                    if (i == 15 && k == OARR && wg) nb_arrive(NB_STAG, 256);
                    wgmma_ss_n128_tb(acc, desc_from(alo + k * 2, DH128), desc_from(blo + k * 128, DH128), k | i);
                    if (k == OREL) {
                        if (i > 0 && i < 12) {
                            wgmma_commit();
                            wgmma_wait<1>();
                            mbar_arrive_if(elect, bars + 8 * (B_SD + i - 1));
                        }
                    }
                }
                wgmma_commit();
                if (i == 0) { TLP(tid == 0, 12); TLG(tid == 0, 51); }
                if (i == 0) {
#pragma unroll
                    for (int q = GSPLIT2; q < 8; q++) { ghr[q] = 0.5f * ldsf(sb + SM_RS + (orow + 2 * q) * 4); ghm[q] = -bf_lo(lds32(sb + SM_MD + (orow + 2 * q) * 4)) * ghr[q]; }
                }
                static_assert(2 * (8 - GSPLIT2) <= 16 - GST, "");
                if (i >= GST && GSPLIT2 + (i - GST) / 2 < 8) {
                    const int q = GSPLIT2 + (i - GST) / 2;
                    if ((i - GST) & 1) { gv[q].z = gate_pair(xv[q].z, ghr[q], ghm[q]); gv[q].w = gate_pair(xv[q].w, ghr[q], ghm[q]); asm volatile("" : "+r"(gv[q].z), "+r"(gv[q].w) :: "memory"); }
                    else { gv[q].x = gate_pair(xv[q].x, ghr[q], ghm[q]); gv[q].y = gate_pair(xv[q].y, ghr[q], ghm[q]); asm volatile("" : "+r"(gv[q].x), "+r"(gv[q].y) :: "memory"); }
                }
            }
        }
        wgmma_wait<0>();
        fence_regs(acc);
        TLP(tid == 0, 13); TLG(tid == 0, 52);
        {
            const uint32_t stg = sb + (wg * 64 + w4 * 16) * 128;
            const int rr = lane & 7;
#pragma unroll
            for (int c = 0; c < 4; c++) {
                const uint32_t a0 = stg + (c >> 1) * 16384 + rr * 128 + ((((c & 1) * 4 + (lane >> 3)) ^ rr) * 16);
                stsm(a0, pack_bf16(acc[c * 16 + 0], acc[c * 16 + 1]), pack_bf16(acc[c * 16 + 4], acc[c * 16 + 5]),
                     pack_bf16(acc[c * 16 + 8], acc[c * 16 + 9]), pack_bf16(acc[c * 16 + 12], acc[c * 16 + 13]));
                stsm(a0 + 1024, pack_bf16(acc[c * 16 + 2], acc[c * 16 + 3]), pack_bf16(acc[c * 16 + 6], acc[c * 16 + 7]),
                     pack_bf16(acc[c * 16 + 10], acc[c * 16 + 11]), pack_bf16(acc[c * 16 + 14], acc[c * 16 + 15]));
            }
            __syncwarp();
#pragma unroll
            for (int i = 0; i < 8; i++) {
                const uint4 sv = lds128(rowc + i * 256 + (((lane & 7) ^ ((2 * i + (lane >> 4)) & 7)) * 16));
                uint4 o;
                o.x = hadd2(xv[i].x, hmul2(sv.x, gv[i].x)); o.y = hadd2(xv[i].y, hmul2(sv.y, gv[i].y));
                o.z = hadd2(xv[i].z, hmul2(sv.z, gv[i].z)); o.w = hadd2(xv[i].w, hmul2(sv.w, gv[i].w));
                *reinterpret_cast<uint4*>(P.out + goff + (size_t)i * 2 * D_) = o;
            }
            const uint32_t sel = lds32(sb + SM_MISC);
            if ((int)(sel >> 4) == rb * 16 + (orow >> 4)) {
                mbar_wait(bars + 8 * B_Y, 0);
                if ((sel & 1u) == (uint32_t)(lane >> 4)) {
                    const int i = (sel & 15u) >> 1;
                    const uint4 sv = lds128(rowc + i * 256 + (((lane & 7) ^ (sel & 7u)) * 16));
                    const uint4 gq = lds128(sb + SM_Y + (lane & 15) * 16), xq = lds128(sb + SM_Y + 256 + (lane & 15) * 16);
                    *reinterpret_cast<uint4*>(P.out + goff + (size_t)i * 2 * D_) = make_uint4(hadd2(xq.x, hmul2(sv.x, gq.x)), hadd2(xq.y, hmul2(sv.y, gq.y)), hadd2(xq.z, hmul2(sv.z, gq.z)), hadd2(xq.w, hmul2(sv.w, gq.w)));
                }
            }
        }
        TLG(tid == 0, 53);
        if (tid == 0) { TL(14); TL_DUMP(); }
        if (blockIdx.x == 0 && tid == 0) asm volatile("st.relaxed.gpu.global.u32 [%0], %1;" :: "l"(&P.scr->epoch), "r"(lds32(sb + SM_MISC + 8) + 1u) : "memory");
    }
}

typedef CUresult (*PFN_encodeTiled)(CUtensorMap*, CUtensorMapDataType, cuuint32_t, void*, const cuuint64_t*, const cuuint64_t*,
                                    const cuuint32_t*, const cuuint32_t*, CUtensorMapInterleave, CUtensorMapSwizzle,
                                    CUtensorMapL2promotion, CUtensorMapFloatOOBfill);

void make_map(PFN_encodeTiled fn, CUtensorMap* m, const void* ptr, int rank, const cuuint64_t* dims, const cuuint64_t* strides, const cuuint32_t* box, CUtensorMapSwizzle sw) {
    const cuuint32_t es[5] = {1, 1, 1, 1, 1};
    fn(m, CU_TENSOR_MAP_DATA_TYPE_BFLOAT16, rank, const_cast<void*>(ptr), dims, strides, box, es, CU_TENSOR_MAP_INTERLEAVE_NONE,
       sw, CU_TENSOR_MAP_L2_PROMOTION_L2_256B, CU_TENSOR_MAP_FLOAT_OOB_FILL_NONE);
}
void make_2d(PFN_encodeTiled fn, CUtensorMap* m, const void* ptr, uint64_t rows, uint64_t cols, uint32_t box_rows, uint32_t box_cols, CUtensorMapSwizzle sw) {
    const cuuint64_t gd[2] = {cols, rows}, gs[1] = {cols * 2};
    const cuuint32_t bd[2] = {box_cols, box_rows};
    make_map(fn, m, ptr, 2, gd, gs, bd, sw);
}

}

extern "C" void kernel_launch(void* const* d_in, const int* in_sizes, int n_in, void* d_out, int out_size) {
    (void)in_sizes; (void)n_in; (void)out_size;
    static PFN_encodeTiled fn = nullptr;
    static void* o_ptr = nullptr;
    static void* scr_ptr = nullptr;
    static void* tl_ptr = nullptr;
    if (!fn) {
        void* p = nullptr;
        cudaDriverEntryPointQueryResult st;
        cudaGetDriverEntryPoint("cuTensorMapEncodeTiled", &p, cudaEnableDefault, &st);
        fn = (PFN_encodeTiled)p;
        cudaGetSymbolAddress(&o_ptr, g_o);
        cudaGetSymbolAddress(&scr_ptr, g_scr);
        cudaFuncSetAttribute(fused_kernel, cudaFuncAttributeMaxDynamicSharedMemorySize, SM_TOTAL);
    }
    CUtensorMap tmX, tmW, tmPhi, tmWo, tmO, tmX2, tmOs;
    SideMaps tmS;
    make_2d(fn, &tmX, d_in[0], S_, D_, 256, 64, CU_TENSOR_MAP_SWIZZLE_128B);
    {
        const cuuint64_t gd[3] = {1024, 1024, 3}, gs[2] = {6144, 2048};
        const cuuint32_t bd[3] = {64, 64, 3};
        make_map(fn, &tmW, d_in[1], 3, gd, gs, bd, CU_TENSOR_MAP_SWIZZLE_128B);
    }
    make_2d(fn, &tmS.wc, d_in[1], D_, 3 * D_, 32, 64, CU_TENSOR_MAP_SWIZZLE_NONE);
    make_2d(fn, &tmPhi, d_in[2], 1024, 32, 64, 32, CU_TENSOR_MAP_SWIZZLE_64B);
    make_2d(fn, &tmS.wg, d_in[6], D_, F_, 32, 32, CU_TENSOR_MAP_SWIZZLE_NONE);
    make_2d(fn, &tmS.wu, d_in[7], D_, F_, 32, 32, CU_TENSOR_MAP_SWIZZLE_NONE);
    {
        const cuuint64_t gd[3] = {64, F_, 16}, gs[2] = {2048, 128};
        const cuuint32_t bd[3] = {64, 32, 8};
        make_map(fn, &tmS.wd8, d_in[8], 3, gd, gs, bd, CU_TENSOR_MAP_SWIZZLE_128B);
    }
    {
        const cuuint64_t gd[4] = {64, 64, 16, 16}, gs[3] = {2048, 64 * 2048, 128};
        const cuuint32_t bd[4] = {64, 32, 2, 2};
        make_map(fn, &tmWo, d_in[3], 4, gd, gs, bd, CU_TENSOR_MAP_SWIZZLE_128B);
    }
    make_2d(fn, &tmO, o_ptr, S_, D_, 128, 64, CU_TENSOR_MAP_SWIZZLE_128B);
    make_2d(fn, &tmOs, o_ptr, S_, D_, 128, 32, CU_TENSOR_MAP_SWIZZLE_NONE);
    make_2d(fn, &tmX2, d_in[0], S_, D_, 128, 64, CU_TENSOR_MAP_SWIZZLE_128B);
    Params P;
    P.x = (const __nv_bfloat16*)d_in[0];
    P.wr = (const __nv_bfloat16*)d_in[5];
    P.wqkv = (const __nv_bfloat16*)d_in[1];
    P.wg = (const __nv_bfloat16*)d_in[6];
    P.wu = (const __nv_bfloat16*)d_in[7];
    P.wd = (const __nv_bfloat16*)d_in[8];
    P.wo = (const __nv_bfloat16*)d_in[3];
    P.out = (__nv_bfloat16*)d_out;
    P.scr = (Scratch*)scr_ptr;
    P.tl = (unsigned long long*)tl_ptr;
    cudaLaunchConfig_t cfg = {};
    cfg.gridDim = dim3(NCTA); cfg.blockDim = dim3(NTHREADS); cfg.dynamicSmemBytes = SM_TOTAL; cfg.stream = cudaStreamPerThread;
    cudaLaunchAttribute at[1];
    at[0].id = cudaLaunchAttributeCooperative; at[0].val.cooperative = 1;
    cfg.attrs = at; cfg.numAttrs = 1;
    cudaLaunchKernelEx(&cfg, fused_kernel, P, tmX, tmW, tmX2, tmS, tmPhi, tmWo, tmO, tmOs);
}
```

```cpp
#include <cuda_runtime.h>
#include <cuda_bf16.h>
#include <cuda.h>
#include <stdint.h>

namespace {

constexpr int S_ = 2048, D_ = 1024, F_ = 3584;
constexpr int NCTA = 128, NTHREADS = 384;
#define OREL 2
#define OSTAG 12
#define OARR 3
#define NC0 3
#define NC2 4
#define NG0 12
#define NG1 12
#define GSPLIT 0
#define GSPLIT2 2
#define GST 3
#define SARR 3
#define PFENCE 1
#define JWO 10

constexpr int STAGE = 57344;
constexpr int SM_PHI = 0;
constexpr int SM_V = 131072;
constexpr int SM_AX = 172032;
constexpr int SM_BX = 176128;
constexpr int SM_SP = 172032;
constexpr int SM_FB = 180224;
constexpr int SM_OS = 196608;
constexpr int SM_XS = 221184;
constexpr int SM_KVOP = 172032;
constexpr int SM_MD = 223232;
constexpr int SM_RS = 224256;
constexpr int SM_Y = 225280;
constexpr int SM_GU = 225536;
constexpr int SM_MISC = 226688;
constexpr int SM_H = 179200;
constexpr int SM_BARS = 226816;
constexpr int SM_WPHI = 227840;
constexpr int SM_TOTAL = 232448;

constexpr int B_FULL = 0, B_EMPTY = 3, B_OF = 6, B_SD = 22, B_O = 33, B_PHI = 35, B_T = 37, B_WPHI = 38, B_Y = 39, B_KV = 40, B_LN = 42, B_S1 = 43, B_FF = 44, B_X = 54, B_C1 = 55, B_DN = 56, B_XS = 58, B_COUNT = 59, B_XR = 59, B_OS = 60, B_PH0 = 68, B_OW = 62;
constexpr int NB_KV = 1, NB_FFN = 2, NB_AUX = 3, NB_LEAD = 4, NB_STAG = 5;
__device__ __forceinline__ int o_slot(int i) { const int r = i % 5; return r == 4 ? 10 : r; }
__device__ __forceinline__ int wo_slot(int i) { const int r = i % 7; return r == 0 ? 11 : r < 4 ? 3 + r : r == 4 ? 8 : r == 5 ? 7 : 9; }

struct __align__(128) Acc {
    float4 cs[48 * 8 * 3];
    float4 y[4 * 4 * 3 * 32];
};
constexpr int ACC_VEC_PER_CTA = (int)(sizeof(Acc) / 16 / NCTA);
static_assert(sizeof(Acc) == ACC_VEC_PER_CTA * 16 * NCTA && ACC_VEC_PER_CTA <= 32, "");
struct __align__(128) Scratch {
    Acc acc[2];
    uint4 kv[32 * 4 * 3 * 32];
    unsigned cnt_o[8 * 128];
    uint2 rows[S_];
    uint4 best[NCTA];
    unsigned epoch;
};
__device__ Scratch g_scr;
__device__ __align__(1024) __nv_bfloat16 g_o[S_ * D_];

#define TL(e) do {} while (0)
#define TLP(c, e) do {} while (0)
#define TLG(c, e) do {} while (0)
#define TL_DUMP() do {} while (0)

struct SideMaps { CUtensorMap wc, wg, wu, wd8; };
struct Params {
    const __nv_bfloat16* x;
    const __nv_bfloat16* wr;
    const __nv_bfloat16* wqkv;
    const __nv_bfloat16* wg;
    const __nv_bfloat16* wu;
    const __nv_bfloat16* wd;
    const __nv_bfloat16* wo;
    __nv_bfloat16* out;
        Scratch* scr;
    unsigned long long* tl;
};

__device__ __forceinline__ bool elect_one() {
    uint32_t p; asm volatile("{\n.reg .pred q;\nelect.sync _|q, 0xffffffff;\nselp.u32 %0, 1, 0, q;\n}" : "=r"(p)); return p;
}
__device__ __forceinline__ uint32_t smem_u32(const void* p) { return (uint32_t)__cvta_generic_to_shared(p); }
__device__ __forceinline__ void mbar_init(uint32_t bar, uint32_t cnt) { asm volatile("mbarrier.init.shared::cta.b64 [%0], %1;" :: "r"(bar), "r"(cnt) : "memory"); }
__device__ __forceinline__ void mbar_expect_tx(uint32_t bar, uint32_t bytes) { asm volatile("mbarrier.arrive.expect_tx.shared::cta.b64 _, [%0], %1;" :: "r"(bar), "r"(bytes) : "memory"); }
__device__ __forceinline__ void mbar_arrive_if(bool p, uint32_t bar) {
    asm volatile("{\n.reg .pred q;\nsetp.ne.b32 q, %1, 0;\n@q mbarrier.arrive.shared::cta.b64 _, [%0];\n}" :: "r"(bar), "r"((int)p) : "memory");
}
__device__ __forceinline__ void mbar_wait(uint32_t bar, uint32_t parity) {
    asm volatile("{\n.reg .pred p;\n.reg .u32 n;\nmov.u32 n, 0;\n"
                 "WAIT_LOOP:\nmbarrier.try_wait.parity.shared::cta.b64 p, [%0], %1;\n@p bra WAIT_DONE;\n"
                 "add.u32 n, n, 1;\nsetp.lt.u32 p, n, 0x40000;\n@p bra WAIT_LOOP;\nWAIT_DONE:\n}" :: "r"(bar), "r"(parity) : "memory");
}
__device__ __forceinline__ void tma_2d(uint32_t dst, const CUtensorMap* tm, uint32_t bar, int c0, int c1) {
    asm volatile("cp.async.bulk.tensor.2d.shared::cluster.global.mbarrier::complete_tx::bytes [%0], [%1, {%3, %4}], [%2];"
        :: "r"(dst), "l"(tm), "r"(bar), "r"(c0), "r"(c1) : "memory");
}
__device__ __forceinline__ void tma_3d(uint32_t dst, const CUtensorMap* tm, uint32_t bar, int c0, int c1, int c2) {
    asm volatile("cp.async.bulk.tensor.3d.shared::cluster.global.mbarrier::complete_tx::bytes [%0], [%1, {%3, %4, %5}], [%2];"
        :: "r"(dst), "l"(tm), "r"(bar), "r"(c0), "r"(c1), "r"(c2) : "memory");
}
__device__ __forceinline__ void tma_4d(uint32_t dst, const CUtensorMap* tm, uint32_t bar, int c0, int c1, int c2, int c3) {
    asm volatile("cp.async.bulk.tensor.4d.shared::cluster.global.mbarrier::complete_tx::bytes [%0], [%1, {%3, %4, %5, %6}], [%2];"
        :: "r"(dst), "l"(tm), "r"(bar), "r"(c0), "r"(c1), "r"(c2), "r"(c3) : "memory");
}
__device__ __forceinline__ void prefetch_l2(const void* p, uint32_t bytes) { asm volatile("cp.async.bulk.prefetch.L2.global [%0], %1;" :: "l"(p), "r"(bytes) : "memory"); }
__device__ __forceinline__ void wgmma_fence() { asm volatile("wgmma.fence.sync.aligned;" ::: "memory"); }
__device__ __forceinline__ void wgmma_commit() { asm volatile("wgmma.commit_group.sync.aligned;" ::: "memory"); }
template <int N> __device__ __forceinline__ void wgmma_wait() { asm volatile("wgmma.wait_group.sync.aligned %0;" :: "n"(N) : "memory"); }
template <int N> __device__ __forceinline__ void fence_regs(float (&a)[N]) {
#pragma unroll
    for (int i = 0; i < N; i++) asm volatile("" : "+f"(a[i]) :: "memory");
}
template <int N> __device__ __forceinline__ void fence_regs(uint32_t (&a)[N]) {
#pragma unroll
    for (int i = 0; i < N; i++) asm volatile("" : "+r"(a[i]) :: "memory");
}
__device__ __forceinline__ uint64_t desc_from(uint32_t lo, uint32_t hi) { uint64_t d; asm("mov.b64 %0, {%1, %2};" : "=l"(d) : "r"(lo), "r"(hi)); return d; }
__device__ __forceinline__ uint32_t dlo(uint32_t addr, uint32_t lbo) { return ((addr & 0x3FFFF) >> 4) | ((lbo >> 4) << 16); }
__device__ __forceinline__ void nb_sync(int id, int cnt) { asm volatile("bar.sync %0, %1;" :: "r"(id), "r"(cnt) : "memory"); }
__device__ __forceinline__ void nb_arrive(int id, int cnt) { asm volatile("bar.arrive %0, %1;" :: "r"(id), "r"(cnt) : "memory"); }
__device__ __forceinline__ void fence_async_smem() { asm volatile("fence.proxy.async.shared::cta;" ::: "memory"); }
__device__ __forceinline__ void red_v4(float4* p, float a, float b, float c, float d) {
    asm volatile("red.relaxed.gpu.global.add.v4.f32 [%0], {%1, %2, %3, %4};" :: "l"(p), "f"(a), "f"(b), "f"(c), "f"(d) : "memory");
}
__device__ __forceinline__ float4 ld_gpu(const float4* p) {
    float4 v; asm volatile("ld.relaxed.gpu.global.v4.f32 {%0, %1, %2, %3}, [%4];" : "=f"(v.x), "=f"(v.y), "=f"(v.z), "=f"(v.w) : "l"(p) : "memory"); return v;
}
__device__ __forceinline__ uint4 ld_gpu(const uint4* p) {
    uint4 v; asm volatile("ld.relaxed.gpu.global.v4.u32 {%0, %1, %2, %3}, [%4];" : "=r"(v.x), "=r"(v.y), "=r"(v.z), "=r"(v.w) : "l"(p) : "memory"); return v;
}
__device__ __forceinline__ uint32_t pack_bf16(float lo, float hi) { uint32_t r; asm("cvt.rn.bf16x2.f32 %0, %1, %2;" : "=r"(r) : "f"(hi), "f"(lo)); return r; }
__device__ __forceinline__ uint32_t pack_f16(float lo, float hi) { uint32_t r; asm("cvt.rn.f16x2.f32 %0, %1, %2;" : "=r"(r) : "f"(hi), "f"(lo)); return r; }
__device__ __forceinline__ float2 unpack_f16(uint32_t v) { float2 r; asm("{\n.reg .f16 l, h;\nmov.b32 {l, h}, %2;\ncvt.f32.f16 %0, l;\ncvt.f32.f16 %1, h;\n}" : "=f"(r.x), "=f"(r.y) : "r"(v)); return r; }
__device__ __forceinline__ float bf_lo(uint32_t v) { return __uint_as_float(v << 16); }
__device__ __forceinline__ float bf_hi(uint32_t v) { return __uint_as_float(v & 0xFFFF0000u); }
__device__ __forceinline__ float round_bf16(float v) { return bf_lo(pack_bf16(v, 0.f)); }
__device__ __forceinline__ float ex2(float v) { float r; asm("ex2.approx.ftz.f32 %0, %1;" : "=f"(r) : "f"(v)); return r; }
__device__ __forceinline__ float rcp(float v) { float r; asm("rcp.approx.ftz.f32 %0, %1;" : "=f"(r) : "f"(v)); return r; }
__device__ __forceinline__ float sqrt_a(float v) { float r; asm("sqrt.approx.f32 %0, %1;" : "=f"(r) : "f"(v)); return r; }
__device__ __forceinline__ void stsm(uint32_t addr, uint32_t r0, uint32_t r1, uint32_t r2, uint32_t r3) {
    asm volatile("stmatrix.sync.aligned.m8n8.x4.shared.b16 [%0], {%1, %2, %3, %4};" :: "r"(addr), "r"(r0), "r"(r1), "r"(r2), "r"(r3) : "memory");
}
__device__ __forceinline__ void stsm_t(uint32_t addr, uint32_t r0, uint32_t r1, uint32_t r2, uint32_t r3) {
    asm volatile("stmatrix.sync.aligned.m8n8.x4.trans.shared.b16 [%0], {%1, %2, %3, %4};" :: "r"(addr), "r"(r0), "r"(r1), "r"(r2), "r"(r3) : "memory");
}
__device__ __forceinline__ uint4 lds128(uint32_t addr) {
    uint4 v; asm volatile("ld.shared.v4.u32 {%0, %1, %2, %3}, [%4];" : "=r"(v.x), "=r"(v.y), "=r"(v.z), "=r"(v.w) : "r"(addr) : "memory"); return v;
}
__device__ __forceinline__ void sts128(uint32_t addr, uint32_t a, uint32_t b, uint32_t c, uint32_t d) {
    asm volatile("st.shared.v4.u32 [%0], {%1, %2, %3, %4};" :: "r"(addr), "r"(a), "r"(b), "r"(c), "r"(d) : "memory");
}
__device__ __forceinline__ void sts64(uint32_t addr, uint32_t a, uint32_t b) { asm volatile("st.shared.v2.u32 [%0], {%1, %2};" :: "r"(addr), "r"(a), "r"(b) : "memory"); }
__device__ __forceinline__ uint32_t lds32(uint32_t addr) { uint32_t v; asm volatile("ld.shared.u32 %0, [%1];" : "=r"(v) : "r"(addr) : "memory"); return v; }
__device__ __forceinline__ float ldsf(uint32_t addr) { return __uint_as_float(lds32(addr)); }
__device__ __forceinline__ void sts32(uint32_t addr, uint32_t v) { asm volatile("st.shared.u32 [%0], %1;" :: "r"(addr), "r"(v) : "memory"); }
__device__ __forceinline__ uint32_t hmul2(uint32_t a, uint32_t b) { uint32_t r; asm("mul.rn.bf16x2 %0, %1, %2;" : "=r"(r) : "r"(a), "r"(b)); return r; }
__device__ __forceinline__ uint32_t hadd2(uint32_t a, uint32_t b) { uint32_t r; asm("add.rn.bf16x2 %0, %1, %2;" : "=r"(r) : "r"(a), "r"(b)); return r; }
__device__ __forceinline__ uint32_t hsub2(uint32_t a, uint32_t b) { uint32_t r; asm("sub.rn.bf16x2 %0, %1, %2;" : "=r"(r) : "r"(a), "r"(b)); return r; }

__device__ __forceinline__ void wgmma_ss_n192_tb(float (&d)[96], uint64_t da, uint64_t db, int scale_d) {
    asm volatile(
        "{\n.reg .pred p;\nsetp.ne.b32 p, %98, 0;\n"
        "wgmma.mma_async.sync.aligned.m64n192k16.f32.bf16.bf16 "
        "{%0, %1, %2, %3, %4, %5, %6, %7, %8, %9, %10, %11, %12, %13, %14, %15, %16, %17, %18, %19, %20, %21, %22, %23, %24, %25, %26, %27, %28, %29, %30, %31, %32, %33, %34, %35, %36, %37, %38, %39, %40, %41, %42, %43, %44, %45, %46, %47, %48, %49, %50, %51, %52, %53, %54, %55, %56, %57, %58, %59, %60, %61, %62, %63, %64, %65, %66, %67, %68, %69, %70, %71, %72, %73, %74, %75, %76, %77, %78, %79, %80, %81, %82, %83, %84, %85, %86, %87, %88, %89, %90, %91, %92, %93, %94, %95}, %96, %97, p, 1, 1, 0, 1;\n}\n"
        : "+f"(d[0]), "+f"(d[1]), "+f"(d[2]), "+f"(d[3]), "+f"(d[4]), "+f"(d[5]), "+f"(d[6]), "+f"(d[7]), "+f"(d[8]), "+f"(d[9]), "+f"(d[10]), "+f"(d[11]), "+f"(d[12]), "+f"(d[13]), "+f"(d[14]), "+f"(d[15]), "+f"(d[16]), "+f"(d[17]), "+f"(d[18]), "+f"(d[19]), "+f"(d[20]), "+f"(d[21]), "+f"(d[22]), "+f"(d[23]), "+f"(d[24]), "+f"(d[25]), "+f"(d[26]), "+f"(d[27]), "+f"(d[28]), "+f"(d[29]), "+f"(d[30]), "+f"(d[31]), "+f"(d[32]), "+f"(d[33]), "+f"(d[34]), "+f"(d[35]), "+f"(d[36]), "+f"(d[37]), "+f"(d[38]), "+f"(d[39]), "+f"(d[40]), "+f"(d[41]), "+f"(d[42]), "+f"(d[43]), "+f"(d[44]), "+f"(d[45]), "+f"(d[46]), "+f"(d[47]), "+f"(d[48]), "+f"(d[49]), "+f"(d[50]), "+f"(d[51]), "+f"(d[52]), "+f"(d[53]), "+f"(d[54]), "+f"(d[55]), "+f"(d[56]), "+f"(d[57]), "+f"(d[58]), "+f"(d[59]), "+f"(d[60]), "+f"(d[61]), "+f"(d[62]), "+f"(d[63]), "+f"(d[64]), "+f"(d[65]), "+f"(d[66]), "+f"(d[67]), "+f"(d[68]), "+f"(d[69]), "+f"(d[70]), "+f"(d[71]), "+f"(d[72]), "+f"(d[73]), "+f"(d[74]), "+f"(d[75]), "+f"(d[76]), "+f"(d[77]), "+f"(d[78]), "+f"(d[79]), "+f"(d[80]), "+f"(d[81]), "+f"(d[82]), "+f"(d[83]), "+f"(d[84]), "+f"(d[85]), "+f"(d[86]), "+f"(d[87]), "+f"(d[88]), "+f"(d[89]), "+f"(d[90]), "+f"(d[91]), "+f"(d[92]), "+f"(d[93]), "+f"(d[94]), "+f"(d[95])
        : "l"(da), "l"(db), "r"(scale_d));
}
__device__ __forceinline__ void wgmma_ss_n128_tb(float (&d)[64], uint64_t da, uint64_t db, int scale_d) {
    asm volatile(
        "{\n.reg .pred p;\nsetp.ne.b32 p, %66, 0;\n"
        "wgmma.mma_async.sync.aligned.m64n128k16.f32.bf16.bf16 "
        "{%0, %1, %2, %3, %4, %5, %6, %7, %8, %9, %10, %11, %12, %13, %14, %15, %16, %17, %18, %19, %20, %21, %22, %23, %24, %25, %26, %27, %28, %29, %30, %31, %32, %33, %34, %35, %36, %37, %38, %39, %40, %41, %42, %43, %44, %45, %46, %47, %48, %49, %50, %51, %52, %53, %54, %55, %56, %57, %58, %59, %60, %61, %62, %63}, %64, %65, p, 1, 1, 0, 1;\n}\n"
        : "+f"(d[0]), "+f"(d[1]), "+f"(d[2]), "+f"(d[3]), "+f"(d[4]), "+f"(d[5]), "+f"(d[6]), "+f"(d[7]), "+f"(d[8]), "+f"(d[9]), "+f"(d[10]), "+f"(d[11]), "+f"(d[12]), "+f"(d[13]), "+f"(d[14]), "+f"(d[15]), "+f"(d[16]), "+f"(d[17]), "+f"(d[18]), "+f"(d[19]), "+f"(d[20]), "+f"(d[21]), "+f"(d[22]), "+f"(d[23]), "+f"(d[24]), "+f"(d[25]), "+f"(d[26]), "+f"(d[27]), "+f"(d[28]), "+f"(d[29]), "+f"(d[30]), "+f"(d[31]), "+f"(d[32]), "+f"(d[33]), "+f"(d[34]), "+f"(d[35]), "+f"(d[36]), "+f"(d[37]), "+f"(d[38]), "+f"(d[39]), "+f"(d[40]), "+f"(d[41]), "+f"(d[42]), "+f"(d[43]), "+f"(d[44]), "+f"(d[45]), "+f"(d[46]), "+f"(d[47]), "+f"(d[48]), "+f"(d[49]), "+f"(d[50]), "+f"(d[51]), "+f"(d[52]), "+f"(d[53]), "+f"(d[54]), "+f"(d[55]), "+f"(d[56]), "+f"(d[57]), "+f"(d[58]), "+f"(d[59]), "+f"(d[60]), "+f"(d[61]), "+f"(d[62]), "+f"(d[63])
        : "l"(da), "l"(db), "r"(scale_d));
}
__device__ __forceinline__ void wgmma_ss_n40(float (&d)[20], uint64_t da, uint64_t db, int scale_d) {
    asm volatile(
        "{\n.reg .pred p;\nsetp.ne.b32 p, %22, 0;\n"
        "wgmma.mma_async.sync.aligned.m64n40k16.f32.bf16.bf16 "
        "{%0, %1, %2, %3, %4, %5, %6, %7, %8, %9, %10, %11, %12, %13, %14, %15, %16, %17, %18, %19}, %20, %21, p, 1, 1, 0, 0;\n}\n"
        : "+f"(d[0]), "+f"(d[1]), "+f"(d[2]), "+f"(d[3]), "+f"(d[4]), "+f"(d[5]), "+f"(d[6]), "+f"(d[7]), "+f"(d[8]), "+f"(d[9]), "+f"(d[10]), "+f"(d[11]), "+f"(d[12]), "+f"(d[13]), "+f"(d[14]), "+f"(d[15]), "+f"(d[16]), "+f"(d[17]), "+f"(d[18]), "+f"(d[19])
        : "l"(da), "l"(db), "r"(scale_d));
}
__device__ __forceinline__ void wgmma_ss_n8_ta(float (&d)[4], uint64_t da, uint64_t db, int scale_d) {
    asm volatile(
        "{\n.reg .pred p;\nsetp.ne.b32 p, %6, 0;\n"
        "wgmma.mma_async.sync.aligned.m64n8k16.f32.bf16.bf16 "
        "{%0, %1, %2, %3}, %4, %5, p, 1, 1, 1, 0;\n}\n"
        : "+f"(d[0]), "+f"(d[1]), "+f"(d[2]), "+f"(d[3])
        : "l"(da), "l"(db), "r"(scale_d));
}
__device__ __forceinline__ void wgmma_rs_n32_tb(float (&d)[16], uint32_t a0, uint32_t a1, uint32_t a2, uint32_t a3, uint64_t db, int scale_d) {
    asm volatile(
        "{\n.reg .pred p;\nsetp.ne.b32 p, %21, 0;\n"
        "wgmma.mma_async.sync.aligned.m64n32k16.f32.bf16.bf16 "
        "{%0, %1, %2, %3, %4, %5, %6, %7, %8, %9, %10, %11, %12, %13, %14, %15}, {%16, %17, %18, %19}, %20, p, 1, 1, 1;\n}\n"
        : "+f"(d[0]), "+f"(d[1]), "+f"(d[2]), "+f"(d[3]), "+f"(d[4]), "+f"(d[5]), "+f"(d[6]), "+f"(d[7]), "+f"(d[8]), "+f"(d[9]), "+f"(d[10]), "+f"(d[11]), "+f"(d[12]), "+f"(d[13]), "+f"(d[14]), "+f"(d[15])
        : "r"(a0), "r"(a1), "r"(a2), "r"(a3), "l"(db), "r"(scale_d));
}
__device__ __forceinline__ void wgmma_rs_n40_tb(float (&d)[20], uint32_t a0, uint32_t a1, uint32_t a2, uint32_t a3, uint64_t db, int scale_d) {
    asm volatile(
        "{\n.reg .pred p;\nsetp.ne.b32 p, %25, 0;\n"
        "wgmma.mma_async.sync.aligned.m64n40k16.f32.bf16.bf16 "
        "{%0, %1, %2, %3, %4, %5, %6, %7, %8, %9, %10, %11, %12, %13, %14, %15, %16, %17, %18, %19}, {%20, %21, %22, %23}, %24, p, 1, 1, 1;\n}\n"
        : "+f"(d[0]), "+f"(d[1]), "+f"(d[2]), "+f"(d[3]), "+f"(d[4]), "+f"(d[5]), "+f"(d[6]), "+f"(d[7]), "+f"(d[8]), "+f"(d[9]), "+f"(d[10]), "+f"(d[11]), "+f"(d[12]), "+f"(d[13]), "+f"(d[14]), "+f"(d[15]), "+f"(d[16]), "+f"(d[17]), "+f"(d[18]), "+f"(d[19])
        : "r"(a0), "r"(a1), "r"(a2), "r"(a3), "l"(db), "r"(scale_d));
}

constexpr float LOG2E = 1.4426950408889634f;
constexpr uint32_t DH128 = (1024u >> 4) | (1u << 30);

__device__ __forceinline__ float silu_f(float v) { return v * rcp(1.0f + ex2(-v * LOG2E)); }
__device__ __forceinline__ float silu_t(float v) { const float h = 0.5f * v; float th; asm("tanh.approx.f32 %0, %1;" : "=f"(th) : "f"(h)); return fmaf(h, th, h); }
__device__ __forceinline__ uint32_t ln_pair(uint32_t xv, uint32_t m2, float rs) { const uint32_t a = hsub2(xv, m2); return pack_bf16(bf_lo(a) * rs, bf_hi(a) * rs); }
__device__ __forceinline__ uint32_t silu_pair(uint32_t v) { return pack_bf16(silu_t(bf_lo(v)), silu_t(bf_hi(v))); }
__device__ __forceinline__ uint32_t gate_pair(uint32_t v, float hr, float hm) {
    const float a = fmaf(bf_lo(v), hr, hm), b = fmaf(bf_hi(v), hr, hm);
    float ta, tb;
    asm("tanh.approx.f32 %0, %1;" : "=f"(ta) : "f"(a)); asm("tanh.approx.f32 %0, %1;" : "=f"(tb) : "f"(b));
    return pack_bf16(fmaf(a, ta, a), fmaf(b, tb, b));
}
__device__ __forceinline__ void gate_item(uint4& v, uint32_t sb, int row) {
    const float hr = 0.5f * ldsf(sb + SM_RS + row * 4), hm = -bf_lo(lds32(sb + SM_MD + row * 4)) * hr;
    v.x = gate_pair(v.x, hr, hm); v.y = gate_pair(v.y, hr, hm); v.z = gate_pair(v.z, hr, hm); v.w = gate_pair(v.w, hr, hm);
    asm volatile("" : "+r"(v.x), "+r"(v.y), "+r"(v.z), "+r"(v.w) :: "memory");
}
__device__ __forceinline__ uint32_t hfma2(uint32_t a, uint32_t b, uint32_t c) { uint32_t r; asm("fma.rn.bf16x2 %0, %1, %2, %3;" : "=r"(r) : "r"(a), "r"(b), "r"(c)); return r; }
__device__ __forceinline__ uint32_t dup_lo(uint32_t v) { uint32_t r; asm("{\n.reg .b16 l, h;\nmov.b32 {l, h}, %1;\nmov.b32 %0, {l, l};\n}" : "=r"(r) : "r"(v)); return r; }
__device__ __forceinline__ uint32_t dup_hi(uint32_t v) { uint32_t r; asm("{\n.reg .b16 l, h;\nmov.b32 {l, h}, %1;\nmov.b32 %0, {h, h};\n}" : "=r"(r) : "r"(v)); return r; }
template <bool SQ> __device__ __forceinline__ void colsum8(float (&a)[8], float& sq, const uint4 (&v)[8]) {
    uint32_t q = 0;
#pragma unroll
    for (int i = 0; i < 8; i++) {
        a[0] += bf_lo(v[i].x); a[1] += bf_hi(v[i].x); a[2] += bf_lo(v[i].y); a[3] += bf_hi(v[i].y);
        a[4] += bf_lo(v[i].z); a[5] += bf_hi(v[i].z); a[6] += bf_lo(v[i].w); a[7] += bf_hi(v[i].w);
        if (SQ) q = hfma2(v[i].x, v[i].x, hfma2(v[i].y, v[i].y, hfma2(v[i].z, v[i].z, hfma2(v[i].w, v[i].w, q))));
    }
    if (SQ) sq += bf_lo(q) + bf_hi(q);
}
__device__ __forceinline__ void hfma8(uint4& h, uint32_t w, const uint4& v) { h.x = hfma2(v.x, w, h.x); h.y = hfma2(v.y, w, h.y); h.z = hfma2(v.z, w, h.z); h.w = hfma2(v.w, w, h.w); }
template <int ST, class F>
__device__ __forceinline__ void gemv_run(float (&a)[8], int cnt, int b, uint32_t ph, uint32_t lo, uint32_t wa, uint32_t ws, uint32_t bar0, uint32_t pin, F done) {
    uint32_t rdy = 0;
#pragma unroll 1
    for (int m = 0; m < cnt; m++) {
        if (!rdy) mbar_wait(bar0 + b * 8, ph);
        uint4 A[8];
        const uint4 w = lds128(wa);
#pragma unroll
        for (int i = 0; i < 8; i++) A[i] = lds128(lo + b * 4096 + i * ST);
        const int bc = b;
        if (++b == 3) { b = 0; ph ^= 1; }
        asm volatile("{\n.reg .pred p;\nmbarrier.test_wait.parity.shared::cta.b64 p, [%1], %2;\nselp.u32 %0, 1, 0, p;\n}" : "=r"(rdy) : "r"(bar0 + b * 8), "r"(ph) : "memory");
        sts32(pin, 0u);
        wa += ws;
        uint4 h = make_uint4(0, 0, 0, 0);
        hfma8(h, dup_lo(w.x), A[0]); hfma8(h, dup_hi(w.x), A[1]); hfma8(h, dup_lo(w.y), A[2]); hfma8(h, dup_hi(w.y), A[3]);
        hfma8(h, dup_lo(w.z), A[4]); hfma8(h, dup_hi(w.z), A[5]); hfma8(h, dup_lo(w.w), A[6]); hfma8(h, dup_hi(w.w), A[7]);
        a[0] += bf_lo(h.x); a[1] += bf_hi(h.x); a[2] += bf_lo(h.y); a[3] += bf_hi(h.y);
        a[4] += bf_lo(h.z); a[5] += bf_hi(h.z); a[6] += bf_lo(h.w); a[7] += bf_hi(h.w);
        fence_regs(a);
        done(m, bc);
    }
}
template <int OFF> __device__ __forceinline__ void pack_head(const float (&acc)[96], uint32_t (&f)[8]) {
#pragma unroll
    for (int i = 0; i < 8; i++) f[i] = pack_bf16(acc[OFF + 2 * i], acc[OFF + 2 * i + 1]);
}
__device__ __forceinline__ void feat_mma(float (&p)[16], const uint32_t (&f)[8], uint32_t wlo) {
    constexpr uint32_t DH = (512u >> 4) | (2u << 30);
    wgmma_rs_n32_tb(p, f[0], f[1], f[2], f[3], desc_from(wlo, DH), 0);
    wgmma_rs_n32_tb(p, f[4], f[5], f[6], f[7], desc_from(wlo + 64, DH), 1);
}
template <int S> __device__ __forceinline__ void row_ext(const float (&p)[16], float& a, float& b) {
    auto op = [](float x, float y) { return S > 0 ? fmaxf(x, y) : fminf(x, y); };
    a = op(op(op(p[0], p[1]), op(p[4], p[5])), op(op(p[8], p[9]), op(p[12], p[13])));
    b = op(op(op(p[2], p[3]), op(p[6], p[7])), op(op(p[10], p[11]), op(p[14], p[15])));
#pragma unroll
    for (int o = 1; o <= 2; o <<= 1) { a = op(a, __shfl_xor_sync(0xffffffffu, a, o)); b = op(b, __shfl_xor_sync(0xffffffffu, b, o)); }
}
__device__ __forceinline__ void dual_exp(const float (&p)[16], float scA, float scB, uint32_t (&pos)[8], uint32_t (&neg)[8], uint32_t& chk) {
#pragma unroll
    for (int j = 0; j < 8; j += 2) {
        const float a0 = ex2(p[2 * j] * scA), a1 = ex2(p[2 * j + 1] * scA);
        const float b0 = ex2(p[2 * j + 2] * scB), b1 = ex2(p[2 * j + 3] * scB);
        const float pa = a0 * a1, pb = b0 * b1, R = rcp(pa * pb);
        const uint32_t r = pack_bf16(R * pb, R * pa);
        pos[j] = pack_bf16(a0, a1); pos[j + 1] = pack_bf16(b0, b1);
        neg[j] = hmul2(pos[j], dup_lo(r)); neg[j + 1] = hmul2(pos[j + 1], dup_hi(r));
        chk = hadd2(chk, hadd2(hadd2(pos[j], neg[j]), hadd2(pos[j + 1], neg[j + 1])));
    }
}
template <int S> __device__ __forceinline__ void exact_exp(const float (&p)[16], float scA, float scB, uint32_t (&o)[8]) {
    float mA, mB;
    row_ext<S>(p, mA, mB);
#pragma unroll
    for (int j = 0; j < 8; j++) {
        const float sc = S * ((j & 1) ? scB : scA), m = (j & 1) ? mB : mA;
        const float u = ex2((p[2 * j] - m) * sc), v = ex2((p[2 * j + 1] - m) * sc);
        o[j] = S > 0 ? pack_bf16(u, v) : pack_bf16(v, u);
    }
}
__device__ __forceinline__ void features(const float (&p0)[16], const float (&p1)[16], const float (&rs)[4],
                                         uint32_t (&pa)[8], uint32_t (&na)[8], uint32_t (&pb)[8], uint32_t (&nb)[8]) {
    uint32_t chk = 0;
    dual_exp(p0, rs[0] * LOG2E, rs[1] * LOG2E, pa, na, chk);
    dual_exp(p1, rs[2] * LOG2E, rs[3] * LOG2E, pb, nb, chk);
    if (__builtin_expect(!__all_sync(0xffffffffu, bf_lo(chk) + bf_hi(chk) < 1.0e9f), 0)) {
        exact_exp<1>(p0, rs[0] * LOG2E, rs[1] * LOG2E, pa); exact_exp<-1>(p0, rs[0] * LOG2E, rs[1] * LOG2E, na);
        exact_exp<1>(p1, rs[2] * LOG2E, rs[3] * LOG2E, pb); exact_exp<-1>(p1, rs[2] * LOG2E, rs[3] * LOG2E, nb);
    }
}
__device__ __forceinline__ float quad_sum(float v) { v += __shfl_xor_sync(0xffffffffu, v, 1); return v + __shfl_xor_sync(0xffffffffu, v, 2); }
__device__ __forceinline__ float key_block(const float (&p)[16], float rsA, float rsB, uint32_t d0, uint32_t d1, uint32_t off) {
    float r[8], sp[2], sn[2];
    uint32_t pos[8], neg[8];
    const float scA = rsA * LOG2E, scB = rsB * LOG2E;
#pragma unroll
    for (int j = 0; j < 8; j += 2) {
        const float a0 = ex2(p[2 * j] * scA), a1 = ex2(p[2 * j + 1] * scA);
        const float b0 = ex2(p[2 * j + 2] * scB), b1 = ex2(p[2 * j + 3] * scB);
        const float pa = a0 * a1, pb = b0 * b1, R = rcp(pa * pb), ta = a0 + a1, tb = b0 + b1;
        r[j] = R * pb; r[j + 1] = R * pa;
        if (j == 0) { sp[0] = ta; sp[1] = tb; sn[0] = r[0] * ta; sn[1] = r[1] * tb; }
        else { sp[0] += ta; sp[1] += tb; sn[0] = fmaf(r[j], ta, sn[0]); sn[1] = fmaf(r[j + 1], tb, sn[1]); }
        pos[j] = pack_bf16(a0, a1); pos[j + 1] = pack_bf16(b0, b1);
    }
    const float qa = quad_sum(sp[0]), qb = quad_sum(sp[1]), na = quad_sum(sn[0]), nb = quad_sum(sn[1]);
    const float iq = rcp(qa * qb), nA = rsA * rcp(na), nB = rsB * rcp(nb);
    const uint32_t fp = pack_bf16(rsA * qb * iq, rsB * qa * iq);
#pragma unroll
    for (int j = 0; j < 8; j += 2) {
        const uint32_t rn = pack_bf16(r[j] * nA, r[j + 1] * nB);
        neg[j] = hmul2(pos[j], dup_lo(rn)); neg[j + 1] = hmul2(pos[j + 1], dup_hi(rn));
        pos[j] = hmul2(pos[j], dup_lo(fp)); pos[j + 1] = hmul2(pos[j + 1], dup_hi(fp));
    }
    stsm_t(d0 + 4096, neg[0], neg[2], neg[4], neg[6]); stsm_t(d1 + 4096, neg[1], neg[3], neg[5], neg[7]);
    stsm_t(d0 + off, pos[0], pos[2], pos[4], pos[6]); stsm_t(d1 + off, pos[1], pos[3], pos[5], pos[7]);
    return (qa + qb) + (na + nb);
}
__device__ __forceinline__ void shift_max(float (&p)[16]) {
    float mA, mB;
    row_ext<1>(p, mA, mB);
#pragma unroll
    for (int j = 0; j < 16; j++) p[j] -= (j & 2) ? mB : mA;
}
__device__ __forceinline__ void key_head(float (&p0)[16], float (&p1)[16], const float (&rs)[4], uint32_t d0, uint32_t d1) {
    uint32_t st;
    asm volatile("mov.u32 %0, 0;" : "=r"(st));
    bool again;
#pragma unroll 1
    do {
        const uint32_t off = (st & 2u) << 11;
        const float chk = key_block(p0, rs[0], rs[1], d0, d1, off) + key_block(p1, rs[2], rs[3], d0 + 8192, d1 + 8192, off);
        again = st == 1u || (st == 0u && !__all_sync(0xffffffffu, chk < 1.0e9f));
        if (__builtin_expect(again, 0)) {
            if (st) {
#pragma unroll
                for (int j = 0; j < 16; j += 2) {
                    float t = p0[j]; p0[j] = -p0[j + 1]; p0[j + 1] = -t;
                    t = p1[j]; p1[j] = -p1[j + 1]; p1[j + 1] = -t;
                }
            }
            shift_max(p0); shift_max(p1);
            st++;
        }
        asm volatile("" ::: "memory");
    } while (again);
}
__device__ __forceinline__ void o_mma(float (&d)[20], float (&e)[20], const uint32_t (&pos)[8], const uint32_t (&neg)[8], uint32_t klo) {
    wgmma_rs_n40_tb(d, pos[0], pos[1], pos[2], pos[3], desc_from(klo, 1024u >> 4), 0);
    wgmma_rs_n40_tb(e, neg[0], neg[1], neg[2], neg[3], desc_from(klo + 32, 1024u >> 4), 0);
    wgmma_rs_n40_tb(d, pos[4], pos[5], pos[6], pos[7], desc_from(klo + 16, 1024u >> 4), 1);
    wgmma_rs_n40_tb(e, neg[4], neg[5], neg[6], neg[7], desc_from(klo + 48, 1024u >> 4), 1);
}
__device__ __forceinline__ void o_store(const float (&d)[20], const float (&e)[20], uint32_t dst) {
    const float iA = rcp(fmaf(d[16], e[17], fmaf(e[16], d[17], 1e-6f * d[17] * e[17])));
    const float iB = rcp(fmaf(d[18], e[19], fmaf(e[18], d[19], 1e-6f * d[19] * e[19])));
    const float pA = e[17] * iA, nA = d[17] * iA, pB = e[19] * iB, nB = d[19] * iB;
    uint32_t oa[4], ob[4];
#pragma unroll
    for (int j = 0; j < 4; j++) {
        oa[j] = pack_bf16(fmaf(d[j * 4], pA, e[j * 4] * nA), fmaf(d[j * 4 + 1], pA, e[j * 4 + 1] * nA));
        ob[j] = pack_bf16(fmaf(d[j * 4 + 2], pB, e[j * 4 + 2] * nB), fmaf(d[j * 4 + 3], pB, e[j * 4 + 3] * nB));
    }
    sts128(dst, oa[0], oa[1], oa[2], oa[3]);
    sts128(dst + 512, ob[0], ob[1], ob[2], ob[3]);
}

template <int N> __device__ __forceinline__ void kv_gather(uint4 (&v)[3 * N], const uint4* src, uint32_t dst, int lane, float us) {
    unsigned it = 0;
#pragma unroll 1
    while (++it < (1u << 20)) {
        bool ok = true;
#pragma unroll
        for (int j = 0; j < 3 * N; j++) ok = ok && (v[j].w >> 16) == 0x4800u;
        if (__all_sync(0xffffffffu, ok)) break;
#pragma unroll
        for (int j = 0; j < 3 * N; j++) v[j] = ld_gpu(src + j * 32);
    }
    dst += (lane >> 2) * 16;
    auto cv = [&](uint32_t w) { const float2 f = unpack_f16(w); return pack_bf16(f.x * us, f.y * us); };
#pragma unroll
    for (int n = 0; n < N; n++) {
        sts128(dst + (lane & 3) * 1024 + n * 256, cv(v[3 * n].x), cv(v[3 * n].y), cv(v[3 * n].z), cv(v[3 * n + 2].x));
        sts128(dst + (lane & 3) * 1024 + n * 256 + 128, cv(v[3 * n + 1].x), cv(v[3 * n + 1].y), cv(v[3 * n + 1].z), cv(v[3 * n + 2].y));
        sts32(dst + 4096 + n * 256 + (lane & 3) * 4, pack_bf16(unpack_f16(v[3 * n].w).x, 1.0f));
        sts32(dst + 4096 + n * 256 + 128 + (lane & 3) * 4, pack_bf16(unpack_f16(v[3 * n + 1].w).x, 1.0f));
    }
    fence_async_smem();
    __syncwarp();
}

__global__ void __launch_bounds__(NTHREADS, 1)
fused_kernel(const Params P, const __grid_constant__ CUtensorMap tmX, const __grid_constant__ CUtensorMap tmW, const __grid_constant__ CUtensorMap tmX2,
             const __grid_constant__ SideMaps tmS, const __grid_constant__ CUtensorMap tmPhi,
             const __grid_constant__ CUtensorMap tmWo, const __grid_constant__ CUtensorMap tmO, const __grid_constant__ CUtensorMap tmOs) {
    extern __shared__ __align__(1024) uint8_t smem_raw[];
    constexpr uint32_t sb = 1024;
    if (smem_u32(smem_raw) != sb) return;
    constexpr uint32_t bars = sb + SM_BARS;
    const int rb = blockIdx.x >> 4, hp = blockIdx.x & 15;
    TLP(threadIdx.x == 32, 0); TLG(threadIdx.x == 32, 48);
    auto load_stage = [&](int s, int ks) {
        mbar_expect_tx(bars + 8 * (B_FULL + s), STAGE);
        tma_2d(sb + s * STAGE, &tmX, bars + 8 * (B_FULL + s), ks * 64, rb * 256);
        tma_3d(sb + s * STAGE + 32768, &tmW, bars + 8 * (B_FULL + s), hp * 64, ks * 64, 0);
    };
    if (threadIdx.x < 256) {
        const uint32_t t = threadIdx.x, r = t >> 3, sw = ((t ^ r) & 7) * 16;
        const __nv_bfloat16* wp = P.wqkv + (size_t)r * 3 * D_ + hp * 64 + (t & 7) * 8;
        const __nv_bfloat16* xp = P.x + (size_t)(rb * 256 + (t >> 7) * 128 + (r & 15)) * D_ + (t & 7) * 8;
#pragma unroll
        for (int i = 0; i < 3; i++) asm volatile("cp.async.cg.shared.global [%0], [%1], 16;" :: "r"(sb + 32768 + i * 8192 + r * 128 + sw), "l"(wp + i * D_) : "memory");
#pragma unroll
        for (int i = 0; i < 8; i++) asm volatile("cp.async.cg.shared.global [%0], [%1], 16;" :: "r"(sb + (t >> 7) * 16384 + ((r & 15) + i * 16) * 128 + sw), "l"(xp + i * 16 * D_) : "memory");
        asm volatile("cp.async.commit_group;" ::: "memory");
#pragma unroll
        for (int i = 0; i < 3; i++) asm volatile("cp.async.cg.shared.global [%0], [%1], 16;" :: "r"(sb + 36864 + i * 8192 + r * 128 + sw), "l"(wp + 96 * D_ + i * D_) : "memory");
        asm volatile("cp.async.commit_group;" ::: "memory");
    }
    const int tid = threadIdx.x, warp = __shfl_sync(0xffffffffu, tid >> 5, 0), lane = tid & 31;
    const bool elect = lane == 0;

    if (warp >= 8) {
        const int aw = warp - 9;
        auto load_o = [&](int i) {
            mbar_expect_tx(bars + 8 * (B_OF + i), 16384);
            tma_2d(sb + o_slot(i) * 16384, &tmO, bars + 8 * (B_OF + i), i * 64, rb * 256 + (hp & 1) * 128);
        };
        auto load_wo = [&](int i) {
            mbar_expect_tx(bars + 8 * (B_OF + i), 16384);
            tma_4d(sb + wo_slot(i) * 16384, &tmWo, bars + 8 * (B_OF + i), 0, (i >> 3) * 32, (i & 7) * 2, hp & 14);
        };
        if (warp == 9) {
            if (elect_one()) {
#pragma unroll
                for (int i = B_OF; i < B_COUNT; i++)
                    mbar_init(bars + 8 * i, i < B_SD ? 2 : (i < B_WPHI ? 8 : ((i < B_KV || i >= B_FF || i == B_LN) ? 1 : 4)));
                mbar_init(bars + 8 * B_OS, 1); mbar_init(bars + 8 * B_PH0, 4); mbar_init(bars + 8 * B_PH0 + 8, 4); mbar_init(bars + 8 * B_OS + 8, 1);
#pragma unroll
                for (int i = 0; i < 4; i++) mbar_init(bars + 8 * (B_OW + i), 4);
                asm volatile("fence.mbarrier_init.release.cluster;" ::: "memory");
            }
        }
        if (warp == 8) {
            if (elect_one()) {
#pragma unroll
                for (int i = 0; i < 3; i++) { mbar_init(bars + 8 * (B_FULL + i), 1); mbar_init(bars + 8 * (B_EMPTY + i), 8); }
                mbar_init(bars + 8 * B_XR, 1);
                asm volatile("fence.mbarrier_init.release.cluster;" ::: "memory");
                asm volatile("mbarrier.arrive.shared::cta.b64 _, [%0];" :: "r"(bars + 8 * B_FULL) : "memory");
            }
            __syncwarp();
            nb_arrive(0, NTHREADS);
        } else {
            __syncwarp();
            nb_sync(0, NTHREADS);
        }
        asm volatile("setmaxnreg.dec.sync.aligned.u32 56;");
        if (warp == 8 && elect_one()) {
            load_stage(1, 1); load_stage(2, 2);
            mbar_expect_tx(bars + 8 * B_XR, 32768);
            asm volatile("cp.async.bulk.shared::cluster.global.mbarrier::complete_tx::bytes [%0], [%1], 32768, [%2];"
                         :: "r"(sb + SM_FB + 4096), "l"(P.x + (size_t)blockIdx.x * 16 * D_), "r"(bars + 8 * B_XR) : "memory");
        }
        __syncwarp();
        nb_sync(NB_KV, 128);
        unsigned epoch;
        asm volatile("ld.relaxed.gpu.global.u32 %0, [%1];" : "=r"(epoch) : "l"(&P.scr->epoch) : "memory");
        auto get_acc = [&]() { return &P.scr->acc[epoch & 1u]; };
        if (warp == 8) {
            epoch = __shfl_sync(0xffffffffu, epoch, 0);
            int s = 0, ph = 0;
#pragma unroll 1
            for (int j = 0; j < 15; j++) {
                mbar_wait(bars + 8 * (B_EMPTY + s), ph);
                if (elect_one()) {
                    if (j < 13) load_stage(s, j + 3);
                    if (j < 2) {
                        prefetch_l2(P.wqkv + (size_t)(256 + j * 384 + blockIdx.x * 3) * 3 * D_, 18432);
                    } else if (j < 10) {
                        if (j == 2) asm volatile("mbarrier.arrive.shared::cta.b64 _, [%0];" :: "r"(bars + 8 * B_FF) : "memory");
                        const size_t o = (size_t)((j - 2) * 128 + blockIdx.x) * F_;
                        prefetch_l2(P.wg + o, F_ * 2); prefetch_l2(P.wu + o, F_ * 2);
                    }
                    if (j == JWO) prefetch_l2(P.wo + (size_t)blockIdx.x * 8 * D_, 16384);
                    if (j == 12) {
                        asm volatile("prefetch.tensormap [%0];" :: "l"(&tmO) : "memory");
                        asm volatile("prefetch.tensormap [%0];" :: "l"(&tmOs) : "memory");
                        asm volatile("prefetch.tensormap [%0];" :: "l"(&tmS.wd8) : "memory");
                        asm volatile("prefetch.tensormap [%0];" :: "l"(&tmWo) : "memory");
                        mbar_expect_tx(bars + 8 * B_WPHI, 4096);
                        tma_2d(sb + SM_WPHI, &tmPhi, bars + 8 * B_WPHI, 0, hp * 64);
                    }
                    if (j >= 13) {
                        if (blockIdx.x >= 112) { if (j == 13) { load_wo(1); load_wo(2); } else { load_wo(3); load_wo(5); } }
                        else {
                            mbar_expect_tx(bars + 8 * (B_DN + j - 13), 32768);
                            tma_3d(sb + (2 * j - 22) * 16384, &tmS.wd8, bars + 8 * (B_DN + j - 13), 0, blockIdx.x * 32, (j - 13) * 8);
                        }
                    }
                }
                __syncwarp();
                if (++s == 3) { s = 0; ph ^= 1; }
                if (j == 3 && lane < ACC_VEC_PER_CTA) reinterpret_cast<uint4*>(&P.scr->acc[~epoch & 1u])[blockIdx.x * ACC_VEC_PER_CTA + lane] = make_uint4(0, 0, 0, 0);
            }
            TLP(elect, 20);
        } else {
            const bool ffn = blockIdx.x < 112;
            const uint32_t fbuf = sb + SM_FB + 4096 + aw * 12288, fbar = bars + 8 * (B_FF + 1 + aw * 3);
        const int nc = aw == 0 ? NC0 : (aw == 1 ? 12 - NC0 - NC2 : NC2), c0 = aw == 0 ? 0 : (aw == 1 ? NC0 : 12 - NC2);
        const int ng = !ffn ? 0 : (aw == 0 ? NG0 : (aw == 1 ? NG1 : 32 - NG0 - NG1)), g0 = aw == 0 ? 0 : (aw == 1 ? NG0 : NG0 + NG1);
        auto issue = [&](int i, int b) {
            __syncwarp();
            if (i < nc + ng && elect_one()) {
                mbar_expect_tx(fbar + b * 8, 4096);
                if (i < nc) {
                    tma_2d(fbuf + b * 4096, &tmS.wc, fbar + b * 8, ((c0 + i) >> 2) * 1024 + hp * 64, rb * 128 + ((c0 + i) & 3) * 32);
                } else {
                    tma_2d(fbuf + b * 4096, &tmS.wg, fbar + b * 8, blockIdx.x * 32, (g0 + i - nc) * 32);
                    tma_2d(fbuf + b * 4096 + 2048, &tmS.wu, fbar + b * 8, blockIdx.x * 32, (g0 + i - nc) * 32);
                }
            }
            __syncwarp();
        };
            {
                uint4 wv[4];
#pragma unroll
                for (int i = 0; i < 4; i++) wv[i] = __ldg(reinterpret_cast<const uint4*>(P.wr) + i * 32 + lane);
                const uint32_t* ww = reinterpret_cast<const uint32_t*>(wv);
                float sw = 0.f;
#pragma unroll
                for (int i = 0; i < 16; i++) sw += bf_lo(ww[i]) + bf_hi(ww[i]);
#pragma unroll 1
                for (int o = 16; o > 0; o >>= 1) sw += __shfl_xor_sync(0xffffffffu, sw, o);
                sts32(sb + SM_MISC + 20, __float_as_uint(sw));
                if (aw == 2) {
#pragma unroll
                    for (int i = 0; i < 3; i++) P.scr->kv[(hp * 8 + rb) * 96 + i * 32 + lane] = make_uint4(0, 0, 0, 0);
                    if (hp == 0) reinterpret_cast<uint4*>(&P.scr->cnt_o[rb * 128])[lane] = make_uint4(0, 0, 0, 0);
                    asm volatile("fence.acq_rel.gpu;" ::: "memory");
                    __syncwarp();
                }
                mbar_wait(bars + 8 * B_XR, 0);
#pragma unroll 1
                for (int r = aw * 6; r < min(aw * 6 + 6, 16); r++) {
                    const uint32_t buf = sb + SM_FB + 4096 + r * 2048;
                    uint4 xv[4];
                    uint32_t c2 = lds32(buf);
#pragma unroll
                    for (int i = 0; i < 4; i++) xv[i] = lds128(buf + i * 512 + lane * 16);
                    sts32(sb + SM_MISC + 12, 0u);
                    c2 = fabsf(bf_lo(c2) - bf_hi(c2)) < 0.25f * fabsf(bf_lo(c2)) ? dup_lo(c2) : 0u;
                    const uint32_t* xw = reinterpret_cast<const uint32_t*>(xv);
                    uint32_t d2[2] = {0u, 0u};
                    float s0 = 0.f, s1 = 0.f, q0 = 0.f, q1 = 0.f;
#pragma unroll
                    for (int i = 0; i < 16; i++) {
                        const uint32_t a = hsub2(xw[i], c2);
                        s0 += bf_lo(a); s1 += bf_hi(a);
                        d2[i & 1] = hfma2(a, ww[i], d2[i & 1]);
                        q0 = fmaf(bf_lo(a), bf_lo(a), q0); q1 = fmaf(bf_hi(a), bf_hi(a), q1);
                    }
                    sts128(sb + SM_SP + r * 512 + lane * 16, __float_as_uint(s0 + s1), __float_as_uint(q0 + q1),
                           __float_as_uint((bf_lo(d2[0]) + bf_hi(d2[0])) + (bf_lo(d2[1]) + bf_hi(d2[1]))), c2 << 16);
                }
                epoch = __shfl_sync(0xffffffffu, epoch, 0);
                if (aw < 2) nb_arrive(NB_FFN, 96);
                mbar_wait(bars + 8 * B_FF, 0);
#pragma unroll 1
                for (int i = 0; i < 3; i++) issue(i, i);
                const unsigned tag = epoch + 1u;
                if (aw == 2) {
                    nb_sync(NB_FFN, 96);
                    TLP(elect, 23);
                    float s = 0.f, q = 0.f, dt = 0.f, x0;
#pragma unroll 8
                    for (int j = 0; j < 16; j++) {
                        const uint4 e = lds128(sb + SM_SP + lane * 256 + ((j + lane) & 15) * 16);
                        s += __uint_as_float(e.x); q += __uint_as_float(e.y); dt += __uint_as_float(e.z); x0 = __uint_as_float(e.w);
                    }
                    s += __shfl_xor_sync(0xffffffffu, s, 1); q += __shfl_xor_sync(0xffffffffu, q, 1); dt += __shfl_xor_sync(0xffffffffu, dt, 1);
                    const float ms = s * (1.0f / D_);
                    const float vb = round_bf16(fmaxf(q - s * ms, 0.f) * (1.0f / D_));
                    const uint32_t md = pack_bf16(x0 + ms, sqrt_a(round_bf16(vb + 1e-5f)));
                    const uint32_t rbits = pack_bf16((dt - (bf_lo(md) - x0) * ldsf(sb + SM_MISC + 20)) * rcp(bf_hi(md)), 0.f);
                    const int row = blockIdx.x * 16 + (lane >> 1);
                    const uint32_t key = ((((rbits & 0x8000u) ? (~rbits & 0xFFFFu) : (rbits | 0x8000u)) + 1u) << 11) | (uint32_t)(2047 - row);
                    asm volatile("st.relaxed.gpu.global.v2.u32 [%0], {%1, %2};" :: "l"(&P.scr->rows[row]), "r"(md), "r"(tag) : "memory");
                    if (key == __reduce_max_sync(0xffffffffu, key))
                        asm volatile("st.relaxed.gpu.global.v4.u32 [%0], {%1, %2, %3, %3};" :: "l"(&P.scr->best[blockIdx.x]), "r"(key), "r"(md), "r"(tag) : "memory");
                    TLP(elect, 24);
                }
                {
                    float a[8], sq = 0.f, wt = 0.f;
#pragma unroll
                    for (int i = 0; i < 8; i++) a[i] = 0.f;
#pragma unroll 1
                    for (int m = 0; m < nc; m++) {
                        const int b = m % 3, c = c0 + m;
                        mbar_wait(fbar + b * 8, (m / 3) & 1);
                        uint4 v[8];
#pragma unroll
                        for (int i = 0; i < 8; i++) v[i] = lds128(fbuf + b * 4096 + i * 512 + lane * 16);
                        sts32(sb + SM_MISC + 12, 0u);
                        colsum8<true>(a, sq, v);
                        fence_regs(a);
                        wt += 1.0f;
                        issue(m + 3, b);
                        if ((c & 3) == 3 || m == nc - 1) {
#pragma unroll 1
                            for (int o = 8; o <= 16; o <<= 1) {
#pragma unroll
                                for (int i = 0; i < 8; i++) a[i] += __shfl_xor_sync(0xffffffffu, a[i], o);
                                sq += __shfl_xor_sync(0xffffffffu, sq, o);
                            }
                            float4* dst = &get_acc()->cs[((c >> 2) * 16 + hp) * 24 + lane];
                            if (lane < 8) { red_v4(dst, a[0], a[1], a[2], wt); red_v4(dst + 8, a[3], a[4], a[5], wt); red_v4(dst + 16, a[6], a[7], sq, wt); }
#pragma unroll
                            for (int i = 0; i < 8; i++) a[i] = 0.f;
                            wt = 0.f;
                        }
                    }
                    TLP(tid == 288, 26); TLP(tid == 320, 15); TLP(tid == 352, 22);
                }
                if (aw == 0) {
                    uint4 v[4];
                    unsigned it = 0;
                    bool ok = true;
#pragma unroll 1
                    do {
                        if (!ok) __nanosleep(200);
#pragma unroll
                        for (int i = 0; i < 4; i++) v[i] = ld_gpu(&P.scr->best[i * 32 + lane]);
                        ok = v[0].z == tag && v[1].z == tag && v[2].z == tag && v[3].z == tag;
                    } while (!__all_sync(0xffffffffu, ok) && ++it < (1u << 20));
#pragma unroll
                    for (int i = 1; i < 4; i++) if (v[i].x > v[0].x) v[0] = v[i];
                    const uint32_t key = __reduce_max_sync(0xffffffffu, v[0].x);
                    const uint32_t md = __reduce_or_sync(0xffffffffu, v[0].x == key ? v[0].y : 0u);
                    const int sel = 2047 - (int)(key & 2047u);
                    const uint4* xp = reinterpret_cast<const uint4*>(P.x + (size_t)sel * D_) + lane;
#pragma unroll
                    for (int i = 0; i < 4; i++) v[i] = __ldg(xp + i * 32);
                    const uint32_t m2 = __byte_perm(md, 0, 0x1010);
                    const float rs = rcp(bf_hi(md));
                    const uint32_t ord = (key >> 11) - 1u;
                    const float r = __uint_as_float(((ord & 0x8000u) ? (ord & 0x7FFFu) : (~ord & 0xFFFFu)) << 16);
                    sts128(sb + SM_MISC, (uint32_t)sel, __float_as_uint(round_bf16(rcp(1.0f + ex2(-r * LOG2E)))), epoch, 0u);
#pragma unroll
                    for (int i = 0; i < 4; i++) {
                        const uint32_t e0 = ln_pair(v[i].x, m2, rs), e1 = ln_pair(v[i].y, m2, rs), e2 = ln_pair(v[i].z, m2, rs), e3 = ln_pair(v[i].w, m2, rs);
                        const uint32_t xa = sb + SM_XS + i * 512 + (lane >> 2) * 64 + (lane & 3) * 4;
                        sts32(xa, __byte_perm(e0, e2, 0x5410)); sts32(xa + 16, __byte_perm(e0, e2, 0x7632));
                        sts32(xa + 32, __byte_perm(e1, e3, 0x5410)); sts32(xa + 48, __byte_perm(e1, e3, 0x7632));
                    }
                    TLP(elect, 25);
                    __syncwarp();
                    mbar_arrive_if(elect, bars + 8 * B_XS);
                }
            }
            if (aw == 2) {
                    const int l = lane < 24 ? lane : 0;
                    const float4* src = &get_acc()->cs[((l >> 3) * 16 + hp) * 24 + (l & 7)];
                    float4 v0, v1, v2;
                    uint4 v[4];
                    unsigned it = 0;
                    bool ok;
#pragma unroll 1
                    do {
                        v0 = ld_gpu(src); v1 = ld_gpu(src + 8); v2 = ld_gpu(src + 16);
                        ok = v0.w == 32.0f && v1.w == 32.0f && v2.w == 32.0f;
#pragma unroll
                        for (int i = 0; i < 4; i++) v[i] = ld_gpu(reinterpret_cast<const uint4*>(&P.scr->rows[rb * 256]) + i * 32 + lane);
#pragma unroll
                        for (int i = 0; i < 4; i++) ok = ok && v[i].y == epoch + 1u && v[i].w == epoch + 1u;
                    } while (!__all_sync(0xffffffffu, ok) && ++it < (1u << 20));
#pragma unroll
                    for (int i = 0; i < 4; i++) {
                        const uint32_t o = i * 256 + lane * 8;
                        sts64(sb + SM_MD + o, v[i].x, v[i].z);
                        sts64(sb + SM_RS + o, __float_as_uint(rcp(bf_hi(v[i].x))), __float_as_uint(rcp(bf_hi(v[i].z))));
                        const uint32_t h0 = hmul2(dup_lo(v[i].x), 0xBF00BF00u), h1 = hmul2(dup_lo(v[i].z), 0xBF00BF00u);
                        sts128(sb + SM_AX + o * 4, h0, h0 & 0xFFFFu, 0u, 0u);
                        sts128(sb + SM_AX + o * 4 + 16, h1, h1 & 0xFFFFu, 0u, 0u);
                    }
                    sts128(sb + SM_H + lane * 16, 0u, 0u, 0u, 0u); sts128(sb + SM_H + 512 + lane * 16, 0u, 0u, 0u, 0u);
                    const uint32_t e2 = __reduce_max_sync(0xffffffffu, l >= 16 ? __float_as_uint(v2.z) : 0u) >> 23;
                    sts32(sb + SM_MISC + 16, (uint32_t)min(max(187 - (int)((e2 + 1) >> 1), 1), 180) << 23);
                    float cc[8] = {v0.x, v0.y, v0.z, v1.x, v1.y, v1.z, v2.x, v2.y};
                    const uint32_t bx = sb + SM_BX + (l >> 3) * 1024;
#pragma unroll 1
                    for (int k = 0; k < 8; k++) {
                        uint32_t w[4];
#pragma unroll
                        for (int i = 0; i < 4; i++) {
                            w[i] = pack_bf16(cc[2 * i], cc[2 * i + 1]);
                            cc[2 * i] -= bf_lo(w[i]); cc[2 * i + 1] -= bf_hi(w[i]);
                        }
                        sts128(bx + k * 128 + (((l & 7) ^ k) * 16), w[0], w[1], w[2], w[3]);
                    }
                    fence_async_smem();
                    __syncwarp();
                    mbar_arrive_if(elect, bars + 8 * B_LN);
                    TLP(elect, 28);
                }
            mbar_wait(bars + 8 * B_XS, 0);
            if (ffn) {
                float a[8];
#pragma unroll
                for (int i = 0; i < 8; i++) a[i] = 0.f;
                TLP(elect, 40 + aw);
                gemv_run<256>(a, ng, nc % 3, (nc / 3) & 1, fbuf + (lane >> 4) * 2048 + (lane & 15) * 16, sb + SM_XS + g0 * 64 + (lane & 12) * 4, 64, fbar, sb + SM_MISC + 12,
                              [&](int m, int b) { issue(nc + m + 3, b); });
                TLP(elect, 44 + aw);
#pragma unroll 1
                for (int o = 4; o <= 8; o <<= 1) {
#pragma unroll
                    for (int i = 0; i < 8; i++) a[i] += __shfl_xor_sync(0xffffffffu, a[i], o);
                }
                if ((lane & 12) == 0) {
                    const uint32_t ga = sb + SM_GU + aw * 256 + (lane >> 4) * 128 + (lane & 3) * 32;
                    sts128(ga, __float_as_uint(a[0]), __float_as_uint(a[1]), __float_as_uint(a[2]), __float_as_uint(a[3]));
                    sts128(ga + 16, __float_as_uint(a[4]), __float_as_uint(a[5]), __float_as_uint(a[6]), __float_as_uint(a[7]));
                }
                nb_sync(NB_AUX, 96);
                if (warp == 9) {
                    const uint32_t ga = sb + SM_GU + lane * 4;
                    const float gg = round_bf16((ldsf(ga) + ldsf(ga + 256)) + ldsf(ga + 512));
                    const float uu = round_bf16((ldsf(ga + 128) + ldsf(ga + 384)) + ldsf(ga + 640));
                    asm volatile("st.shared.u16 [%0], %1;" :: "r"(sb + SM_H + (lane >> 3) * 256 + 112 + (lane & 7) * 2), "h"((uint16_t)pack_bf16(round_bf16(silu_f(gg)) * uu, 0.f)) : "memory");
                    fence_async_smem();
                }
                __syncwarp();
                TLP(tid == 288, 27);
            } else {
                nb_sync(NB_AUX, 96);
            }
            if (warp == 10 && elect_one()) load_wo(0);
            __syncwarp();
        }
        {
            TLP(tid == 288, 38);
            const int w4 = warp & 3;
            const uint32_t sp = sb + 212992 + w4 * 1536;
            auto send = [&](int h) {
                if (elect_one()) {
                    asm volatile("cp.reduce.async.bulk.global.shared::cta.bulk_group.add.noftz.f16 [%0], [%1], 1536;"
                                 :: "l"(&P.scr->kv[(hp * 8 + h * 4 + w4) * 96]), "r"(sp) : "memory");
                    asm volatile("cp.async.bulk.commit_group;" ::: "memory");
                }
            };
            float ya[4] = {0.f, 0.f, 0.f, 0.f}, yb[4] = {0.f, 0.f, 0.f, 0.f};
            uint4 g0[3];
#pragma unroll 1
            for (int h = 0; h < 2; h++) {
                {
                    float d[20];
                    const uint32_t alo = dlo(sb + SM_PHI + h * 32768, 16), vlo = dlo(sb + SM_V + h * 20480, 16);
#pragma unroll
                    for (int k = 0; k < 16; k++) {
                        if (!(k & 7)) { mbar_wait(bars + 8 * (k ? B_PHI : B_PH0) + 8 * h, 0); wgmma_fence(); }
                        wgmma_ss_n40(d, desc_from(alo + (k >> 2) * 512 + (k & 3) * 2, DH128), desc_from(vlo + (k >> 2) * 320 + (k & 3) * 2, DH128), k);
                        if ((k & 7) == 7) wgmma_commit();
                    }
#pragma unroll
                    for (int j = 0; j < 3; j++) g0[j] = ld_gpu(&P.scr->kv[(hp * 8 + w4) * 96 + j * 32 + lane]);
                    asm volatile("cp.async.bulk.wait_group.read 0;" ::: "memory");
                    __syncwarp();
                    const float ksc = ldsf(sb + SM_MISC + 16);
                    wgmma_wait<0>();
                    fence_regs(d);
#define U(x) pack_f16(d[x] * ksc, d[x + 1] * ksc)
                    sts128(sp + lane * 16, U(0), U(4), U(8), pack_f16(d[16], 1.0f));
                    sts128(sp + 512 + lane * 16, U(2), U(6), U(10), pack_f16(d[18], 1.0f));
                    sts128(sp + 1024 + lane * 16, U(12), U(14), 0u, 0x3C000000u);
#undef U
                    fence_async_smem();
                    __syncwarp();
                    send(h);
                    TLP(tid == 256, 30 + h);
                    nb_sync(NB_KV, 128);
                    if (h) break;
                    if (warp == 8 && elect_one()) {
                        mbar_expect_tx(bars + 8 * B_X, 32768);
                        tma_2d(sb, &tmX2, bars + 8 * B_X, (hp >> 1) * 128, rb * 256 + (hp & 1) * 128);
                        tma_2d(sb + 16384, &tmX2, bars + 8 * B_X, (hp >> 1) * 128 + 64, rb * 256 + (hp & 1) * 128);
                    }
                    __syncwarp();
                }
                if (blockIdx.x < 112) {
                    const uint32_t hlo = dlo(sb + SM_H, 256);
                    mbar_wait(bars + 8 * B_DN, 0);
                    mbar_wait(bars + 8 * (B_DN + 1), 0);
                    wgmma_fence();
#pragma unroll 2
                    for (int k = 0; k < 16; k++) {
                        wgmma_ss_n8_ta(yb, desc_from(dlo(sb + 6 * 16384, 16) + k * 128, DH128), desc_from(hlo + (k & 1) * 32 + 7 - (k >> 1), 8), k);
                        wgmma_ss_n8_ta(ya, desc_from(dlo(sb + 4 * 16384, 16) + k * 128, DH128), desc_from(hlo + (k & 1) * 32 + 7 - (k >> 1), 8), k);
                    }
                    wgmma_commit();
                    wgmma_wait<0>();
                    fence_regs(ya); fence_regs(yb);
                    if (warp == 8) {
                        nb_sync(NB_KV, 128);
                        if (elect_one()) { load_wo(1); load_wo(2); }
                        __syncwarp();
                    } else {
                        nb_arrive(NB_KV, 128);
                    }
                    TLP(tid == 288, 29);
                }
            }
            const float kus = __uint_as_float((254u << 23) - lds32(sb + SM_MISC + 16));
            kv_gather<1>(g0, &P.scr->kv[(hp * 8 + w4) * 96 + lane], sb + SM_KVOP + w4 * 256, lane, kus);
            mbar_arrive_if(elect, bars + 8 * B_KV);
            if (warp == 8 && elect_one()) { load_wo(4); if (blockIdx.x < 112) { load_wo(3); load_wo(5); } }
            __syncwarp();
            asm volatile("cp.async.bulk.wait_group.read 0;" ::: "memory");
            __syncwarp();
            if (blockIdx.x < 112) {
#define U(x) __float_as_uint(x)
                sts128(sp + lane * 16, U(ya[0]), U(ya[1]), U(ya[2]), U(1.0f));
                sts128(sp + 512 + lane * 16, U(ya[3]), U(yb[0]), U(yb[1]), U(1.0f));
                sts128(sp + 1024 + lane * 16, U(yb[2]), U(yb[3]), 0u, U(1.0f));
#undef U
                fence_async_smem();
                __syncwarp();
                if (elect_one()) {
                    asm volatile("cp.reduce.async.bulk.global.shared::cta.bulk_group.add.f32 [%0], [%1], 1536;"
                                 :: "l"(&get_acc()->y[((blockIdx.x & 3) * 4 + w4) * 96]), "r"(sp) : "memory");
                    asm volatile("cp.async.bulk.commit_group;" ::: "memory");
                }
                __syncwarp();
            }
            if (w4 >= 2) {
                uint4 g1[6];
#pragma unroll
                for (int j = 0; j < 6; j++) g1[j] = make_uint4(0, 0, 0, 0);
                kv_gather<2>(g1, &P.scr->kv[(hp * 8 + 2 * w4) * 96 + lane], sb + SM_KVOP - 5120 + (w4 - 2) * 512, lane, kus);
                mbar_arrive_if(lane < 2, bars + 8 * (B_KV + 1));
            }
            asm volatile("cp.async.bulk.wait_group.read 0;" ::: "memory");
        }
        if (warp == 8) {
            if (elect_one()) {
                uint4 cnt;
                mbar_wait(bars + 8 * B_O, 0);
#pragma unroll
                for (int i = 0; i < 16; i++) {
                    if (!(i & 3)) cnt = make_uint4(0, 0, 0, 0);
                    unsigned it = 0;
#pragma unroll 1
                    while (((i & 3) == 0 ? cnt.x : ((i & 3) == 1 ? cnt.y : ((i & 3) == 2 ? cnt.z : cnt.w))) < 2u && ++it < (1u << 20))
                        cnt = ld_gpu(reinterpret_cast<const uint4*>(&P.scr->cnt_o[rb * 128 + (hp & 1) * 64 + (i >> 3) * 32 + (i & 4)]));
                    if (PFENCE) asm volatile("fence.proxy.async.global;" ::: "memory");
                    if ((i & 3) == 0 && i < 12) TL(i == 0 ? 21 : (i == 4 ? 34 : 36));
                    if (i == 4 || i > 5) mbar_wait(bars + 8 * (B_SD + max(i - 5, 0)), 0);
                    load_o(i);
                    if (i == 3) load_wo(6);
                    if (i >= 5 && i < 14) load_wo(i + 2);
                }
            }
        } else if (warp < 11) {
            if (elect_one()) {
#pragma unroll
                for (int w = 0; w < 2; w++) {
                    mbar_wait(bars + 8 * (B_OW + 2 * aw + w), 0);
                    asm volatile("cp.async.bulk.tensor.2d.global.shared::cta.bulk_group [%0, {%2, %3}], [%1];"
                                 :: "l"(&tmOs), "r"(sb + SM_OS + w * 8192), "r"(aw * 512 + hp * 32), "r"(rb * 256 + w * 128) : "memory");
                    asm volatile("cp.async.bulk.commit_group;" ::: "memory");
                }
#pragma unroll
                for (int w = 0; w < 2; w++) {
                    if (w) asm volatile("cp.async.bulk.wait_group 0;" ::: "memory"); else asm volatile("cp.async.bulk.wait_group 1;" ::: "memory");
                    asm volatile("fence.proxy.async.global;" ::: "memory");
                    asm volatile("red.relaxed.gpu.global.add.u32 [%0], 1;" :: "l"(&P.scr->cnt_o[rb * 128 + w * 64 + aw * 32 + (hp >> 1)]) : "memory");
                }
                asm volatile("mbarrier.arrive.shared::cta.b64 _, [%0];" :: "r"(bars + 8 * B_OS) : "memory");
            }
        } else if (warp == 11) {
            const uint4 misc = lds128(sb + SM_MISC);
            if ((int)(misc.x >> 7) == rb * 2 + (hp & 1)) {
                float y[4] = {0.f, 0.f, 0.f, 0.f};
#pragma unroll 1
                for (int rep = 0; rep < 4; rep++) {
                    const float4* yp = &get_acc()->y[(rep * 4 + (lane >> 3)) * 96 + (hp >> 3) * 32 + (lane & 7) * 4 + ((hp >> 1) & 3)];
                    float4 u, v;
                    unsigned it = 0;
#pragma unroll 1
                    do { u = ld_gpu(yp); v = ld_gpu(yp + 32); } while (!__all_sync(0xffffffffu, u.w == 28.0f && v.w == 28.0f) && ++it < (1u << 20));
                    if (hp & 8) { y[0] += u.y; y[1] += v.x; y[2] += u.z; y[3] += v.y; } else { y[0] += u.x; y[1] += u.z; y[2] += u.y; y[3] += v.x; }
                }
                const uint32_t sg = __byte_perm(misc.y, 0, 0x3232), ya = sb + SM_Y + ((lane >> 3) * 16 + (lane & 7)) * 2;
                const uint32_t w0 = hmul2(pack_bf16(y[0], y[1]), sg), w1 = hmul2(pack_bf16(y[2], y[3]), sg);
                asm volatile("st.shared.u16 [%0], %1;" :: "r"(ya), "h"((uint16_t)w0) : "memory");
                asm volatile("st.shared.u16 [%0], %1;" :: "r"(ya + 16), "h"((uint16_t)(w0 >> 16)) : "memory");
                asm volatile("st.shared.u16 [%0], %1;" :: "r"(ya + 128), "h"((uint16_t)w1) : "memory");
                asm volatile("st.shared.u16 [%0], %1;" :: "r"(ya + 144), "h"((uint16_t)(w1 >> 16)) : "memory");
                __syncwarp();
                if (lane < 16) {
                    const uint4 xc = __ldg(reinterpret_cast<const uint4*>(P.x + (size_t)misc.x * D_ + (hp >> 1) * 128) + lane);
                    const uint32_t m2 = __byte_perm(lds32(sb + SM_MD + (misc.x & 255u) * 4), 0, 0x1010);
                    const float r = ldsf(sb + SM_RS + (misc.x & 255u) * 4);
                    const uint4 yv = lds128(sb + SM_Y + lane * 16);
                    sts128(sb + SM_Y + lane * 16, silu_pair(hadd2(ln_pair(xc.x, m2, r), yv.x)), silu_pair(hadd2(ln_pair(xc.y, m2, r), yv.y)),
                           silu_pair(hadd2(ln_pair(xc.z, m2, r), yv.z)), silu_pair(hadd2(ln_pair(xc.w, m2, r), yv.w)));
                    sts128(sb + SM_Y + 256 + lane * 16, xc.x, xc.y, xc.z, xc.w);
                }
                __syncwarp();
                mbar_arrive_if(elect, bars + 8 * B_Y);
                TLP(elect, 39);
            }
        }
    } else {
        const int wg = warp >> 2, w4 = warp & 3, g = lane >> 2;
        nb_sync(0, NTHREADS);
        asm volatile("setmaxnreg.inc.sync.aligned.u32 224;");
        TLP(tid == 0, 1);
        const int row0 = wg * 128 + w4 * 16 + g;
        float pq0[16], pq1[16];
        float rs[4];
        uint32_t f2[8], f3[8], q0[8], q1[8], q2[8], q3[8];
        float qa[16], qb[16];
        const uint32_t wlo = dlo(sb + SM_WPHI, 16);
        const uint32_t sw0 = (uint32_t)(((w4 * 2) ^ (lane & 7)) * 16), sw1 = sw0 ^ 16u;
        {
            float acc0[96], acc1[96];
            {
                const uint32_t alo0 = dlo(sb + wg * 16384, 16), blo0 = dlo(sb + 32768, 8192);
                {
#pragma unroll
                    for (int k = 0; k < 4; k++) {
                        if (k == 0) asm volatile("cp.async.wait_group 1;" ::: "memory");
                        if (k == 2) { wgmma_commit(); asm volatile("cp.async.wait_group 0;" ::: "memory"); }
                        if (!(k & 1)) { fence_async_smem(); nb_sync(NB_STAG, 256); wgmma_fence(); }
                        if (k == 0) { TLP(tid == 0, 2); TLG(tid == 0, 49); }
                        wgmma_ss_n192_tb(acc0, desc_from(alo0 + k * 2, DH128), desc_from(blo0 + k * 128, DH128), k);
                        wgmma_ss_n192_tb(acc1, desc_from(alo0 + 512 + k * 2, DH128), desc_from(blo0 + k * 128, DH128), k);
                    }
                    wgmma_commit();
                }
                int s = 1, ph = 0, ps = 0;
#pragma unroll 1
                for (int ks = 1; ks < 16; ks++) {
                    const bool hold = wg && ks == 15;
                    if (hold) {
                        wgmma_wait<0>();
                        mbar_arrive_if(elect, bars + 8 * (B_EMPTY + ps));
                        nb_sync(NB_LEAD, 256);
                    }
                    mbar_wait(bars + 8 * (B_FULL + s), ph);
                    const uint32_t alo = alo0 + s * (STAGE >> 4), blo = blo0 + s * (STAGE >> 4);
                    wgmma_fence();
#pragma unroll
                    for (int k = 0; k < 4; k++) {
                        if (k == SARR && !wg && ks == 15) nb_arrive(NB_LEAD, 256);
                        wgmma_ss_n192_tb(acc0, desc_from(alo + k * 2, DH128), desc_from(blo + k * 128, DH128), 1);
                        wgmma_ss_n192_tb(acc1, desc_from(alo + 512 + k * 2, DH128), desc_from(blo + k * 128, DH128), 1);
                        if (k == 0) {
                            wgmma_commit();
                            wgmma_wait<1>();
                            mbar_arrive_if(elect && !hold, bars + 8 * (B_EMPTY + ps));
                        }
                    }
                    wgmma_commit();
                    ps = s;
                    if (++s == 3) { s = 0; ph ^= 1; }
                }
            }
            mbar_wait(bars + 8 * B_LN, 0);
            wgmma_fence();
            wgmma_ss_n192_tb(acc0, desc_from(dlo(sb + SM_AX + wg * 2048, 0), 128u >> 4), desc_from(dlo(sb + SM_BX, 1024), 1u << 30), 1);
            wgmma_ss_n192_tb(acc1, desc_from(dlo(sb + SM_AX + wg * 2048 + 1024, 0), 128u >> 4), desc_from(dlo(sb + SM_BX, 1024), 1u << 30), 1);
            wgmma_commit();
            mbar_wait(bars + 8 * (B_EMPTY + 2), 0);
            mbar_wait(bars + 8 * B_WPHI, 0);
            {
                uint32_t md[4];
#pragma unroll
                for (int i = 0; i < 4; i++) {
                    const int r = row0 + (i >> 1) * 64 + (i & 1) * 8;
                    md[i] = __byte_perm(lds32(sb + SM_MD + r * 4), 0, 0x3232);
                    rs[i] = ldsf(sb + SM_RS + r * 4);
                }
                const uint32_t zb = sb + SM_V + wg * 10240 + (lane >> 4) * 5120 + 4096 + (lane & 7) * 128 + (sw0 ^ ((lane & 8) * 2));
                stsm_t(zb, md[0], md[1], md[2], md[3]);
                stsm_t(zb + 20480, md[0], md[1], md[2], md[3]);
            }
            wgmma_wait<0>();
            fence_regs(acc0); fence_regs(acc1);
            TLP(tid == 0, 3); TLG(tid == 0, 50);
            const uint32_t vb = sb + SM_V + wg * 10240 + lane * 128;
            uint32_t f0[8], f1[8], v[8];
            pack_head<64>(acc0, v); stsm_t(vb + sw0, v[0], v[2], v[4], v[6]); stsm_t(vb + sw1, v[1], v[3], v[5], v[7]);
            pack_head<64>(acc1, v); stsm_t(vb + 5120 + sw0, v[0], v[2], v[4], v[6]); stsm_t(vb + 5120 + sw1, v[1], v[3], v[5], v[7]);
#pragma unroll
            for (int i = 32; i < 48; i++) { asm volatile("" : "+f"(acc0[i]) :: "memory"); asm volatile("" : "+f"(acc1[i]) :: "memory"); }
            pack_head<32>(acc0, f0); pack_head<32>(acc1, f1);
            wgmma_fence();
            feat_mma(pq0, f0, wlo); feat_mma(pq1, f1, wlo);
            wgmma_commit();
            pack_head<80>(acc0, v); stsm_t(vb + 20480 + sw0, v[0], v[2], v[4], v[6]); stsm_t(vb + 20480 + sw1, v[1], v[3], v[5], v[7]);
            pack_head<80>(acc1, v); stsm_t(vb + 25600 + sw0, v[0], v[2], v[4], v[6]); stsm_t(vb + 25600 + sw1, v[1], v[3], v[5], v[7]);
            pack_head<48>(acc0, f2); pack_head<48>(acc1, f3);
            pack_head<0>(acc0, q0); pack_head<0>(acc1, q1);
#pragma unroll
            for (int i = 0; i < 16; i++) { qa[i] = acc0[16 + i]; qb[i] = acc1[16 + i]; }
            fence_regs(f2); fence_regs(f3); fence_regs(q0); fence_regs(q1);
            wgmma_wait<0>();
            fence_regs(pq0); fence_regs(pq1); fence_regs(f0); fence_regs(f1);
            mbar_arrive_if(elect, bars + 8 * B_T);
            TLP(tid == 0, 4);
        }
#pragma unroll 1
        for (int h = 0; h < 2; h++) {
            const uint32_t pb = sb + SM_PHI + wg * 16384 + lane * 128 + h * 32768;
            key_head(pq0, pq1, rs, pb + sw0, pb + sw1);
            wgmma_fence();
            feat_mma(pq0, f2, wlo + 128 - h * 128); feat_mma(pq1, f3, wlo + 128 - h * 128);
            wgmma_commit();
            fence_async_smem();
            __syncwarp();
            mbar_arrive_if(elect, bars + 8 * (B_PHI + h));
            mbar_arrive_if(elect && !wg, bars + 8 * (B_PH0 + h));
            TLP(tid == 0, 6 + 2 * h);
            mbar_wait(bars + 8 * B_T, 0);
            wgmma_wait<0>();
            fence_regs(pq0); fence_regs(pq1); fence_regs(f2); fence_regs(f3);
#pragma unroll
            for (int j = 0; j < 8; j++) { f2[j] = q0[j]; f3[j] = q1[j]; }
            fence_regs(f2); fence_regs(f3);
        }
#pragma unroll
        for (int j = 0; j < 8; j++) { q2[j] = pack_bf16(qa[2 * j], qa[2 * j + 1]); q3[j] = pack_bf16(qb[2 * j], qb[2 * j + 1]); }
        const int orow = (hp & 1) * 128 + wg * 64 + w4 * 16 + (lane >> 4);
        const size_t goff = (size_t)(rb * 256 + orow) * D_ + (hp >> 1) * 128 + (lane & 15) * 8;
        uint4 gv[8], xv[8];
#pragma unroll
        for (int i = 0; i < 8; i++) xv[i] = make_uint4(0, 0, 0, 0);
#pragma unroll
        for (int i = 0; i < GSPLIT2; i++) gv[i] = make_uint4(0, 0, 0, 0);
        const uint32_t rowc = sb + ((lane >> 3) & 1) * 16384 + (wg * 64 + w4 * 16 + (lane >> 4)) * 128;
        {
            const uint32_t od = sb + SM_OS + (wg * 128 + w4 * 16) * 64 + lane * 16;
#pragma unroll 1
            for (int h = 0; h < 2; h++) {
                uint32_t pa[8], na[8], pb[8], nb[8];
                features(pq0, pq1, rs, pa, na, pb, nb);
                TLP(tid == 0, 16 + h);
                if (h == 0) {
                    wgmma_fence();
                    feat_mma(pq0, q2, wlo + 128); feat_mma(pq1, q3, wlo + 128);
                    wgmma_commit();
                    wgmma_wait<0>();
                    fence_regs(pq0); fence_regs(pq1); fence_regs(q2); fence_regs(q3);
                    TLP(tid == 0, 18);
                } else {
#pragma unroll
                    for (int i = GSPLIT; i < GSPLIT2; i++) { gv[i] = xv[i]; gate_item(gv[i], sb, orow + 2 * i); }
                    TLP(tid == 0, 10);
                }
                {
                    float d0[20], e0[20], d1[20], e1[20];
                    const uint32_t klo = dlo(sb + SM_KVOP - h * 5120, 128);
                    fence_regs(pa); fence_regs(na); fence_regs(pb); fence_regs(nb);
                    mbar_wait(bars + 8 * (B_KV + h), 0);
                    TLP(tid == 0, 32 + h);
                    wgmma_fence();
                    o_mma(d0, e0, pa, na, klo);
                    wgmma_commit();
                    o_mma(d1, e1, pb, nb, klo);
                    wgmma_commit();
                    if (h) mbar_wait(bars + 8 * B_OS, 0);
                    wgmma_wait<1>();
                    fence_regs(d0); fence_regs(e0); fence_regs(pa); fence_regs(na);
                    o_store(d0, e0, od);
                    wgmma_wait<0>();
                    fence_regs(d1); fence_regs(e1); fence_regs(pb); fence_regs(nb);
                    o_store(d1, e1, od + 4096);
                    fence_async_smem();
                    __syncwarp();
                    mbar_arrive_if(elect, bars + 8 * (B_OW + 2 * h + wg));
                    if (!h) {
                    mbar_wait(bars + 8 * B_X, 0);
#pragma unroll
                    for (int i = 0; i < 8; i++) xv[i] = lds128(rowc + i * 256 + (((lane & 7) ^ ((2 * i + (lane >> 4)) & 7)) * 16));
#pragma unroll
                    for (int i = 0; i < GSPLIT; i++) { gv[i] = xv[i]; gate_item(gv[i], sb, orow + 2 * i); }
                    __syncwarp();
                    }
                    mbar_arrive_if(elect, bars + 8 * (B_O + h));
                }
                TLP(tid == 0, 9 + 2 * h);
            }
        }
        float ghr[8], ghm[8];
        float acc[64];
        {
            const uint32_t alo0 = dlo(sb + wg * 8192, 16), blo0 = dlo(sb, 8192);
#pragma unroll
            for (int i = 0; i < 16; i++) {
                const uint32_t alo = alo0 + o_slot(i) * 1024, blo = blo0 + wo_slot(i) * 1024;
                mbar_wait(bars + 8 * (B_OF + i), 0);
                if (i == OSTAG && wg == 0) nb_sync(NB_STAG, 256);
                wgmma_fence();
#pragma unroll
                for (int k = 0; k < 4; k++) {
                    if (i == 15 && k == OARR && wg) nb_arrive(NB_STAG, 256);
                    wgmma_ss_n128_tb(acc, desc_from(alo + k * 2, DH128), desc_from(blo + k * 128, DH128), k | i);
                    if (k == OREL) {
                        if (i > 0 && i < 12) {
                            wgmma_commit();
                            wgmma_wait<1>();
                            mbar_arrive_if(elect, bars + 8 * (B_SD + i - 1));
                        }
                    }
                }
                wgmma_commit();
                if (i == 0) { TLP(tid == 0, 12); TLG(tid == 0, 51); }
                if (i == 0) {
#pragma unroll
                    for (int q = GSPLIT2; q < 8; q++) { ghr[q] = 0.5f * ldsf(sb + SM_RS + (orow + 2 * q) * 4); ghm[q] = -bf_lo(lds32(sb + SM_MD + (orow + 2 * q) * 4)) * ghr[q]; }
                }
                static_assert(2 * (8 - GSPLIT2) <= 16 - GST, "");
                if (i >= GST && GSPLIT2 + (i - GST) / 2 < 8) {
                    const int q = GSPLIT2 + (i - GST) / 2;
                    if ((i - GST) & 1) { gv[q].z = gate_pair(xv[q].z, ghr[q], ghm[q]); gv[q].w = gate_pair(xv[q].w, ghr[q], ghm[q]); asm volatile("" : "+r"(gv[q].z), "+r"(gv[q].w) :: "memory"); }
                    else { gv[q].x = gate_pair(xv[q].x, ghr[q], ghm[q]); gv[q].y = gate_pair(xv[q].y, ghr[q], ghm[q]); asm volatile("" : "+r"(gv[q].x), "+r"(gv[q].y) :: "memory"); }
                }
            }
        }
        wgmma_wait<0>();
        fence_regs(acc);
        TLP(tid == 0, 13); TLG(tid == 0, 52);
        {
            const uint32_t stg = sb + (wg * 64 + w4 * 16) * 128;
            const int rr = lane & 7;
#pragma unroll
            for (int c = 0; c < 4; c++) {
                const uint32_t a0 = stg + (c >> 1) * 16384 + rr * 128 + ((((c & 1) * 4 + (lane >> 3)) ^ rr) * 16);
                stsm(a0, pack_bf16(acc[c * 16 + 0], acc[c * 16 + 1]), pack_bf16(acc[c * 16 + 4], acc[c * 16 + 5]),
                     pack_bf16(acc[c * 16 + 8], acc[c * 16 + 9]), pack_bf16(acc[c * 16 + 12], acc[c * 16 + 13]));
                stsm(a0 + 1024, pack_bf16(acc[c * 16 + 2], acc[c * 16 + 3]), pack_bf16(acc[c * 16 + 6], acc[c * 16 + 7]),
                     pack_bf16(acc[c * 16 + 10], acc[c * 16 + 11]), pack_bf16(acc[c * 16 + 14], acc[c * 16 + 15]));
            }
            __syncwarp();
#pragma unroll
            for (int i = 0; i < 8; i++) {
                const uint4 sv = lds128(rowc + i * 256 + (((lane & 7) ^ ((2 * i + (lane >> 4)) & 7)) * 16));
                uint4 o;
                o.x = hadd2(xv[i].x, hmul2(sv.x, gv[i].x)); o.y = hadd2(xv[i].y, hmul2(sv.y, gv[i].y));
                o.z = hadd2(xv[i].z, hmul2(sv.z, gv[i].z)); o.w = hadd2(xv[i].w, hmul2(sv.w, gv[i].w));
                *reinterpret_cast<uint4*>(P.out + goff + (size_t)i * 2 * D_) = o;
            }
            const uint32_t sel = lds32(sb + SM_MISC);
            if ((int)(sel >> 4) == rb * 16 + (orow >> 4)) {
                mbar_wait(bars + 8 * B_Y, 0);
                if ((sel & 1u) == (uint32_t)(lane >> 4)) {
                    const int i = (sel & 15u) >> 1;
                    const uint4 sv = lds128(rowc + i * 256 + (((lane & 7) ^ (sel & 7u)) * 16));
                    const uint4 gq = lds128(sb + SM_Y + (lane & 15) * 16), xq = lds128(sb + SM_Y + 256 + (lane & 15) * 16);
                    *reinterpret_cast<uint4*>(P.out + goff + (size_t)i * 2 * D_) = make_uint4(hadd2(xq.x, hmul2(sv.x, gq.x)), hadd2(xq.y, hmul2(sv.y, gq.y)), hadd2(xq.z, hmul2(sv.z, gq.z)), hadd2(xq.w, hmul2(sv.w, gq.w)));
                }
            }
        }
        TLG(tid == 0, 53);
        if (tid == 0) { TL(14); TL_DUMP(); }
        if (blockIdx.x == 0 && tid == 0) asm volatile("st.relaxed.gpu.global.u32 [%0], %1;" :: "l"(&P.scr->epoch), "r"(lds32(sb + SM_MISC + 8) + 1u) : "memory");
    }
}

typedef CUresult (*PFN_encodeTiled)(CUtensorMap*, CUtensorMapDataType, cuuint32_t, void*, const cuuint64_t*, const cuuint64_t*,
                                    const cuuint32_t*, const cuuint32_t*, CUtensorMapInterleave, CUtensorMapSwizzle,
                                    CUtensorMapL2promotion, CUtensorMapFloatOOBfill);

void make_map(PFN_encodeTiled fn, CUtensorMap* m, const void* ptr, int rank, const cuuint64_t* dims, const cuuint64_t* strides, const cuuint32_t* box, CUtensorMapSwizzle sw) {
    const cuuint32_t es[5] = {1, 1, 1, 1, 1};
    fn(m, CU_TENSOR_MAP_DATA_TYPE_BFLOAT16, rank, const_cast<void*>(ptr), dims, strides, box, es, CU_TENSOR_MAP_INTERLEAVE_NONE,
       sw, CU_TENSOR_MAP_L2_PROMOTION_L2_256B, CU_TENSOR_MAP_FLOAT_OOB_FILL_NONE);
}
void make_2d(PFN_encodeTiled fn, CUtensorMap* m, const void* ptr, uint64_t rows, uint64_t cols, uint32_t box_rows, uint32_t box_cols, CUtensorMapSwizzle sw) {
    const cuuint64_t gd[2] = {cols, rows}, gs[1] = {cols * 2};
    const cuuint32_t bd[2] = {box_cols, box_rows};
    make_map(fn, m, ptr, 2, gd, gs, bd, sw);
}

}

extern "C" void kernel_launch(void* const* d_in, const int* in_sizes, int n_in, void* d_out, int out_size) {
    (void)in_sizes; (void)n_in; (void)out_size;
    static PFN_encodeTiled fn = nullptr;
    static void* o_ptr = nullptr;
    static void* scr_ptr = nullptr;
    static void* tl_ptr = nullptr;
    if (!fn) {
        void* p = nullptr;
        cudaDriverEntryPointQueryResult st;
        cudaGetDriverEntryPoint("cuTensorMapEncodeTiled", &p, cudaEnableDefault, &st);
        fn = (PFN_encodeTiled)p;
        cudaGetSymbolAddress(&o_ptr, g_o);
        cudaGetSymbolAddress(&scr_ptr, g_scr);
        cudaFuncSetAttribute(fused_kernel, cudaFuncAttributeMaxDynamicSharedMemorySize, SM_TOTAL);
    }
    CUtensorMap tmX, tmW, tmPhi, tmWo, tmO, tmX2, tmOs;
    SideMaps tmS;
    make_2d(fn, &tmX, d_in[0], S_, D_, 256, 64, CU_TENSOR_MAP_SWIZZLE_128B);
    {
        const cuuint64_t gd[3] = {1024, 1024, 3}, gs[2] = {6144, 2048};
        const cuuint32_t bd[3] = {64, 64, 3};
        make_map(fn, &tmW, d_in[1], 3, gd, gs, bd, CU_TENSOR_MAP_SWIZZLE_128B);
    }
    make_2d(fn, &tmS.wc, d_in[1], D_, 3 * D_, 32, 64, CU_TENSOR_MAP_SWIZZLE_NONE);
    make_2d(fn, &tmPhi, d_in[2], 1024, 32, 64, 32, CU_TENSOR_MAP_SWIZZLE_64B);
    make_2d(fn, &tmS.wg, d_in[6], D_, F_, 32, 32, CU_TENSOR_MAP_SWIZZLE_NONE);
    make_2d(fn, &tmS.wu, d_in[7], D_, F_, 32, 32, CU_TENSOR_MAP_SWIZZLE_NONE);
    {
        const cuuint64_t gd[3] = {64, F_, 16}, gs[2] = {2048, 128};
        const cuuint32_t bd[3] = {64, 32, 8};
        make_map(fn, &tmS.wd8, d_in[8], 3, gd, gs, bd, CU_TENSOR_MAP_SWIZZLE_128B);
    }
    {
        const cuuint64_t gd[4] = {64, 64, 16, 16}, gs[3] = {2048, 64 * 2048, 128};
        const cuuint32_t bd[4] = {64, 32, 2, 2};
        make_map(fn, &tmWo, d_in[3], 4, gd, gs, bd, CU_TENSOR_MAP_SWIZZLE_128B);
    }
    make_2d(fn, &tmO, o_ptr, S_, D_, 128, 64, CU_TENSOR_MAP_SWIZZLE_128B);
    make_2d(fn, &tmOs, o_ptr, S_, D_, 128, 32, CU_TENSOR_MAP_SWIZZLE_NONE);
    make_2d(fn, &tmX2, d_in[0], S_, D_, 128, 64, CU_TENSOR_MAP_SWIZZLE_128B);
    Params P;
    P.x = (const __nv_bfloat16*)d_in[0];
    P.wr = (const __nv_bfloat16*)d_in[5];
    P.wqkv = (const __nv_bfloat16*)d_in[1];
    P.wg = (const __nv_bfloat16*)d_in[6];
    P.wu = (const __nv_bfloat16*)d_in[7];
    P.wd = (const __nv_bfloat16*)d_in[8];
    P.wo = (const __nv_bfloat16*)d_in[3];
    P.out = (__nv_bfloat16*)d_out;
    P.scr = (Scratch*)scr_ptr;
    P.tl = (unsigned long long*)tl_ptr;
    cudaLaunchConfig_t cfg = {};
    cfg.gridDim = dim3(NCTA); cfg.blockDim = dim3(NTHREADS); cfg.dynamicSmemBytes = SM_TOTAL; cfg.stream = cudaStreamPerThread;
    cudaLaunchAttribute at[1];
    at[0].id = cudaLaunchAttributeCooperative; at[0].val.cooperative = 1;
    cfg.attrs = at; cfg.numAttrs = 1;
    cudaLaunchKernelEx(&cfg, fused_kernel, P, tmX, tmW, tmX2, tmS, tmPhi, tmWo, tmO, tmOs);
}
```
